```python
import torch

def _softmax(x, axis=-1):
    return torch.softmax(x, dim=axis)

def _gelu(x):
    return torch.nn.functional.gelu(x, approximate='tanh')

def _silu(x):
    return torch.nn.functional.silu(x)

def _sigmoid(x):
    return torch.sigmoid(x)

def _layernorm(x, axis=-1, eps=1e-05):
    m = x.mean(dim=axis, keepdim=True)
    v = x.var(dim=axis, keepdim=True, unbiased=False)
    return (x - m) / torch.sqrt(v + eps)

def _scatter_add(tgt, idx, src, axis=0):
    return tgt.clone().index_add_(axis, idx, src)

def _segment_sum(src, seg, n):
    out = torch.zeros((n,) + src.shape[1:], dtype=src.dtype)
    return out.index_add_(0, seg, src)

def _pad(x, pw):
    flat = tuple((v for pair in reversed(pw) for v in pair))
    return torch.nn.functional.pad(x, flat)
kernel_name = 'standalone__molecular_angular_painn__graph'

def setup_inputs():

    _w = lambda a: (lambda t: t.to(torch.bfloat16) if t.is_floating_point() else t)(torch.as_tensor(a))
    N, deg, D = (50000, 16, 64)
    n_rbf = max(16, 4)
    E = N * deg
    cutoff = 5.0
    freqs = (torch.arange(1, n_rbf + 1) * torch.pi / cutoff).to(float)
    return {'sv': _w((lambda *s: torch.randn(*s, dtype=torch.bfloat16) * 0.4)(N, 4, D) * 0.3), 'pos': _w((lambda *s: torch.randn(*s, dtype=torch.bfloat16) * 3.2)(N, 3) * 1.2), 'src': _w((lambda lo, hi, *s: torch.randint(lo, hi, s))(0, N, E).to(torch.int64)), 'dst': _w((lambda lo, hi, *s: torch.randint(lo, hi, s))(0, N, E).to(torch.int64)), 'freqs': _w(freqs), 'w_phi1': _w((lambda *s: torch.randn(*s, dtype=torch.bfloat16) * 3.2)(D, D) / D ** 0.5), 'w_phi2': _w((lambda *s: torch.randn(*s, dtype=torch.bfloat16) * 3.2)(D, 3 * D) / D ** 0.5), 'w_rbf': _w((lambda *s: torch.randn(*s, dtype=torch.bfloat16) * 3.2)(n_rbf, 3 * D) / n_rbf ** 0.5)}

def reference(sv, pos, src, dst, freqs, w_phi1, w_phi2, w_rbf):
    N, _, D = sv.shape
    E = src.shape[0]
    PI, cutoff = (3.141592653589793, 5.0)
    s, v = (sv[:, 0, :].clone(), sv[:, 1:, :].clone())
    r_vec = pos[src] - pos[dst]
    d = torch.sqrt((r_vec * r_vec).sum(-1) + 1e-08)
    r_hat = r_vec / d[:, None]
    rbf = torch.sin(d[:, None] * freqs[None, :]) / d[:, None]
    fcut = 0.5 * (torch.cos(PI * d / cutoff) + 1.0)
    fcut = torch.where(d < cutoff, fcut, 0.0 * d)
    Wf = rbf @ w_rbf * fcut[:, None]
    phi = (_silu(s @ w_phi1) @ w_phi2)[src]
    m = phi * Wf
    m_s, m_vv, m_vr = (m[:, :D].clone(), m[:, D:2 * D].clone(), m[:, 2 * D:].clone())
    ds = _segment_sum(m_s, dst, N)
    dv_e = m_vv[:, None, :] * v[src] + m_vr[:, None, :] * r_hat[:, :, None]
    dv = _segment_sum(dv_e.reshape(E, 3 * D), dst, N).reshape(N, 3, D)
    return sv + torch.concatenate([ds[:, None, :], dv], axis=1)
```

```cpp
#include <cuda_runtime.h>
#include <cuda_bf16.h>
#include <stdint.h>

namespace {

constexpr int REG_C = 224;
constexpr int RESV = 48;
constexpr int PDELAY = 300;
constexpr int THREADS = 512;
constexpr int MAXG = 136;
constexpr int TILE = 64;
constexpr int ROWB = 512;
constexpr int SLOTB = TILE * ROWB;
constexpr int NSLOT = 4;
constexpr int CAP = 1264;
constexpr int MAXNPC = 480;
constexpr int MAXE = 1 << 20;

constexpr int W1_OFF = 0;
constexpr int W2_OFF = 8192;
constexpr int WR_OFF = 32768;
constexpr int RING_OFF = 38912;
constexpr int SIDE_OFF = RING_OFF + NSLOT * SLOTB;
constexpr int REC_OFF = SIDE_OFF + SLOTB;
constexpr int HEAD_OFF = REC_OFF + 16 * CAP;
constexpr int START_OFF = HEAD_OFF + 2048;
constexpr int RIDX_OFF = START_OFF + 4096;
constexpr int BAR_OFF = RIDX_OFF + 2048;
constexpr int MISC_OFF = BAR_OFF + 8 * 46;
constexpr int SMEM_BYTES = MISC_OFF + 192 + MAXG;
constexpr int TABLE_MAXN = 50176;
constexpr int STAGE_OFF = TABLE_MAXN * 4;
constexpr int SCNT_OFF = STAGE_OFF + MAXG * 128;
constexpr int OVL_OFF = MISC_OFF + 192;
constexpr int OPOS_OFF = START_OFF;
constexpr int NCNT_OFF = SIDE_OFF;
static_assert(SCNT_OFF + 4 * (MAXG + 32) <= HEAD_OFF, "smem map");
static_assert(3 * (THREADS - 3 * MAXG) >= 2 * MAXG, "chunk map");
static_assert(SMEM_BYTES <= 232448 && BAR_OFF % 8 == 0 && RING_OFF % 128 == 0, "smem map");

constexpr uint32_t PAY_INVALID = 0x3FFFFFFu;
constexpr uint32_t PAY_MARK = 0x3FFFDFFu;
constexpr uint32_t ENT_PAD = 0xFFFFu;
constexpr uint32_t ST_START = 512, ST_CLOSE = 1024;
constexpr float QINVP = 9.0f / 510.0f;
constexpr uint32_t QTHRESH = 2126;

struct Scratch {
    unsigned sync[32];
    uint4 table[TABLE_MAXN / 4];
    uint4 wimg[RING_OFF / 16];
    uint2 pos8[TABLE_MAXN];
    uint4 xbuf[MAXG * MAXG * 8 + 3 * THREADS];
    int ovfcnt[MAXG];
    int2 ovf[MAXE + 8 * MAXG + 8];
    uint4 rec[MAXE + 1];
};
__device__ __align__(128) Scratch g_scratch;

struct Params {
    const __nv_bfloat16* pos;
    Scratch* g;
    const int* src;
    const int* dst;
    int N, NPC, E, gpc;
    const __nv_bfloat16* w2;
    const __nv_bfloat16* wr;
    const __nv_bfloat16* w1;
    const __nv_bfloat16* freqs;
    const __nv_bfloat16* sv;
    __nv_bfloat16* out;
    uint64_t desc0;
    int G;
    uint32_t magic;
    int pf_rows;
    int odd_edges;
};
constexpr uint32_t SB = 1024;

#define TSX(i, thr)
#define TR(k, thr, t)
#define TS0(i) TSX(i, 0)

__device__ __forceinline__ uint32_t smem_u32(const void* p) { return (uint32_t)__cvta_generic_to_shared(p); }
__device__ __forceinline__ void mbar_init(uint32_t bar, uint32_t cnt) {
    asm volatile("mbarrier.init.shared::cta.b64 [%0], %1;" ::"r"(bar), "r"(cnt) : "memory");
}
__device__ __forceinline__ void mbar_arrive(uint32_t bar) {
    asm volatile("mbarrier.arrive.shared::cta.b64 _, [%0];" ::"r"(bar) : "memory");
}
__device__ __forceinline__ void mbar_expect_tx(uint32_t bar, uint32_t bytes) {
    asm volatile("mbarrier.arrive.expect_tx.shared::cta.b64 _, [%0], %1;" ::"r"(bar), "r"(bytes) : "memory");
}
__device__ __forceinline__ void mbar_wait(uint32_t bar, uint32_t parity) {
    uint32_t ok;
    int it = 0;
    do {
        asm volatile(
            "{\n.reg .pred p;\n"
            "mbarrier.try_wait.parity.shared::cta.b64 p, [%1], %2, 2000;\n"
            "selp.u32 %0, 1, 0, p;\n}\n"
            : "=r"(ok) : "r"(bar), "r"(parity) : "memory");
        if (++it > (1 << 20)) __trap();
    } while (!ok);
}
__device__ __forceinline__ uint32_t mbar_test(uint32_t bar, uint32_t parity) {
    uint32_t ok;
    asm volatile("{\n.reg .pred p;\nmbarrier.test_wait.parity.shared::cta.b64 p, [%1], %2;\nselp.u32 %0, 1, 0, p;\n}\n"
                 : "=r"(ok) : "r"(bar), "r"(parity) : "memory");
    return ok;
}
__device__ __forceinline__ uint32_t pin(uint32_t x) {
    uint32_t r;
    asm volatile("shfl.sync.bfly.b32 %0, %1, 0, 31, -1;" : "=r"(r) : "r"(x));
    return r;
}
__device__ __forceinline__ void bulk_g2s(uint32_t dst, const void* src, uint32_t bytes, uint32_t bar) {
    asm volatile("cp.async.bulk.shared::cluster.global.mbarrier::complete_tx::bytes [%0], [%1], %2, [%3];"
                 ::"r"(dst), "l"(src), "r"(bytes), "r"(bar) : "memory");
}
__device__ __forceinline__ void ldsm4(uint32_t addr, uint32_t* r) {
    asm volatile("ldmatrix.sync.aligned.m8n8.x4.shared.b16 {%0,%1,%2,%3}, [%4];"
                 : "=r"(r[0]), "=r"(r[1]), "=r"(r[2]), "=r"(r[3]) : "r"(addr) : "memory");
}
__device__ __forceinline__ uint32_t pack2(float lo, float hi) {
    uint32_t r;
    asm("cvt.rn.bf16x2.f32 %0, %1, %2;" : "=r"(r) : "f"(hi), "f"(lo));
    return r;
}
__device__ __forceinline__ float bf_lo(uint32_t w) { return __uint_as_float(w << 16); }
__device__ __forceinline__ float bf_hi(uint32_t w) { return __uint_as_float(w & 0xFFFF0000u); }
__device__ __forceinline__ float rbf16(float x) { return __uint_as_float(pack2(0.f, x)); }
__device__ __forceinline__ uint32_t hmul2(uint32_t a, uint32_t b) {
    uint32_t r;
    asm("mul.rn.bf16x2 %0, %1, %2;" : "=r"(r) : "r"(a), "r"(b));
    return r;
}
__device__ __forceinline__ uint32_t hfma2(uint32_t a, uint32_t b, uint32_t c) {
    uint32_t r;
    asm("fma.rn.bf16x2 %0, %1, %2, %3;" : "=r"(r) : "r"(a), "r"(b), "r"(c));
    return r;
}
__device__ __forceinline__ uint32_t hfma2_lo(uint32_t a, uint32_t b, uint32_t c) {
    uint32_t r;
    asm("{\n.reg .b16 l, h;\n.reg .b32 t;\nmov.b32 {l, h}, %2;\nmov.b32 t, {l, l};\nfma.rn.bf16x2 %0, %1, t, %3;\n}\n" : "=r"(r) : "r"(a), "r"(b), "r"(c));
    return r;
}
__device__ __forceinline__ uint32_t hfma2_hi(uint32_t a, uint32_t b, uint32_t c) {
    uint32_t r;
    asm("{\n.reg .b16 l, h;\n.reg .b32 t;\nmov.b32 {l, h}, %2;\nmov.b32 t, {h, h};\nfma.rn.bf16x2 %0, %1, t, %3;\n}\n" : "=r"(r) : "r"(a), "r"(b), "r"(c));
    return r;
}
__device__ __forceinline__ uint32_t hmul2_hi(uint32_t a, uint32_t b) {
    uint32_t r;
    asm("{\n.reg .b16 l, h;\n.reg .b32 t;\nmov.b32 {l, h}, %2;\nmov.b32 t, {h, h};\nmul.rn.bf16x2 %0, %1, t;\n}\n" : "=r"(r) : "r"(a), "r"(b));
    return r;
}
__device__ __forceinline__ uint32_t hadd2(uint32_t a, uint32_t b) {
    uint32_t r;
    asm("add.rn.bf16x2 %0, %1, %2;" : "=r"(r) : "r"(a), "r"(b));
    return r;
}
__device__ __forceinline__ uint32_t hsub2(uint32_t a, uint32_t b) {
    uint32_t r;
    asm("sub.rn.bf16x2 %0, %1, %2;" : "=r"(r) : "r"(a), "r"(b));
    return r;
}
__device__ __forceinline__ void cp_async_arrive(uint32_t bar) {
    asm volatile("cp.async.mbarrier.arrive.noinc.shared::cta.b64 [%0];" ::"r"(bar) : "memory");
}
__device__ __forceinline__ float tanh_fast(float x) {
    float r;
    asm("tanh.approx.f32 %0, %1;" : "=f"(r) : "f"(x));
    return r;
}
__device__ __forceinline__ void wg_fence() { asm volatile("wgmma.fence.sync.aligned;" ::: "memory"); }
__device__ __forceinline__ void wg_commit() { asm volatile("wgmma.commit_group.sync.aligned;" ::: "memory"); }
template <int N>
__device__ __forceinline__ void wg_wait() { asm volatile("wgmma.wait_group.sync.aligned %0;" ::"n"(N) : "memory"); }

#define WG_REGS "{%0,%1,%2,%3,%4,%5,%6,%7,%8,%9,%10,%11,%12,%13,%14,%15,%16,%17,%18,%19,%20,%21,%22,%23,%24,%25,%26,%27,%28,%29,%30,%31}"
#define WG_OPS(c) c(d[0]), c(d[1]), c(d[2]), c(d[3]), c(d[4]), c(d[5]), c(d[6]), c(d[7]), c(d[8]), c(d[9]), c(d[10]), \
    c(d[11]), c(d[12]), c(d[13]), c(d[14]), c(d[15]), c(d[16]), c(d[17]), c(d[18]), c(d[19]), c(d[20]), c(d[21]),     \
    c(d[22]), c(d[23]), c(d[24]), c(d[25]), c(d[26]), c(d[27]), c(d[28]), c(d[29]), c(d[30]), c(d[31])
__device__ __forceinline__ void wgmma_first(float* d, const uint32_t* a, uint64_t desc) {
#pragma unroll
    for (int i = 0; i < 32; i++) d[i] = 0.f;
    asm volatile("wgmma.mma_async.sync.aligned.m64n64k16.f32.bf16.bf16 " WG_REGS ", {%32,%33,%34,%35}, %36, 0, 1, 1, 1;"
                 : WG_OPS("+f") : "r"(a[0]), "r"(a[1]), "r"(a[2]), "r"(a[3]), "l"(desc));
}
__device__ __forceinline__ void wgmma_acc(float* d, const uint32_t* a, uint64_t desc) {
    asm volatile("wgmma.mma_async.sync.aligned.m64n64k16.f32.bf16.bf16 " WG_REGS ", {%32,%33,%34,%35}, %36, 1, 1, 1, 1;"
                 : WG_OPS("+f") : "r"(a[0]), "r"(a[1]), "r"(a[2]), "r"(a[3]), "l"(desc));
}
__device__ __forceinline__ void wgmma_k64(float* d, const uint32_t* a, uint64_t desc) {
    wgmma_first(d, a, desc);
    wgmma_acc(d, a + 4, desc + 128);
    wgmma_acc(d, a + 8, desc + 256);
    wgmma_acc(d, a + 12, desc + 384);
}
__device__ __forceinline__ void fence_regs(float* d) { asm volatile("" : WG_OPS("+f")::"memory"); }
__device__ __forceinline__ uint32_t qaxis(float x) {
    const float u = fmaf(x, QINVP, 0.25f);
    const float f = u - ((u + 12582912.f) - 12582912.f);
    return __float_as_uint(fmaf(fabsf(f), 510.f, 12582912.f));
}
__device__ __forceinline__ uint32_t qcode(float x, float y, float z, uint32_t tx) {
    return __byte_perm(__byte_perm(qaxis(x), qaxis(y), 0x3340), qaxis(z), 0x3410) ^ tx;
}
__device__ __forceinline__ bool near_test(uint32_t ca, uint32_t cb, uint32_t tag24) {
    const uint32_t D = __vabsdiffu4(ca, cb);
    return __dp4a(D, D, 0u) <= QTHRESH || ((ca ^ tag24) | (cb ^ tag24)) >= 0x1000000u;
}
__device__ __forceinline__ bool inside(uint32_t rxy, uint32_t rz) {
    const uint32_t qxy = hmul2(rxy, rxy), qz = hmul2(rz, rz);
    return bf_lo(qxy) + bf_hi(qxy) + bf_lo(qz) < 23.9375f;
}

__device__ __forceinline__ uint32_t lds32(uint32_t addr) {
    uint32_t r;
    asm volatile("ld.shared.u32 %0, [%1];" : "=r"(r) : "r"(addr));
    return r;
}
__device__ __forceinline__ void sts32_if(uint32_t addr, uint32_t v, bool c) {
    asm volatile("{\n.reg .pred p;\nsetp.ne.u32 p, %2, 0;\n@p st.shared.u32 [%0], %1;\n}\n" ::"r"(addr), "r"(v), "r"((uint32_t)c) : "memory");
}
__device__ __forceinline__ void stg128_if(void* ptr, uint4 v, bool c) {
    asm volatile("{\n.reg .pred p;\nsetp.ne.u32 p, %5, 0;\n@p st.relaxed.gpu.global.v4.u32 [%0], {%1,%2,%3,%4};\n}\n"
                 ::"l"(ptr), "r"(v.x), "r"(v.y), "r"(v.z), "r"(v.w), "r"((uint32_t)c) : "memory");
}
__device__ __forceinline__ void lds128(uint32_t addr, uint32_t* r) {
    asm volatile("ld.shared.v4.u32 {%0,%1,%2,%3}, [%4];" : "=r"(r[0]), "=r"(r[1]), "=r"(r[2]), "=r"(r[3]) : "r"(addr) : "memory");
}
__device__ __forceinline__ void stg2_if(uint64_t ptr, const uint32_t* r, bool c) {
    asm volatile("{\n.reg .pred p;\nsetp.ne.u32 p, %9, 0;\n@p st.global.cs.v4.u32 [%8], {%0,%1,%2,%3};\n"
                 "@p st.global.cs.v4.u32 [%8 + 64], {%4,%5,%6,%7};\n}\n"
                 ::"r"(r[0]), "r"(r[1]), "r"(r[2]), "r"(r[3]), "r"(r[4]), "r"(r[5]), "r"(r[6]), "r"(r[7]), "l"(ptr), "r"((uint32_t)c) : "memory");
}
__device__ __forceinline__ void stg2_fl(uint64_t ptr, const uint32_t* r, uint32_t fl) {
    asm volatile("{\n.reg .pred p;\n.reg .b32 t;\nand.b32 t, %9, 1024;\nsetp.ne.u32 p, t, 0;\n@p st.global.cs.v4.u32 [%8], {%0,%1,%2,%3};\n"
                 "@p st.global.cs.v4.u32 [%8 + 64], {%4,%5,%6,%7};\n}\n"
                 ::"r"(r[0]), "r"(r[1]), "r"(r[2]), "r"(r[3]), "r"(r[4]), "r"(r[5]), "r"(r[6]), "r"(r[7]), "l"(ptr), "r"(fl) : "memory");
}
__device__ __forceinline__ void gather_row(uint32_t dst, const char* base, uint32_t src) {
    asm volatile("{\n.reg .pred p;\nsetp.eq.u32 p, %2, 0xFFFF;\ncp.async.cg.shared.global [%0], [%1], 16, p;\n"
                 "cp.async.cg.shared.global [%0 + 128], [%1 + 128], 16, p;\ncp.async.cg.shared.global [%0 + 256], [%1 + 256], 16, p;\n"
                 "cp.async.cg.shared.global [%0 + 384], [%1 + 384], 16, p;\n}\n" ::"r"(dst), "l"(base + (size_t)src * 512), "r"(src) : "memory");
}
__device__ __forceinline__ void gather_row_if(uint32_t dst, const char* src, uint32_t c) {
    asm volatile("{\n.reg .pred p;\nsetp.ne.u32 p, %2, 0;\n@p cp.async.cg.shared.global [%0], [%1], 16;\n"
                 "@p cp.async.cg.shared.global [%0 + 128], [%1 + 128], 16;\n@p cp.async.cg.shared.global [%0 + 256], [%1 + 256], 16;\n"
                 "@p cp.async.cg.shared.global [%0 + 384], [%1 + 384], 16;\n}\n" ::"r"(dst), "l"(src), "r"(c) : "memory");
}
__device__ __forceinline__ void lds2_if(uint32_t a0, uint32_t a1, uint32_t* r, uint32_t c) {
    asm volatile("{\n.reg .pred p;\nsetp.ne.u32 p, %10, 0;\n@p ld.shared.v4.u32 {%0,%1,%2,%3}, [%8];\n@p ld.shared.v4.u32 {%4,%5,%6,%7}, [%9];\n}\n"
                 : "+r"(r[0]), "+r"(r[1]), "+r"(r[2]), "+r"(r[3]), "+r"(r[4]), "+r"(r[5]), "+r"(r[6]), "+r"(r[7])
                 : "r"(a0), "r"(a1), "r"(c) : "memory");
}
__device__ __forceinline__ int fresh_lane() {
    int l;
    asm volatile("mov.u32 %0, %%laneid;" : "=r"(l));
    return l;
}

__device__ __forceinline__ void cold_edges(unsigned char* smem, const Params& p, int lo, int hi, uint32_t tag) {
#pragma unroll 1
    for (int e = lo + threadIdx.x; e < hi; e += THREADS) {
        const int s = p.src[e], d = p.dst[e];
        if (near_test(reinterpret_cast<const uint32_t*>(smem)[s], reinterpret_cast<const uint32_t*>(smem)[d], tag << 24)) {
            const uint32_t own = __umulhi((uint32_t)d, p.magic);
            const uint32_t slot4 = atomicAdd(reinterpret_cast<uint32_t*>(smem + SCNT_OFF) + own, 4u);
            uint32_t* line = reinterpret_cast<uint32_t*>(smem + STAGE_OFF) + own * 32;
            if (slot4 < 124) {
                line[slot4 >> 2] = ((uint32_t)s << 15) + ((uint32_t)(d - own * p.NPC) << 6) + tag;
            } else {
                uint32_t o = atomicAdd(reinterpret_cast<uint32_t*>(smem + MISC_OFF) + 16, 1u);
                p.g->ovf[(size_t)blockIdx.x * (4 * p.gpc + 4) + o] = make_int2(s, d);
                line[31] = (PAY_MARK << 6) | tag;
            }
        }
    }
}
__device__ __forceinline__ void cold_filter(unsigned char* smem, const Params& p, int e0, int e1, uint32_t tag, int redo) {
    if (redo) {
        if (threadIdx.x < MAXG) reinterpret_cast<uint32_t*>(smem + SCNT_OFF)[threadIdx.x] = 0;
        __syncthreads();
    }
    cold_edges(smem, p, redo ? 4 * e0 : 4 * (e0 + 3 * THREADS), 4 * e1, tag);
    if (blockIdx.x == 0) cold_edges(smem, p, p.E & ~3, p.E, tag);
    __syncthreads();
    if (threadIdx.x == 0) p.g->ovfcnt[blockIdx.x] = reinterpret_cast<uint32_t*>(smem + MISC_OFF)[16];
    __threadfence();
    __syncthreads();
}
__device__ __forceinline__ uint4 geometry(uint4 r) {
    const uint32_t qxy = hmul2(r.x, r.x), qz = hmul2(r.y, r.y);
    float d, id;
    asm("sqrt.approx.ftz.f32 %0, %1;" : "=f"(d) : "f"(rbf16(rbf16(bf_lo(qxy) + bf_hi(qxy) + bf_lo(qz)) + 1e-8f)));
    d = rbf16(d);
    asm("rcp.approx.ftz.f32 %0, %1;" : "=f"(id) : "f"(d));
    const float cs = rbf16(__cosf(rbf16(rbf16(3.14159265358979f * d) * 0.2f)));
    return make_uint4(pack2(bf_lo(r.x) * id, bf_hi(r.x) * id), pack2(bf_lo(r.y) * id, d < 5.0f ? 0.5f * rbf16(cs + 1.0f) * id : 0.f),
                      __byte_perm(r.z, __float_as_uint(d), 0x7610), r.w);
}
__device__ __forceinline__ void cold_lists(unsigned char* smem, const Params& p, unsigned* alloc) {
    uint32_t* head = reinterpret_cast<uint32_t*>(smem + HEAD_OFF);
    uint32_t* ncnt = reinterpret_cast<uint32_t*>(smem + NCNT_OFF);
    const int nmark = reinterpret_cast<uint32_t*>(smem + MISC_OFF)[17], nbase = blockIdx.x * p.NPC;
    head[threadIdx.x] = ncnt[threadIdx.x] = 0;
    p.g->rec[0] = make_uint4(0, 0, ENT_PAD, 0);
    __threadfence();
    __syncthreads();
#pragma unroll 1
    for (int m = -1; m < nmark; m++) {
        const int pr = m < 0 ? 0 : smem[OVL_OFF + m];
        const int cnt = m < 0 ? p.G * 32 : __ldcg(&p.g->ovfcnt[pr]);
#pragma unroll 1
        for (int i = threadIdx.x; i < cnt; i += THREADS) {
            int2 e;
            if (m < 0) {
                const uint32_t w = __ldcg(reinterpret_cast<const uint32_t*>(p.g->xbuf) + blockIdx.x * p.G * 32 + i);
                e = make_int2(w >> 15, nbase + ((w >> 6) & 511u));
            } else {
                e = __ldcg(p.g->ovf + (size_t)pr * (4 * p.gpc + 4) + i);
            }
            const uint32_t dl = (uint32_t)(e.y - nbase);
            if (dl < (uint32_t)p.NPC) {
                const uint2 ps = __ldcg(p.g->pos8 + e.x), pd = __ldcg(p.g->pos8 + e.y);
                const uint32_t rxy = hsub2(ps.x, pd.x), rz = hsub2(ps.y, pd.y);
                if (inside(rxy, rz)) {
                    const uint32_t o = atomicAdd(alloc, 1u) + 1;
                    atomicAdd(&ncnt[dl], 1u);
                    p.g->rec[o] = geometry(make_uint4(rxy, rz, e.x, atomicExch(&head[dl], o)));
                }
            }
        }
    }
    __syncthreads();
}

template <bool B> struct BoolC { static constexpr bool value = B; };

template <int CN, int CE, int CG>
__global__ void __launch_bounds__(THREADS, 1) painn_kernel(const __grid_constant__ Params p) {
    extern __shared__ __align__(1024) unsigned char smem_dyn[];
    unsigned char* const smem = static_cast<unsigned char*>(__cvta_shared_to_generic(SB));
    constexpr uint32_t sb = SB;
    const int tid = threadIdx.x, lane = tid & 31;
    const int warp = __shfl_sync(0xffffffffu, tid >> 5, 0);
    constexpr int CNPC = CG ? (CN + CG - 1) / CG : 1, CGPC = CG ? (CE / 4 + CG - 1) / CG : 1;
    const int b = blockIdx.x, G = CG ? CG : p.G, NPC = CG ? CNPC : p.NPC, N = CG ? CN : p.N, gpc = CG ? CGPC : p.gpc;
    const uint32_t magic = CG ? (uint32_t)(((1ull << 32) + CNPC - 1) / CNPC) : p.magic;
    const bool odd_edges = CG ? (CE & 3) != 0 || CGPC > 3 * THREADS : p.odd_edges;
    const int nbase = b * NPC, nn = min(NPC, N - nbase);
    const int e0 = b * gpc, e1 = min((CG ? CE : p.E) >> 2, e0 + gpc);

    uint4* stage4 = reinterpret_cast<uint4*>(smem + STAGE_OFF);
    uint32_t* head = reinterpret_cast<uint32_t*>(smem + HEAD_OFF);
    uint32_t* ncnt = reinterpret_cast<uint32_t*>(smem + NCNT_OFF);
    uint2* start = reinterpret_cast<uint2*>(smem + START_OFF);
    uint32_t* misc = reinterpret_cast<uint32_t*>(smem + MISC_OFF);
    const uint32_t bar_full = sb + BAR_OFF + (warp & 7) * 40, bar_empty = bar_full + 16, bar_side = bar_full + 32, bar_tab = sb + BAR_OFF + 336;

    TS0(0);
    int4 es[3], ed[3];
    auto load_edges = [&](int i) {
        const int g = min(e0 + tid + i * THREADS, e1 - 1);
        asm volatile("ld.global.cs.v4.u32 {%0,%1,%2,%3}, [%8];\nld.global.cs.v4.u32 {%4,%5,%6,%7}, [%9];"
                     : "=r"(es[i].x), "=r"(es[i].y), "=r"(es[i].z), "=r"(es[i].w), "=r"(ed[i].x), "=r"(ed[i].y), "=r"(ed[i].z), "=r"(ed[i].w)
                     : "l"(reinterpret_cast<const int4*>(p.src) + g), "l"(reinterpret_cast<const int4*>(p.dst) + g) : "memory");
    };
    unsigned epoch;
    const uint32_t tbytes = ((N + 3) >> 2) * 16;
    {
        uint32_t pxy, pz;
        asm volatile("ld.global.nc.u32 %0, [%3];\nld.global.nc.u32 %1, [%3 + 4];\nld.global.ca.u32 %2, [%4];"
                     : "=r"(pxy), "=r"(pz), "=r"(epoch)
                     : "l"(reinterpret_cast<const uint32_t*>(p.pos) + ((nbase + min(tid, nn - 1)) * 3 >> 1)), "l"(p.g->sync) : "memory");
        const uint32_t sh = ((nbase + tid) & 1) << 4;
        pxy = __funnelshift_r(pxy, pz, sh);
        pz >>= sh;
        if (tid < nn) {
            reinterpret_cast<uint32_t*>(p.g->table)[nbase + tid] = qcode(bf_lo(pxy), bf_hi(pxy), bf_lo(pz), ((epoch & 31u) ^ 0x6Bu) << 24);
            p.g->pos8[nbase + tid] = make_uint2(pxy, pz);
        }
        reinterpret_cast<uint2*>(smem + OPOS_OFF)[tid] = make_uint2(pxy, pz);
        if (pxy == 0xFFFFFFFFu && pz == 0xFFFFFFFFu && epoch == 0xFFFFFFFFu) asm volatile("nanosleep.u32 0;");
        load_edges(0);
    }
    __syncthreads();
    const uint32_t tag = (epoch & 31u) | 32u;
    if (tid == THREADS - 1) {
        asm volatile("red.relaxed.gpu.global.add.u32 [%0], 1;" ::"l"(p.g->sync + 1) : "memory");
        TSX(1, 511);
        const unsigned want = (epoch + 1) * G;
        unsigned c;
        int it = smem_u32(smem_dyn) == SB ? 0 : 1 << 22;
        do {
            asm volatile("ld.relaxed.gpu.global.u32 %0, [%1];" : "=r"(c) : "l"(p.g->sync + 1) : "memory");
            if (++it > (1 << 22)) __trap();
        } while (c != want);
        mbar_init(bar_tab, 1);
        mbar_expect_tx(bar_tab, tbytes);
        bulk_g2s(sb, p.g->table, tbytes, bar_tab);
        TSX(2, 511);
        if (b == 0) p.g->sync[2 + ((epoch + 1) & 1)] = 0;
    }
    if (warp == 14) {
#pragma unroll 1
        for (int c = b * 32 + lane; c < RING_OFF / 16; c += G * 32) {
            const int row = c >> 3, j = (c ^ row) & 7;
            uint4 v;
            if (c < 512) {
                const uint32_t half = 0x3F003F00u;
                v = __ldg(reinterpret_cast<const uint4*>(p.w1) + row * 8 + j);
                v = make_uint4(hmul2(v.x, half), hmul2(v.y, half), hmul2(v.z, half), hmul2(v.w, half));
            } else {
                const uint32_t* q = (c < 2048 ? reinterpret_cast<const uint32_t*>(p.w2) + (row & 63) * 96 + ((row >> 6) - 1) * 32
                                              : reinterpret_cast<const uint32_t*>(p.wr) + (row & 15) * 96 + ((row >> 4) - 16) * 32) + (j & 4) * 4 + (j & 3);
                v = make_uint4(__ldg(q), __ldg(q + 4), __ldg(q + 8), __ldg(q + 12));
            }
            p.g->wimg[c] = v;
        }
    }
    if (warp < 8 && lane == 0) {
        mbar_init(bar_full, 33); mbar_init(bar_full + 8, 33);
        mbar_init(bar_empty, 1);
        mbar_init(bar_side, 32);
    }
    head[tid] = 0;
    if (tid < MAXG) reinterpret_cast<uint32_t*>(smem + SCNT_OFF)[tid] = 0;
    if (tid < 48) misc[tid] = tid == 0;
    {
        const uint32_t inv = (PAY_INVALID << 6) | tag;
        stage4[tid] = stage4[tid + THREADS] = make_uint4(inv, inv, inv, inv);
        if (tid < MAXG * 8 - 2 * THREADS) stage4[tid + 2 * THREADS] = make_uint4(inv, inv, inv, inv);
    }
    __syncthreads();
    uint4* const xout = p.g->xbuf + ((tid >> 3) * G + b) * 8 + (tid & 7);
#pragma unroll
    for (int i = 0; i < 3; i++) stg128_if(xout + i * G * THREADS, make_uint4(0, 0, 0, 0), tid + i * THREADS < G * 8);
    load_edges(1);
    load_edges(2);
    if (tid < 8) asm volatile("cp.async.ca.shared.global [%0], [%1], 4;" ::"r"(sb + MISC_OFF + 96 + 4 * tid),
                              "l"(reinterpret_cast<const uint32_t*>(p.freqs) + (tid >> 1) + (tid & 1) * 4) : "memory");
    if (tid == THREADS - 1) asm volatile("fence.acq_rel.gpu;" ::: "memory");
    mbar_wait(bar_tab, 0);
    TS0(3);
    if (tid == 0) asm volatile("cp.async.bulk.prefetch.L2.global [%0], %1;" ::"l"(p.sv + (size_t)nbase * 256), "r"(min(p.pf_rows, nn) * 512) : "memory");

#pragma unroll 1
    for (int i = 0, g = e0 + tid; i < 3; i++, g += THREADS) {
        const int s[4] = {es[0].x, es[0].y, es[0].z, es[0].w}, d[4] = {ed[0].x, ed[0].y, ed[0].z, ed[0].w};
        uint32_t ca[4], cb[4], own[4], sl[4];
        bool c[4];
#pragma unroll
        for (int j = 0; j < 4; j++) { ca[j] = lds32(sb + 4 * s[j]); cb[j] = lds32(sb + 4 * d[j]); }
#pragma unroll
        for (int j = 0; j < 4; j++) {
            c[j] = near_test(ca[j], cb[j], tag << 24) && g < e1;
            own[j] = __umulhi((uint32_t)d[j], magic);
            sl[j] = atomicAdd(reinterpret_cast<uint32_t*>(smem + SCNT_OFF) + (c[j] ? own[j] : MAXG + lane), 4u);
        }
#pragma unroll
        for (int j = 0; j < 4; j++)
            sts32_if(sb + STAGE_OFF + own[j] * 128 + sl[j], own[j] * (uint32_t)(-64 * NPC) + (((uint32_t)s[j] << 15) + (((uint32_t)d[j] << 6) + tag)),
                     c[j] && sl[j] < 124);
        es[0] = es[1]; es[1] = es[2];
        ed[0] = ed[1]; ed[1] = ed[2];
    }
    __syncthreads();
    {
        const int redo = __syncthreads_or(tid < MAXG && reinterpret_cast<uint32_t*>(smem + SCNT_OFF)[tid] > 124);
        if (__builtin_expect(redo || odd_edges, 0)) cold_filter(smem, p, e0, e1, tag, redo);
    }
    TS0(4);
#pragma unroll
    for (int i = 0; i < 3; i++) stg128_if(xout + i * G * THREADS, stage4[tid + i * THREADS], tid + i * THREADS < G * 8);
    ncnt[tid] = 0;
    asm volatile("cp.async.wait_all;" ::: "memory");
    __syncthreads();
    __nanosleep(PDELAY);
    TS0(5);

    {
        uint32_t ew[3][4];
        const uint4* cp[3];
        bool has[3];
#pragma unroll
        for (int i = 0; i < 3; i++) {
            const int u = tid - 3 * G + i * (THREADS - 3 * G), ln = tid / 3;
            has[i] = tid < 3 * G ? i < 2 : u < 2 * G;
            cp[i] = p.g->xbuf + b * G * 8 + (tid < 3 * G ? tid + ln * 5 + i * 5 : u < G ? u * 8 + 3 : (u - G) * 8 + 4);
        }
        uint32_t bad[3] = {has[0], has[1], has[2]};
#pragma unroll
        for (int i = 0; i < 3; i++) ew[i][0] = ew[i][1] = ew[i][2] = ew[i][3] = (PAY_INVALID << 6) | tag;
        int it = 0;
#pragma unroll 1
        do {
#pragma unroll
            for (int i = 0; i < 3; i++)
                asm volatile("{\n.reg .pred p;\nsetp.ne.u32 p, %5, 0;\n@p ld.relaxed.gpu.global.v4.u32 {%0,%1,%2,%3}, [%4];\n}\n"
                             : "+r"(ew[i][0]), "+r"(ew[i][1]), "+r"(ew[i][2]), "+r"(ew[i][3]) : "l"(cp[i]), "r"(bad[i]) : "memory");
#pragma unroll
            for (int i = 0; i < 3; i++) bad[i] = ((ew[i][0] ^ tag) | (ew[i][1] ^ tag) | (ew[i][2] ^ tag) | (ew[i][3] ^ tag)) & 63u;
            if (++it > (1 << 22)) __trap();
        } while (__any_sync(0xffffffffu, bad[0] | bad[1] | bad[2]));
        if ((ew[1][3] >> 6) == PAY_MARK) smem[OVL_OFF + atomicAdd(&misc[17], 1u)] = (unsigned char)(tid / 3);
#pragma unroll
        for (int i = 2; i > 0; i--)
            if (ew[i - 1][0] >= (PAY_MARK << 6)) {
#pragma unroll
                for (int j = 0; j < 4; j++) { ew[i - 1][j] = ew[i][j]; ew[i][j] = 0xFFFFFFFFu; }
            }
        if (tid == 0) reinterpret_cast<uint4*>(smem + REC_OFF)[0] = make_uint4(0, 0, ENT_PAD, 0);
#pragma unroll 1
        do {
            uint2 ps[4];
            uint32_t dl[4], bm[4];
            bool in[4];
#pragma unroll
            for (int j = 0; j < 4; j++) {
                dl[j] = (ew[0][j] >> 6) & 511u;
                ps[j] = __ldcg(p.g->pos8 + (dl[j] == 511u ? nbase : ew[0][j] >> 15));
            }
#pragma unroll
            for (int j = 0; j < 4; j++) {
                const uint2 pd = reinterpret_cast<const uint2*>(smem + OPOS_OFF)[dl[j]];
                ps[j] = make_uint2(hsub2(ps[j].x, pd.x), hsub2(ps[j].y, pd.y));
                in[j] = inside(ps[j].x, ps[j].y) && dl[j] != 511u;
                bm[j] = __ballot_sync(0xffffffffu, in[j]);
            }
            uint32_t o = 0;
            asm volatile("atom.shared.add.u32 %0, [%1], %2;" : "=r"(o)
                         : "r"(lane ? sb + NCNT_OFF + 4 * (480 + lane) : sb + MISC_OFF), "r"(__popc(bm[0]) + __popc(bm[1]) + __popc(bm[2]) + __popc(bm[3])) : "memory");
            o = __shfl_sync(0xffffffffu, o, 0);
            uint32_t e[4], nx[4];
#pragma unroll
            for (int j = 0; j < 4; j++) {
                e[j] = o + __popc(bm[j] & ((1u << lane) - 1));
                const uint32_t n = in[j] ? dl[j] : 480 + lane;
                atomicAdd(&ncnt[n], 1u);
                nx[j] = atomicExch(&head[n], e[j]);
                o += __popc(bm[j]);
            }
#pragma unroll
            for (int j = 0; j < 4; j++)
                if (in[j] && e[j] < CAP) reinterpret_cast<uint4*>(smem + REC_OFF)[e[j]] = make_uint4(ps[j].x, ps[j].y, ew[0][j] >> 15, nx[j]);
#pragma unroll
            for (int j = 0; j < 4; j++) { ew[0][j] = ew[1][j]; ew[1][j] = ew[2][j]; ew[2][j] = 0xFFFFFFFFu; }
        } while (__any_sync(0xffffffffu, (ew[0][0] & ew[1][0]) < (PAY_MARK << 6)));
    }
    __syncthreads();
    TS0(6);
    if (tid == THREADS - 1) {
        if (b == 0) p.g->sync[0] = epoch + 1;
        asm volatile("fence.proxy.async.global;" ::: "memory");
        mbar_expect_tx(bar_tab, RING_OFF);
        bulk_g2s(sb, p.g->wimg, RING_OFF, bar_tab);
    }
    __syncwarp();
    const uint32_t total = __shfl_sync(0xffffffffu, misc[0], 0);
    const bool cold = total > CAP || misc[17];
    if (__builtin_expect(cold, 0)) cold_lists(smem, p, &p.g->sync[2 + (epoch & 1)]);
    auto rest = [&](auto big) {
    uint4* recs = decltype(big)::value ? p.g->rec : reinterpret_cast<uint4*>(smem + REC_OFF);

    if (warp < 8) {
        {
            const int lane = fresh_lane();
            uint32_t c2[2], bin[2], order[2];
#pragma unroll
            for (int i = 0; i < 2; i++) {
                const int n = tid + 256 * i;
                c2[i] = n < nn ? (ncnt[n] + 1) & ~1u : 0u;
                const bool first = c2[i] && (n < 64 || (n < 128 && ncnt[n - 64] == 0));
                bin[i] = n < nn && !first ? 14 - min(c2[i] >> 1, 14u) : 15;
                order[i] = atomicAdd(&misc[32 + bin[i]], 1u);
            }
            asm volatile("bar.sync 1, 256;" ::: "memory");
            const uint32_t v = misc[32 + (lane & 15)];
            uint32_t z = v;
#pragma unroll
            for (int o = 1; o < 16; o <<= 1) {
                uint32_t y = __shfl_up_sync(0xffffffffu, z, o);
                if (lane >= o) z += y;
            }
            const int nsched = __shfl_sync(0xffffffffu, z, 13), zend = __shfl_sync(0xffffffffu, z, 14);
            if (tid == 0) { misc[20] = nsched; misc[21] = zend; }
#pragma unroll
            for (int i = 0; i < 2; i++) {
                const int n = tid + 256 * i;
                int r = order[i] + __shfl_sync(0xffffffffu, z - v, bin[i]);
                const int R = nsched - RESV;
                if (r < R) r = 2 * r < R ? 2 * r : 2 * (R - r) - 1;
                start[r] = bin[i] < 15 ? make_uint2(head[n], (c2[i] << 9) | ST_START | n) : make_uint2(0, 1024);
            }
            asm volatile("bar.arrive 4, 512;" ::: "memory");
            TS0(7);
        }
        if constexpr (!decltype(big)::value) {
#pragma unroll 1
            for (int e = warp * 32 + fresh_lane() + 1; e < (int)total; e += 512) {
                const uint4 r0 = recs[e], r1 = recs[min(e + 256, (int)total - 1)];
                recs[e] = geometry(r0);
                const uint4 g1 = geometry(r1);
                if (e + 256 < (int)total) recs[e + 256] = g1;
            }
        }
        asm volatile("bar.sync 1, 256;" ::: "memory");
        mbar_wait(bar_tab, 1);
        if (warp >= 4) asm volatile("bar.arrive 2, 256;" ::: "memory");
        asm volatile("setmaxnreg.inc.sync.aligned.u32 %0;" ::"n"(REG_C));
        const int lane = fresh_lane();
        const int g = lane >> 2, q = lane & 3;
        const uint64_t dW1 = p.desc0, dW2 = dW1 + (W2_OFF >> 4), dWR = dW1 + (WR_OFF >> 4);
        const uint32_t swz = (q ^ ((g & 1) << 2) ^ (g >> 1)) << 4;
        const uint32_t ring = sb + RING_OFF + warp * 32 * ROWB;
        const uint32_t srow = pin(sb + SIDE_OFF + (warp * 8 + g) * ROWB + swz);
        const uint32_t mrow = pin(ring + (2 * (lane & 7) + ((lane >> 3) & 1)) * ROWB + (((lane >> 4) ^ ((lane & 1) << 2) ^ ((lane & 7) >> 1)) << 4));
        const uint32_t nrow = pin(ring + 2 * g * ROWB + swz);
        const uint32_t gq = pin(g * 16 + (q << 20) + (lane ? 0x80000000u : 0u));
        uint64_t outq;
        {
            const uint64_t a = reinterpret_cast<uint64_t>(p.out) + (size_t)nbase * 512 + q * 16;
            const uint32_t lo = pin((uint32_t)a), hi = pin((uint32_t)(a >> 32));
            asm volatile("mov.b64 %0, {%1, %2};" : "=l"(outq) : "r"(lo), "r"(hi));
        }
        uint32_t acc[32];
#pragma unroll
        for (int i = 0; i < 32; i++) acc[i] = 0;
        uint32_t rf[4] = {0, 0, 0, 0}, h[16], base = sb;
#pragma unroll
        for (int i = 0; i < 16; i++) h[i] = 0;
        int t = -1, fl = 0;
        uint4 rr = make_uint4(0, 0, 0, 0);
        bool more = total < 0x7FFFFFFFu;
#pragma unroll 1
        while (more) {
            float y[32], p1[32], w1[32], p2[32], w2[32], p3[32], w3[32];
            asm volatile("bar.sync %0, 256;" ::"r"(2 + (warp >> 2)) : "memory");
            wg_fence();
            wgmma_k64(p1, h, dW2 + 512);
            wgmma_first(w1, rf, dWR + 128);
            wg_commit();
            if constexpr (!decltype(big)::value) {
                wgmma_k64(p2, h, dW2 + 1024);
                wgmma_first(w2, rf, dWR + 256);
                wg_commit();
            }
            const uint32_t side_ok = mbar_test(bar_side, t & 1);
            const uint32_t full_ok = mbar_test(bar_full + 8 * (~t & 1), ((t + 1) >> 1) & 1);
            wg_wait<decltype(big)::value ? 0 : 1>();
            fence_regs(p1); fence_regs(w1);
            {
                uint32_t m[16], v[4][16];
#pragma unroll
                for (int j = 0; j < 8; j++) {
                    m[j] = pack2(p1[4 * j] * w1[4 * j], p1[4 * j + 1] * w1[4 * j + 1]);
                    m[8 + j] = pack2(p1[4 * j + 2] * w1[4 * j + 2], p1[4 * j + 3] * w1[4 * j + 3]);
                }
                TR(0, 0, t);
                if (!side_ok && t >= 0) mbar_wait(bar_side, t & 1);
                TR(1, 0, t);
#pragma unroll
                for (int k = 0; k < 4; k++) lds2_if(srow + 128 * k, (srow ^ 64) + 128 * k, acc + 8 * k, fl & ST_START);
#pragma unroll
                for (int k = 1; k < 4; k++) {
                    lds128(base + 128 * k, v[k]); lds128((base ^ 64) + 128 * k, v[k] + 4);
                    lds128(base + ROWB + 128 * k, v[k] + 8); lds128((base ^ 64) + ROWB + 128 * k, v[k] + 12);
                }
#pragma unroll
                for (int k = 1; k < 4; k++)
#pragma unroll
                    for (int j = 0; j < 8; j++) acc[8 * k + j] = hfma2(m[8 + j], v[k][8 + j], hfma2(m[j], v[k][j], acc[8 * k + j]));
            }
            __syncwarp();
            if ((int)gq >= 0) mbar_arrive(bar_empty);
            t++;
            if constexpr (decltype(big)::value) {
                wg_fence();
                wgmma_k64(p2, h, dW2 + 1024);
                wgmma_first(w2, rf, dWR + 256);
                wg_commit();
            }
            wg_wait<0>();
            fence_regs(p2); fence_regs(w2);
            uint64_t op;
            asm("mad.wide.u32 %0, %1, 512, %2;" : "=l"(op) : "r"(fl & 511), "l"(outq));
            const uint32_t close = fl;
            {
                uint32_t m[16];
#pragma unroll
                for (int j = 0; j < 8; j++) {
                    m[j] = pack2(p2[4 * j] * w2[4 * j], p2[4 * j + 1] * w2[4 * j + 1]);
                    m[8 + j] = pack2(p2[4 * j + 2] * w2[4 * j + 2], p2[4 * j + 3] * w2[4 * j + 3]);
                }
            asm volatile("bar.arrive %0, 256;" ::"r"(3 - (warp >> 2)) : "memory");
            TR(2, 0, t - 1);
            if (!full_ok) mbar_wait(bar_full + 8 * (t & 1), (t >> 1) & 1);
            TR(3, 0, t - 1);
            uint32_t ix[4];
            lds128(sb + RIDX_OFF + (warp * 2 + (t & 1)) * 128 + (gq & 0xFF), ix);
            uint32_t a[16];
#pragma unroll
            for (int i = 0; i < 4; i++) ldsm4((mrow ^ (i << 5)) + (t & 1) * 16 * ROWB, a + 4 * i);
                const uint4 na = recs[ix[0]], nb = recs[ix[1]];
                uint32_t f01, f23;
                asm volatile("ld.shared.v2.u32 {%0,%1}, [%2];" : "=r"(f01), "=r"(f23) : "r"(sb + MISC_OFF + 96 + ((gq >> 17) & 0x18)));
                wg_fence();
                wgmma_k64(p3, h, dW2);
                wgmma_first(w3, rf, dWR);
                wg_commit();
                wgmma_k64(y, a, dW1);
                wg_commit();
#pragma unroll
                for (int k = 1; k < 4; k++)
#pragma unroll
                    for (int j = 0; j < 8; j++) {
                        const uint32_t x = k == 1 ? hfma2_lo(m[j], rr.x, acc[8 * k + j]) : k == 2 ? hfma2_hi(m[j], rr.x, acc[8 * k + j]) : hfma2_lo(m[j], rr.y, acc[8 * k + j]);
                        acc[8 * k + j] = k == 1 ? hfma2_lo(m[8 + j], rr.z, x) : k == 2 ? hfma2_hi(m[8 + j], rr.z, x) : hfma2_lo(m[8 + j], rr.w, x);
                    }
                fl = ix[2];
#pragma unroll
                for (int k = 1; k < 4; k++) stg2_fl(op + 128 * k, acc + 8 * k, close);
                rr = make_uint4(na.x, na.y, nb.x, nb.y);
                base = nrow + (t & 1) * 16 * ROWB;
                more = __all_sync(0xffffffffu, fl >= 0);
                wg_wait<1>();
                fence_regs(p3); fence_regs(w3);
#pragma unroll
                for (int j = 0; j < 8; j++)
                    acc[j] = hadd2(acc[j], pack2(fmaf(p3[4 * j], w3[4 * j], p3[4 * j + 2] * w3[4 * j + 2]),
                                                 fmaf(p3[4 * j + 1], w3[4 * j + 1], p3[4 * j + 3] * w3[4 * j + 3])));
                stg2_fl(op, acc, close);
#pragma unroll
                for (int hh = 0; hh < 2; hh++) {
                    const float s = bf_hi(hh ? rr.w : rr.y);
                    const uint32_t x01 = hmul2_hi(f01, hh ? nb.z : na.z), x23 = hmul2_hi(f23, hh ? nb.z : na.z);
                    rf[hh] = pack2(__sinf(bf_lo(x01)) * s, __sinf(bf_hi(x01)) * s);
                    rf[2 + hh] = pack2(__sinf(bf_lo(x23)) * s, __sinf(bf_hi(x23)) * s);
                }
            }
            wg_wait<0>();
            fence_regs(y);
#pragma unroll
            for (int i = 0; i < 16; i++)
                h[i] = pack2(fmaf(y[2 * i], tanh_fast(y[2 * i]), y[2 * i]), fmaf(y[2 * i + 1], tanh_fast(y[2 * i + 1]), y[2 * i + 1]));
        }
    } else {
        asm volatile("setmaxnreg.dec.sync.aligned.u32 %0;" ::"n"(256 - REG_C));
        const int lane = fresh_lane();
        const int w = warp & 3, s = lane >> 3;
        const uint32_t lt = (1u << lane) - 1;
        const uint32_t swz = ((lane & 7) ^ ((s & 1) << 2) ^ (s >> 1)) << 4;
        const uint32_t urow = sb + RING_OFF + ((warp - 8) * 32 + 2 * s) * ROWB + swz, srow = sb + SIDE_OFF + ((warp - 8) * 8 + s) * ROWB + swz;
        const char* svl = reinterpret_cast<const char*>(p.sv) + (lane & 7) * 16;
        uint32_t pos = 0, inf = 1024;
        int next = 0, f0 = 0, f1 = 0, nsched = 0, zend = 0;
        uint32_t oinf = 1024;
        {
            const int mine = lane + ((warp & 4) << 3), other = mine ^ 32;
            const uint32_t c0 = ncnt[mine], c1 = ncnt[mine + 64], h0 = head[mine], h1 = head[mine + 64], o0 = ncnt[other], o1 = ncnt[other + 64];
            const uint32_t c = c0 ? c0 : c1, oc = o0 ? o0 : o1;
            if (c) { pos = c0 ? h0 : h1; inf = (((c + 1) & ~1u) << 9) | ST_START | (c0 ? mine : mine + 64); }
            if (oc) oinf = ((oc + 1) & ~1u) << 9;
        }
        uint32_t ur;
        TSX(9, 256);
        bool stop = false;
#pragma unroll 1
        for (int t = 0; !stop; t++) {
            TR(4, 256, t);
            if (t == 1) {
                asm volatile("bar.sync 4, 512;" ::: "memory");
                nsched = misc[20]; zend = misc[21];
            }
            if (t + (warp & 4)) {
                const uint32_t om = __ballot_sync(0xffffffffu, oinf < 1024);
                const uint32_t oy = start[min(next + __popc(om & lt), 511)].y;
                if (oinf < 1024) oinf = max(oy, 1024u);
                next = min(next + __popc(om), 512);
                oinf -= 1024;
            }
            const bool need = inf < 1024;
            const uint32_t m = __ballot_sync(0xffffffffu, need);
            const int idx = next + __popc(m & lt);
            const uint2 st = start[idx < nsched ? idx : 511];
            if (need) { pos = st.x; inf = st.y; }
            next = min(next + __popc(m), 512);
            inf -= 1024;
            int fl = (inf & (need || t == 0 ? 1023 : 511)) | (inf < 1024 ? (inf & 512) << 1 : 0);
            stop = __all_sync(0xffffffffu, t && inf == 0 && oinf < 1024);
            const uint2 la = reinterpret_cast<const uint2*>(recs + pos)[1], lb = reinterpret_cast<const uint2*>(recs + la.y)[1];
            const uint32_t sp = __byte_perm(la.x, lb.x, 0x5410);
            const uint32_t e0 = __shfl_sync(0xffffffffu, sp, 8 * w + s), e1 = __shfl_sync(0xffffffffu, sp, 8 * w + 4 + s);
            TR(5, 256, t);
            if (t) mbar_wait(bar_empty, ~t & 1);
            TR(6, 256, t);
            if (t) {
                gather_row_if(srow, svl + (size_t)(nbase + (f0 & 511)) * 512, f0 & ST_START);
                gather_row_if((srow ^ 32) + 4 * ROWB, svl + (size_t)(nbase + (f1 & 511)) * 512, f1 & ST_START);
                cp_async_arrive(bar_side);
            }
            ur = urow + (t & 1) * 16 * ROWB;
            if (!stop) {
                gather_row(ur, svl, e0 & 0xFFFFu);
                gather_row(ur + ROWB, svl, e0 >> 16);
                gather_row((ur ^ 32) + 8 * ROWB, svl, e1 & 0xFFFFu);
                gather_row((ur ^ 32) + 9 * ROWB, svl, e1 >> 16);
            }
            cp_async_arrive(bar_full + 8 * (t & 1));
            if (s == w) reinterpret_cast<uint4*>(smem + RIDX_OFF)[((warp - 8) * 2 + (t & 1)) * 8 + (lane & 7)] = make_uint4(pos, la.y, stop ? -1 : fl, 0);
            __syncwarp();
            if (lane == 0) mbar_arrive(bar_full + 8 * (t & 1));
            TR(7, 256, t);
            pos = lb.y;
            f0 = __shfl_sync(0xffffffffu, fl, 8 * w + s);
            f1 = __shfl_sync(0xffffffffu, fl, 8 * w + 4 + s);
        }
#pragma unroll 1
        for (int z0 = nsched + (warp - 8) * 4 + s; z0 - s < zend; z0 += 128) {
#pragma unroll 1
            for (int pass = 0; pass < 2; pass++) {
#pragma unroll 1
                for (int i = 0; i < 4; i++) {
                    const int zi = z0 + 32 * i;
                    const size_t zo = (size_t)(nbase + (start[min(zi, zend - 1)].y & 511)) * 512;
                    const uint32_t row = ur + (i & 1) * ROWB + (i >> 1) * 8 * ROWB;
                    if (pass == 0) {
                        gather_row_if(row, svl + zo, zi < zend);
                    } else if (zi < zend) {
#pragma unroll
                        for (int k = 0; k < 4; k++)
                            __stcs(reinterpret_cast<uint4*>(reinterpret_cast<char*>(p.out) + zo + (lane & 7) * 16 + k * 128),
                                   *reinterpret_cast<const uint4*>(smem + (row - sb) + k * 128));
                    }
                }
                asm volatile("cp.async.wait_all;" ::: "memory");
            }
        }
        TSX(11, 256);
    }
    };
    if (__builtin_expect(cold, 0)) rest(BoolC<true>{});
    else rest(BoolC<false>{});
}

}

#define PF_ROWS 128

extern "C" void kernel_launch(void* const* d_in, const int* in_sizes, int n_in, void* d_out, int out_size) {
    static int s_G = 0;
    static void* s_scratch = nullptr;
    const int N = in_sizes[0] / 256, E = in_sizes[2];
    if (s_G == 0) {
        cudaFuncSetAttribute(painn_kernel<0, 0, 0>, cudaFuncAttributeMaxDynamicSharedMemorySize, SMEM_BYTES);
        cudaFuncSetAttribute(painn_kernel<50000, 800000, 132>, cudaFuncAttributeMaxDynamicSharedMemorySize, SMEM_BYTES);
        int dev = 0, sms = 0, occ = 0;
        cudaGetDevice(&dev);
        cudaDeviceGetAttribute(&sms, cudaDevAttrMultiProcessorCount, dev);
        cudaOccupancyMaxActiveBlocksPerMultiprocessor(&occ, painn_kernel<0, 0, 0>, THREADS, SMEM_BYTES);
        cudaGetSymbolAddress(&s_scratch, g_scratch);
        s_G = occ >= 1 ? (sms < MAXG ? sms : MAXG) : 0;
    }
    if (s_G == 0 || N > TABLE_MAXN || N > s_G * MAXNPC || (s_G - 1) * ((N + s_G - 1) / s_G) >= N || E > MAXE || E < 4 * MAXG * MAXG) return;
    Params p;
    p.g = (Scratch*)s_scratch;
    p.sv = (const __nv_bfloat16*)d_in[0];
    p.pos = (const __nv_bfloat16*)d_in[1];
    p.src = (const int*)d_in[2];
    p.dst = (const int*)d_in[3];
    p.freqs = (const __nv_bfloat16*)d_in[4];
    p.w1 = (const __nv_bfloat16*)d_in[5];
    p.w2 = (const __nv_bfloat16*)d_in[6];
    p.wr = (const __nv_bfloat16*)d_in[7];
    p.out = (__nv_bfloat16*)d_out;
    p.desc0 = (uint64_t)(SB >> 4) | ((uint64_t)1 << 16) | ((uint64_t)64 << 32) | ((uint64_t)1 << 62);
    p.N = N; p.E = E; p.G = s_G;
    p.NPC = (N + s_G - 1) / s_G;
    p.magic = (uint32_t)(((1ull << 32) + p.NPC - 1) / p.NPC);
    p.gpc = ((E >> 2) + s_G - 1) / s_G;
    p.pf_rows = PF_ROWS;
    p.odd_edges = (E & 3) != 0 || p.gpc > 3 * THREADS;
    if (N == 50000 && E == 800000 && s_G == 132) painn_kernel<50000, 800000, 132><<<s_G, THREADS, SMEM_BYTES, cudaStreamPerThread>>>(p);
    else painn_kernel<0, 0, 0><<<s_G, THREADS, SMEM_BYTES, cudaStreamPerThread>>>(p);
}
```

```cpp
#include <cuda_runtime.h>
#include <cuda_bf16.h>
#include <cuda.h>
#include <stdint.h>

namespace {

constexpr int REG_C = 224;
#define PDELAY 200
#define WA 6
#define WC 0
#define WP 0
#define WE 3
#define GROLL 0
#define RESV 0
#define SPREAD 2
#define PACE 0
#define SKIP1 1
constexpr int THREADS = 512;
constexpr int MAXG = 136;
constexpr int ROUNDS = 11;
constexpr int LUTS = 286, LUTN = 320;
constexpr int LUTG = 2048;
constexpr int MAXNPC = 480;
constexpr int MAXE = 1 << 20;

constexpr int W2_OFF = 8192;
constexpr int WR_OFF = 32768;
constexpr int WIMG = 38912;
constexpr int ZL_OFF = WIMG;
constexpr int RING_OFF = 39936;
constexpr int SIDE_OFF = RING_OFF + 16 * 8192;
constexpr int RR_OFF = SIDE_OFF + 32768;
constexpr int ND_OFF = RR_OFF + ROUNDS * 1024;
constexpr int SRC_OFF = ND_OFF + ROUNDS * 256;
constexpr int LUT_OFF = SRC_OFF + ROUNDS * 256;
constexpr int SINK_OFF = LUT_OFF + LUTN * 32;
constexpr int BAR_OFF = SINK_OFF + 512;
constexpr int MISC_OFF = BAR_OFF + 8 * 46;
constexpr int SMEM_BYTES = MISC_OFF + 192 + MAXG;
constexpr int TABLE_MAXN = 50176;
constexpr int STAGE_OFF = TABLE_MAXN * 4;
constexpr int SCNT_OFF = STAGE_OFF + MAXG * 128;
constexpr int OVL_OFF = MISC_OFF + 192;
constexpr int OPOS_OFF = LUT_OFF;
constexpr int NCNT_OFF = SIDE_OFF;
constexpr int NPOS_OFF = NCNT_OFF + 2048;
constexpr int YL_OFF = NPOS_OFF + 4096;
constexpr int SLOT_OFF = YL_OFF + 1024;
constexpr int SIZE_OFF = SLOT_OFF + 1280;
static_assert(SCNT_OFF + 4 * (MAXG + 32) <= OPOS_OFF && OPOS_OFF + 4096 <= LUT_OFF + LUTS * 32, "smem map");
static_assert(2 * (480 - 3 * MAXG) >= MAXG, "chunk map");
static_assert(SMEM_BYTES <= 232448 && MISC_OFF % 16 == 0 && BAR_OFF % 8 == 0 && (RING_OFF + 1024) % 8192 == 0 && SINK_OFF % 128 == 0, "smem map");

constexpr uint32_t PAY_INVALID = 0x3FFFFFFu;
constexpr uint32_t PAY_MARK = 0x3FFFDFFu;
constexpr uint32_t ST_START = 512, ST_CLOSE = 1024, ST_MID = 2048;
constexpr float QINVP = 9.0f / 510.0f;
constexpr uint32_t QTHRESH = 2126;

struct Scratch {
    unsigned sync[32];
    uint4 table[TABLE_MAXN / 4];
    uint4 wimg[WIMG / 16 + LUTG * 2];
    uint2 pos8[TABLE_MAXN];
    uint4 xbuf[MAXG * MAXG * 8 + 3 * THREADS];
    int ovfcnt[MAXG];
    int2 ovf[MAXE + 8 * MAXG + 8];
};
__device__ __align__(128) Scratch g_scratch;

struct Params {
    CUtensorMap tm;
    const __nv_bfloat16* pos;
    Scratch* g;
    const int* src;
    const int* dst;
    int N, NPC, E, gpc;
    const __nv_bfloat16* w2;
    const __nv_bfloat16* wr;
    const __nv_bfloat16* w1;
    const __nv_bfloat16* freqs;
    const __nv_bfloat16* sv;
    __nv_bfloat16* out;
    uint64_t desc0;
    int G;
    uint32_t magic;
    int odd_edges;
};
constexpr uint32_t SB = 1024;

#define TSX(i, thr)
#define TR(k, thr, t)
#define TS0(i) TSX(i, 0)

__device__ __forceinline__ uint32_t smem_u32(const void* p) { return (uint32_t)__cvta_generic_to_shared(p); }
__device__ __forceinline__ void mbar_init(uint32_t bar, uint32_t cnt) {
    asm volatile("mbarrier.init.shared::cta.b64 [%0], %1;" ::"r"(bar), "r"(cnt) : "memory");
}
__device__ __forceinline__ void mbar_arrive(uint32_t bar) {
    asm volatile("mbarrier.arrive.shared::cta.b64 _, [%0];" ::"r"(bar) : "memory");
}
__device__ __forceinline__ void mbar_expect_tx(uint32_t bar, uint32_t bytes) {
    asm volatile("mbarrier.arrive.expect_tx.shared::cta.b64 _, [%0], %1;" ::"r"(bar), "r"(bytes) : "memory");
}
__device__ __forceinline__ void mbar_wait(uint32_t bar, uint32_t parity) {
    asm volatile("{\n.reg .pred p;\n.reg .u32 c;\nmbarrier.try_wait.parity.shared::cta.b64 p, [%0], %1;\n@p bra DONE;\nmov.u32 c, 0;\n"
                 "AGAIN:\nmbarrier.try_wait.parity.shared::cta.b64 p, [%0], %1, 2000;\n@p bra DONE;\nadd.u32 c, c, 1;\n"
                 "setp.lt.u32 p, c, 0x100000;\n@p bra AGAIN;\ntrap;\nDONE:\n}\n" ::"r"(bar), "r"(parity) : "memory");
}
__device__ __forceinline__ bool elect() {
    uint32_t r;
    asm volatile("{\n.reg .pred p;\nelect.sync _|p, 0xffffffff;\nselp.u32 %0, 1, 0, p;\n}\n" : "=r"(r));
    return r;
}
__device__ __forceinline__ uint32_t pin(uint32_t x) {
    uint32_t r;
    asm volatile("shfl.sync.bfly.b32 %0, %1, 0, 31, -1;" : "=r"(r) : "r"(x));
    return r;
}
__device__ __forceinline__ void bulk_g2s(uint32_t dst, const void* src, uint32_t bytes, uint32_t bar) {
    asm volatile("cp.async.bulk.shared::cluster.global.mbarrier::complete_tx::bytes [%0], [%1], %2, [%3];"
                 ::"r"(dst), "l"(src), "r"(bytes), "r"(bar) : "memory");
}
__device__ __forceinline__ void ldsm4(uint32_t addr, uint32_t* r) {
    asm volatile("ldmatrix.sync.aligned.m8n8.x4.shared.b16 {%0,%1,%2,%3}, [%4];"
                 : "=r"(r[0]), "=r"(r[1]), "=r"(r[2]), "=r"(r[3]) : "r"(addr) : "memory");
}
__device__ __forceinline__ uint32_t pack2(float lo, float hi) {
    uint32_t r;
    asm("cvt.rn.bf16x2.f32 %0, %1, %2;" : "=r"(r) : "f"(hi), "f"(lo));
    return r;
}
__device__ __forceinline__ float bf_lo(uint32_t w) { return __uint_as_float(w << 16); }
__device__ __forceinline__ float bf_hi(uint32_t w) { return __uint_as_float(w & 0xFFFF0000u); }
__device__ __forceinline__ float rbf16(float x) { return __uint_as_float(pack2(0.f, x)); }
__device__ __forceinline__ uint32_t hmul2(uint32_t a, uint32_t b) {
    uint32_t r;
    asm("mul.rn.bf16x2 %0, %1, %2;" : "=r"(r) : "r"(a), "r"(b));
    return r;
}
__device__ __forceinline__ uint32_t hfma2(uint32_t a, uint32_t b, uint32_t c) {
    uint32_t r;
    asm("fma.rn.bf16x2 %0, %1, %2, %3;" : "=r"(r) : "r"(a), "r"(b), "r"(c));
    return r;
}
__device__ __forceinline__ uint32_t hfma2_lo(uint32_t a, uint32_t b, uint32_t c) {
    uint32_t r;
    asm("{\n.reg .b16 l, h;\n.reg .b32 t;\nmov.b32 {l, h}, %2;\nmov.b32 t, {l, l};\nfma.rn.bf16x2 %0, %1, t, %3;\n}\n" : "=r"(r) : "r"(a), "r"(b), "r"(c));
    return r;
}
__device__ __forceinline__ uint32_t hfma2_hi(uint32_t a, uint32_t b, uint32_t c) {
    uint32_t r;
    asm("{\n.reg .b16 l, h;\n.reg .b32 t;\nmov.b32 {l, h}, %2;\nmov.b32 t, {h, h};\nfma.rn.bf16x2 %0, %1, t, %3;\n}\n" : "=r"(r) : "r"(a), "r"(b), "r"(c));
    return r;
}
__device__ __forceinline__ uint32_t hadd2(uint32_t a, uint32_t b) {
    uint32_t r;
    asm("add.rn.bf16x2 %0, %1, %2;" : "=r"(r) : "r"(a), "r"(b));
    return r;
}
__device__ __forceinline__ uint32_t hsub2(uint32_t a, uint32_t b) {
    uint32_t r;
    asm("sub.rn.bf16x2 %0, %1, %2;" : "=r"(r) : "r"(a), "r"(b));
    return r;
}
__device__ __forceinline__ void cp_async_arrive(uint32_t bar) {
    asm volatile("cp.async.mbarrier.arrive.noinc.shared::cta.b64 [%0];" ::"r"(bar) : "memory");
}
__device__ __forceinline__ float tanh_fast(float x) {
    float r;
    asm("tanh.approx.f32 %0, %1;" : "=f"(r) : "f"(x));
    return r;
}
__device__ __forceinline__ void wg_fence() { asm volatile("wgmma.fence.sync.aligned;" ::: "memory"); }
__device__ __forceinline__ void wg_commit() { asm volatile("wgmma.commit_group.sync.aligned;" ::: "memory"); }
template <int N>
__device__ __forceinline__ void wg_wait() { asm volatile("wgmma.wait_group.sync.aligned %0;" ::"n"(N) : "memory"); }

#define WG_REGS "{%0,%1,%2,%3,%4,%5,%6,%7,%8,%9,%10,%11,%12,%13,%14,%15,%16,%17,%18,%19,%20,%21,%22,%23,%24,%25,%26,%27,%28,%29,%30,%31}"
#define WG_OPS(c) c(d[0]), c(d[1]), c(d[2]), c(d[3]), c(d[4]), c(d[5]), c(d[6]), c(d[7]), c(d[8]), c(d[9]), c(d[10]), \
    c(d[11]), c(d[12]), c(d[13]), c(d[14]), c(d[15]), c(d[16]), c(d[17]), c(d[18]), c(d[19]), c(d[20]), c(d[21]),     \
    c(d[22]), c(d[23]), c(d[24]), c(d[25]), c(d[26]), c(d[27]), c(d[28]), c(d[29]), c(d[30]), c(d[31])
template <int OFF, int ACC, int IDX>
__device__ __forceinline__ void wgmma_rs(float* d, const uint32_t* a, uint64_t d0) {
    if (!ACC) {
#pragma unroll
        for (int i = 0; i < 32; i++) d[i] = 0.f;
    }
    if (IDX < 9)
        asm volatile("wgmma.mma_async.sync.aligned.m64n64k16.f32.bf16.bf16 " WG_REGS ", {%32,%33,%34,%35}, %36, %37, 1, 1, 1;"
                     : WG_OPS("+f") : "r"(a[0]), "r"(a[1]), "r"(a[2]), "r"(a[3]), "l"(d0 + (OFF >> 4)), "n"(ACC));
    else
        asm volatile("{\n.reg .b64 dd;\nmov.b64 dd, {%36, 0x40000040};\nwgmma.mma_async.sync.aligned.m64n64k16.f32.bf16.bf16 " WG_REGS
                     ", {%32,%33,%34,%35}, dd, %37, 1, 1, 1;\n}\n"
                     : WG_OPS("+f") : "r"(a[0]), "r"(a[1]), "r"(a[2]), "r"(a[3]), "n"(((SB + OFF) >> 4) | (1u << 16)), "n"(ACC));
}
template <int G>
__device__ __forceinline__ void wgmma_group(float* P, float* W, const uint32_t* h, const uint32_t* rf, uint64_t d0) {
    wgmma_rs<W2_OFF + 8192 * G, 0, 5 * G>(P, h, d0);
    wgmma_rs<W2_OFF + 8192 * G + 2048, 1, 5 * G + 1>(P, h + 4, d0);
    wgmma_rs<W2_OFF + 8192 * G + 4096, 1, 5 * G + 2>(P, h + 8, d0);
    wgmma_rs<W2_OFF + 8192 * G + 6144, 1, 5 * G + 3>(P, h + 12, d0);
    wgmma_rs<WR_OFF + 2048 * G, 0, 5 * G + 4>(W, rf, d0);
}
__device__ __forceinline__ void wgmma_ss_k64(float* d, uint64_t da, uint64_t db) {
#pragma unroll
    for (int i = 0; i < 32; i++) d[i] = 0.f;
    asm volatile("wgmma.mma_async.sync.aligned.m64n64k16.f32.bf16.bf16 " WG_REGS ", %32, %33, 0, 1, 1, 0, 1;" : WG_OPS("+f") : "l"(da), "l"(db));
#pragma unroll
    for (int k = 1; k < 4; k++)
        asm volatile("wgmma.mma_async.sync.aligned.m64n64k16.f32.bf16.bf16 " WG_REGS ", %32, %33, 1, 1, 1, 0, 1;"
                     : WG_OPS("+f") : "l"(da + 2 * k), "l"(db + 128 * k));
}
__device__ __forceinline__ void fence_regs(float* d) { asm volatile("" : WG_OPS("+f")::"memory"); }
__device__ __forceinline__ uint32_t qaxis(float x) {
    const float u = fmaf(x, QINVP, 0.25f);
    const float f = u - ((u + 12582912.f) - 12582912.f);
    return __float_as_uint(fmaf(fabsf(f), 510.f, 12582912.f));
}
__device__ __forceinline__ uint32_t qcode(float x, float y, float z, uint32_t tx) {
    return __byte_perm(__byte_perm(qaxis(x), qaxis(y), 0x3340), qaxis(z), 0x3410) ^ tx;
}
__device__ __forceinline__ bool near_test(uint32_t ca, uint32_t cb, uint32_t tag24) {
    const uint32_t D = __vabsdiffu4(ca, cb);
    return __dp4a(D, D, 0u) <= QTHRESH || ((ca ^ tag24) | (cb ^ tag24)) >= 0x1000000u;
}
constexpr float QMAX = 23.9375f;
__device__ __forceinline__ float square(uint32_t rxy, uint32_t rz) {
    const uint32_t qxy = hmul2(rxy, rxy), qz = hmul2(rz, rz);
    return bf_lo(qxy) + bf_hi(qxy) + bf_lo(qz);
}

__device__ __forceinline__ uint32_t lds32(uint32_t addr) {
    uint32_t r;
    asm volatile("ld.shared.u32 %0, [%1];" : "=r"(r) : "r"(addr) : "memory");
    return r;
}
__device__ __forceinline__ void sts32_if(uint32_t addr, uint32_t v, bool c) {
    asm volatile("{\n.reg .pred p;\nsetp.ne.u32 p, %2, 0;\n@p st.shared.u32 [%0], %1;\n}\n" ::"r"(addr), "r"(v), "r"((uint32_t)c) : "memory");
}
__device__ __forceinline__ uint32_t lds16(uint32_t addr) {
    uint32_t r;
    asm volatile("ld.shared.u16 %0, [%1];" : "=r"(r) : "r"(addr) : "memory");
    return r;
}
__device__ __forceinline__ void sts16_if(uint32_t addr, uint32_t v, bool c) {
    asm volatile("{\n.reg .pred p;\nsetp.ne.u32 p, %2, 0;\n@p st.shared.u16 [%0], %1;\n}\n" ::"r"(addr), "h"((unsigned short)v), "r"((uint32_t)c) : "memory");
}
__device__ __forceinline__ void sts64_if(uint32_t addr, uint32_t x, uint32_t y, bool c) {
    asm volatile("{\n.reg .pred p;\nsetp.ne.u32 p, %3, 0;\n@p st.shared.v2.u32 [%0], {%1, %2};\n}\n" ::"r"(addr), "r"(x), "r"(y), "r"((uint32_t)c) : "memory");
}
__device__ __forceinline__ uint32_t atoms_add(uint32_t addr, uint32_t v) {
    uint32_t r;
    asm volatile("atom.shared.add.u32 %0, [%1], %2;" : "=r"(r) : "r"(addr), "r"(v) : "memory");
    return r;
}
__device__ __forceinline__ void stg128_if(void* ptr, uint4 v, bool c) {
    asm volatile("{\n.reg .pred p;\nsetp.ne.u32 p, %5, 0;\n@p st.relaxed.gpu.global.v4.u32 [%0], {%1,%2,%3,%4};\n}\n"
                 ::"l"(ptr), "r"(v.x), "r"(v.y), "r"(v.z), "r"(v.w), "r"((uint32_t)c) : "memory");
}
__device__ __forceinline__ void lds128(uint32_t addr, uint32_t* r) {
    asm volatile("ld.shared.v4.u32 {%0,%1,%2,%3}, [%4];" : "=r"(r[0]), "=r"(r[1]), "=r"(r[2]), "=r"(r[3]) : "r"(addr) : "memory");
}
__device__ __forceinline__ void stg2_fl(uint64_t ptr, const uint32_t* r, uint32_t fl) {
    asm volatile("{\n.reg .pred p;\n.reg .b32 t;\nand.b32 t, %9, 1024;\nsetp.ne.u32 p, t, 0;\n@p st.global.cs.v4.u32 [%8], {%0,%1,%2,%3};\n"
                 "@p st.global.cs.v4.u32 [%8 + 64], {%4,%5,%6,%7};\n}\n"
                 ::"r"(r[0]), "r"(r[1]), "r"(r[2]), "r"(r[3]), "r"(r[4]), "r"(r[5]), "r"(r[6]), "r"(r[7]), "l"(ptr), "r"(fl) : "memory");
}
__device__ __forceinline__ void gather_s(uint32_t dst, const char* base, uint32_t src) {
    asm volatile("{\n.reg .pred p;\nsetp.eq.u32 p, %2, 0xFFFF;\ncp.async.cg.shared.global [%0], [%1], 16, p;\n}\n"
                 ::"r"(dst), "l"(base + (size_t)src * 512), "r"(src) : "memory");
}
__device__ __forceinline__ void gather_v(uint32_t dst, const char* base, uint32_t src) {
    asm volatile("{\n.reg .pred p;\nsetp.eq.u32 p, %2, 0xFFFF;\n"
                 "cp.async.cg.shared.global [%0 + 1024], [%1 + 128], 16, p;\ncp.async.cg.shared.global [%0 + 2048], [%1 + 256], 16, p;\n"
                 "cp.async.cg.shared.global [%0 + 3072], [%1 + 384], 16, p;\n}\n" ::"r"(dst), "l"(base + (size_t)src * 512), "r"(src) : "memory");
}
__device__ __forceinline__ void gather_row_if(uint32_t dst, const char* src, uint32_t c) {
    asm volatile("{\n.reg .pred p;\nsetp.ne.u32 p, %2, 0;\n@p cp.async.cg.shared.global [%0], [%1], 16;\n"
                 "@p cp.async.cg.shared.global [%0 + 1024], [%1 + 128], 16;\n@p cp.async.cg.shared.global [%0 + 2048], [%1 + 256], 16;\n"
                 "@p cp.async.cg.shared.global [%0 + 3072], [%1 + 384], 16;\n}\n" ::"r"(dst), "l"(src), "r"(c) : "memory");
}
__device__ __forceinline__ void lds2_if(uint32_t a0, uint32_t a1, uint32_t* r, uint32_t c) {
    asm volatile("{\n.reg .pred p;\nsetp.ne.u32 p, %10, 0;\n@p ld.shared.v4.u32 {%0,%1,%2,%3}, [%8];\n@p ld.shared.v4.u32 {%4,%5,%6,%7}, [%9];\n}\n"
                 : "+r"(r[0]), "+r"(r[1]), "+r"(r[2]), "+r"(r[3]), "+r"(r[4]), "+r"(r[5]), "+r"(r[6]), "+r"(r[7])
                 : "r"(a0), "r"(a1), "r"(c) : "memory");
}
__device__ __forceinline__ int fresh_lane() {
    int l;
    asm volatile("mov.u32 %0, %%laneid;" : "=r"(l));
    return l;
}

__device__ __forceinline__ void cold_edges(unsigned char* smem, const Params& p, int lo, int hi, uint32_t tag) {
#pragma unroll 1
    for (int e = lo + threadIdx.x; e < hi; e += THREADS) {
        const int s = p.src[e], d = p.dst[e];
        if (near_test(reinterpret_cast<const uint32_t*>(smem)[s], reinterpret_cast<const uint32_t*>(smem)[d], tag << 24)) {
            const uint32_t own = __umulhi((uint32_t)d, p.magic);
            const uint32_t slot4 = atomicAdd(reinterpret_cast<uint32_t*>(smem + SCNT_OFF) + own, 4u);
            uint32_t* line = reinterpret_cast<uint32_t*>(smem + STAGE_OFF) + own * 32;
            if (slot4 < 124) {
                line[slot4 >> 2] = ((uint32_t)s << 15) + ((uint32_t)(d - own * p.NPC) << 6) + tag;
            } else {
                uint32_t o = atomicAdd(reinterpret_cast<uint32_t*>(smem + MISC_OFF) + 16, 1u);
                p.g->ovf[(size_t)blockIdx.x * (4 * p.gpc + 4) + o] = make_int2(s, d);
                line[31] = (PAY_MARK << 6) | tag;
            }
        }
    }
}
__device__ __forceinline__ void cold_filter(unsigned char* smem, const Params& p, int e0, int e1, uint32_t tag, int redo) {
    if (redo) {
        if (threadIdx.x < MAXG) reinterpret_cast<uint32_t*>(smem + SCNT_OFF)[threadIdx.x] = 0;
        __syncthreads();
    }
    cold_edges(smem, p, redo ? 4 * e0 : 4 * (e0 + 3 * THREADS), 4 * e1, tag);
    if (blockIdx.x == 0) cold_edges(smem, p, p.E & ~3, p.E, tag);
    __syncthreads();
    if (threadIdx.x == 0) p.g->ovfcnt[blockIdx.x] = reinterpret_cast<uint32_t*>(smem + MISC_OFF)[16];
    __threadfence();
    __syncthreads();
}
__device__ __forceinline__ float distance(uint32_t rxy, uint32_t rz) {
    float d;
    asm("sqrt.approx.ftz.f32 %0, %1;" : "=f"(d) : "f"(rbf16(rbf16(square(rxy, rz)) + 1e-8f)));
    return rbf16(d);
}
__device__ __forceinline__ float fcut(float d) {
    return d < 5.0f ? 0.5f * rbf16(rbf16(__cosf(rbf16(rbf16(3.14159265358979f * d) * 0.2f))) + 1.0f) : 0.f;
}
__device__ __forceinline__ uint4 basis8(float d, uint4 f) {
    const float sc = __fdividef(fcut(d), d);
    const uint32_t dd = __byte_perm(__float_as_uint(d), 0, 0x3232);
    uint32_t x[4] = {hmul2(f.x, dd), hmul2(f.y, dd), hmul2(f.z, dd), hmul2(f.w, dd)};
#pragma unroll
    for (int i = 0; i < 4; i++) x[i] = pack2(__sinf(bf_lo(x[i])) * sc, __sinf(bf_hi(x[i])) * sc);
    return make_uint4(x[0], x[1], x[2], x[3]);
}
__device__ __forceinline__ void cold_nodes(unsigned char* smem, const Params& p, int nn, uint32_t tag) {
    float* acc = reinterpret_cast<float*>(smem + RING_OFF);
    const int nbase = blockIdx.x * p.NPC, lane = threadIdx.x & 31;
    const uint32_t* sv = reinterpret_cast<const uint32_t*>(p.sv);
    const volatile uint32_t* xin = reinterpret_cast<const uint32_t*>(p.g->xbuf) + blockIdx.x * p.G * 32;
#pragma unroll 1
    for (int i = threadIdx.x; i < p.G * 32; i += THREADS) {
        if (xin[(i & ~31) + 15] < (PAY_MARK << 6)) {
            uint32_t w;
            int it = 0;
            do {
                w = xin[i];
                if (++it > (1 << 22)) __trap();
            } while ((w ^ tag) & 63u);
            if ((w >> 6) == PAY_MARK) smem[OVL_OFF + atomicAdd(reinterpret_cast<uint32_t*>(smem + MISC_OFF) + 17, 1u)] = (unsigned char)(i >> 5);
        }
    }
    __threadfence();
    __syncthreads();
    const int nmark = reinterpret_cast<uint32_t*>(smem + MISC_OFF)[17];
#pragma unroll 1
    for (int c0 = 0; c0 < nn; c0 += 128) {
        __syncthreads();
#pragma unroll 1
        for (int i = threadIdx.x; i < 128 * 256; i += THREADS) acc[i] = 0.f;
        __syncthreads();
#pragma unroll 1
        for (int m = -1; m < nmark; m++) {
            const int pr = m < 0 ? 0 : smem[OVL_OFF + m];
            const int cnt = m < 0 ? p.G * 32 : __ldcg(&p.g->ovfcnt[pr]);
#pragma unroll 1
            for (int i = threadIdx.x; i - lane < cnt; i += THREADS) {
                int2 e = make_int2(0, -1);
                if (i < cnt) {
                    if (m < 0) {
                        const uint32_t w = xin[i];
                        if (((w ^ tag) & 63u) == 0) e = make_int2(w >> 15, (w >> 6) & 511u);
                    } else {
                        e = __ldcg(p.g->ovf + (size_t)pr * (4 * p.gpc + 4) + i);
                        e.y -= nbase;
                    }
                }
                uint32_t rxy = 0, rz = 0;
                bool in = e.y >= c0 && e.y < min(c0 + 128, nn);
                if (in) {
                    const uint2 ps = __ldcg(p.g->pos8 + e.x), pd = __ldcg(p.g->pos8 + nbase + e.y);
                    rxy = hsub2(ps.x, pd.x);
                    rz = hsub2(ps.y, pd.y);
                    in = square(rxy, rz) < QMAX;
                }
#pragma unroll 1
                for (uint32_t todo = __ballot_sync(0xffffffffu, in); todo; todo &= todo - 1) {
                    const int l = __ffs(todo) - 1;
                    const uint32_t* row = sv + (size_t)__shfl_sync(0xffffffffu, e.x, l) * 128 + lane;
                    float* o = acc + (__shfl_sync(0xffffffffu, e.y, l) - c0) * 256 + 2 * lane;
                    const uint32_t xy = __shfl_sync(0xffffffffu, rxy, l), z = __shfl_sync(0xffffffffu, rz, l);
                    const float d = distance(xy, z), fc = fcut(d);
                    uint32_t x = __ldg(row);
                    float y0 = 0.f, y1 = 0.f, m2[6];
#pragma unroll 4
                    for (int k = 0; k < 64; k++) {
                        const uint32_t u = __shfl_sync(0xffffffffu, x, k >> 1), w = __ldg(reinterpret_cast<const uint32_t*>(p.w1) + k * 32 + lane);
                        const float a = k & 1 ? bf_hi(u) : bf_lo(u);
                        y0 = fmaf(a, bf_lo(w), y0);
                        y1 = fmaf(a, bf_hi(w), y1);
                    }
                    y0 = rbf16(y0); y1 = rbf16(y1);
                    x = pack2(y0 / (1.f + __expf(-y0)), y1 / (1.f + __expf(-y1)));
                    const float rb = rbf16(rbf16(__sinf(rbf16(d * __bfloat162float(p.freqs[lane & 15])))) / d);
#pragma unroll
                    for (int g = 0; g < 3; g++) {
                        float p0 = 0.f, p1 = 0.f, w0 = 0.f, w1 = 0.f;
#pragma unroll 4
                        for (int k = 0; k < 64; k++) {
                            const uint32_t u = __shfl_sync(0xffffffffu, x, k >> 1), w = __ldg(reinterpret_cast<const uint32_t*>(p.w2) + k * 96 + g * 32 + lane);
                            const float a = k & 1 ? bf_hi(u) : bf_lo(u);
                            p0 = fmaf(a, bf_lo(w), p0);
                            p1 = fmaf(a, bf_hi(w), p1);
                        }
#pragma unroll 4
                        for (int k = 0; k < 16; k++) {
                            const uint32_t w = __ldg(reinterpret_cast<const uint32_t*>(p.wr) + k * 96 + g * 32 + lane);
                            const float a = __shfl_sync(0xffffffffu, rb, k);
                            w0 = fmaf(a, bf_lo(w), w0);
                            w1 = fmaf(a, bf_hi(w), w1);
                        }
                        m2[2 * g] = rbf16(rbf16(p0) * rbf16(rbf16(w0) * fc));
                        m2[2 * g + 1] = rbf16(rbf16(p1) * rbf16(rbf16(w1) * fc));
                    }
                    atomicAdd(o, m2[0]);
                    atomicAdd(o + 1, m2[1]);
#pragma unroll
                    for (int k = 1; k < 4; k++) {
                        const uint32_t v = __ldg(row + 32 * k);
                        const float rh = rbf16((k == 1 ? bf_lo(xy) : k == 2 ? bf_hi(xy) : bf_lo(z)) / d);
                        atomicAdd(o + 64 * k, fmaf(m2[2], bf_lo(v), m2[4] * rh));
                        atomicAdd(o + 64 * k + 1, fmaf(m2[3], bf_hi(v), m2[5] * rh));
                    }
                }
            }
        }
        __syncthreads();
#pragma unroll 1
        for (int i = threadIdx.x; i < min(128, nn - c0) * 128; i += THREADS) {
            const uint32_t v = __ldg(sv + (size_t)(nbase + c0) * 128 + i);
            reinterpret_cast<uint32_t*>(p.out)[(size_t)(nbase + c0) * 128 + i] = pack2(bf_lo(v) + rbf16(acc[2 * i]), bf_hi(v) + rbf16(acc[2 * i + 1]));
        }
    }
}

template <int CN, int CE, int CG>
__global__ void __launch_bounds__(THREADS, 1) painn_kernel(const __grid_constant__ Params p) {
    extern __shared__ __align__(1024) unsigned char smem_dyn[];
    unsigned char* const smem = static_cast<unsigned char*>(__cvta_shared_to_generic(SB));
    constexpr uint32_t sb = SB;
    const int tid = threadIdx.x, lane = tid & 31;
    const int warp = __shfl_sync(0xffffffffu, tid >> 5, 0);
    constexpr int CNPC = CG ? (CN + CG - 1) / CG : 1, CGPC = CG ? (CE / 4 + CG - 1) / CG : 1;
    const int b = blockIdx.x, G = CG ? CG : p.G, NPC = CG ? CNPC : p.NPC, N = CG ? CN : p.N, gpc = CG ? CGPC : p.gpc;
    const uint32_t magic = CG ? (uint32_t)(((1ull << 32) + CNPC - 1) / CNPC) : p.magic;
    const bool odd_edges = CG ? (CE & 3) != 0 || CGPC > 3 * THREADS : p.odd_edges;
    const int nbase = b * NPC, nn = min(NPC, N - nbase);
    const int e0 = b * gpc, e1 = min((CG ? CE : p.E) >> 2, e0 + gpc);

    uint4* stage4 = reinterpret_cast<uint4*>(smem + STAGE_OFF);
    uint32_t* ncnt = reinterpret_cast<uint32_t*>(smem + NCNT_OFF);
    uint32_t* misc = reinterpret_cast<uint32_t*>(smem + MISC_OFF);
    const uint32_t bar_full = sb + BAR_OFF + (warp & 7) * 40, bar_empty = bar_full + 16, bar_side = bar_full + 32, bar_tab = sb + BAR_OFF + 336;

    auto warm = [&](int first, int n, int pause) {
#pragma unroll 1
        for (int i = first; i < first + n; i++) {
            if (elect())
                asm volatile("cp.async.bulk.tensor.2d.shared::cluster.global.mbarrier::complete_tx::bytes [%0], [%1, {0, %3}], [%2];"
                             ::"r"(sb + SINK_OFF), "l"(&p.tm), "r"(bar_tab + 8), "r"(nbase * 4 + i * 32) : "memory");
            if (pause) __nanosleep(pause);
        }
    };
    TS0(0);
    int4 es[3], ed[3];
    auto load_edges = [&](int i) {
        const int g = min(e0 + tid + i * THREADS, e1 - 1);
        asm volatile("ld.global.cs.v4.u32 {%0,%1,%2,%3}, [%8];\nld.global.cs.v4.u32 {%4,%5,%6,%7}, [%9];"
                     : "=r"(es[i].x), "=r"(es[i].y), "=r"(es[i].z), "=r"(es[i].w), "=r"(ed[i].x), "=r"(ed[i].y), "=r"(ed[i].z), "=r"(ed[i].w)
                     : "l"(reinterpret_cast<const int4*>(p.src) + g), "l"(reinterpret_cast<const int4*>(p.dst) + g) : "memory");
    };
    unsigned epoch;
    const uint32_t tbytes = ((N + 3) >> 2) * 16;
    {
        uint32_t pxy, pz;
        asm volatile("ld.global.nc.u32 %0, [%3];\nld.global.nc.u32 %1, [%3 + 4];\nld.global.ca.u32 %2, [%4];"
                     : "=r"(pxy), "=r"(pz), "=r"(epoch)
                     : "l"(reinterpret_cast<const uint32_t*>(p.pos) + ((nbase + min(tid, nn - 1)) * 3 >> 1)), "l"(p.g->sync) : "memory");
        const uint32_t sh = ((nbase + tid) & 1) << 4;
        pxy = __funnelshift_r(pxy, pz, sh);
        pz >>= sh;
        if (tid < nn) {
            reinterpret_cast<uint32_t*>(p.g->table)[nbase + tid] = qcode(bf_lo(pxy), bf_hi(pxy), bf_lo(pz), ((epoch & 31u) ^ 0x6Bu) << 24);
            p.g->pos8[nbase + tid] = make_uint2(pxy, pz);
        }
        reinterpret_cast<uint2*>(smem + OPOS_OFF)[tid] = make_uint2(pxy, pz);
        if (pxy == 0xFFFFFFFFu && pz == 0xFFFFFFFFu && epoch == 0xFFFFFFFFu) asm volatile("nanosleep.u32 0;");
        load_edges(0);
    }
    __syncthreads();
    const uint32_t tag = (epoch & 31u) | 32u;
    if (warp == 15) {
        if (elect()) {
            asm volatile("red.relaxed.gpu.global.add.u32 [%0], 1;" ::"l"(p.g->sync + 1) : "memory");
            asm volatile("prefetch.tensormap [%0];" ::"l"(&p.tm) : "memory");
            mbar_init(bar_tab, 1);
            mbar_init(bar_tab + 8, 1);
            mbar_init(bar_tab + 16, 96);
                        mbar_expect_tx(bar_tab, tbytes);
            mbar_expect_tx(bar_tab + 8, (WA + WC + WE) * 512);
        }
        TSX(1, 511);
        const unsigned want = (epoch + 1) * G;
        unsigned c;
        int it = smem_u32(smem_dyn) == SB ? 0 : 1 << 22;
        do {
            asm volatile("ld.relaxed.gpu.global.u32 %0, [%1];" : "=r"(c) : "l"(p.g->sync + 1) : "memory");
            if (++it > (1 << 22)) __trap();
        } while (c != want);
        __syncwarp();
        if (elect()) bulk_g2s(sb, p.g->table, tbytes, bar_tab);
        TSX(2, 511);
    }
    if (warp == 13 || warp == 14) {
#pragma unroll 1
        for (int c = b * 64 + tid - 416; c < WIMG / 16 + LUTG * 2; c += G * 64) {
            const int row = c >> 3, j = (c ^ row) & 7;
            uint4 v;
            if (c < 512) {
                const uint32_t half = 0x3F003F00u;
                v = __ldg(reinterpret_cast<const uint4*>(p.w1) + row * 8 + j);
                v = make_uint4(hmul2(v.x, half), hmul2(v.y, half), hmul2(v.z, half), hmul2(v.w, half));
            } else if (c >= WIMG / 16) {
                v = basis8(__uint_as_float((0x409D - ((c - WIMG / 16) >> 1)) << 16), __ldg(reinterpret_cast<const uint4*>(p.freqs) + (c & 1)));
            } else {
                const uint32_t* q = (c < 2048 ? reinterpret_cast<const uint32_t*>(p.w2) + (row & 63) * 96 + ((row >> 6) - 1) * 32
                                              : reinterpret_cast<const uint32_t*>(p.wr) + (row & 15) * 96 + ((row >> 4) - 16) * 32) + (j & 4) * 4 + (j & 3);
                v = make_uint4(__ldg(q), __ldg(q + 4), __ldg(q + 8), __ldg(q + 12));
            }
            p.g->wimg[c] = v;
        }
    }
    if (warp < 8 && elect()) {
        mbar_init(bar_full, 32); mbar_init(bar_full + 8, 32);
        mbar_init(bar_empty, 1);
        mbar_init(bar_side, 32);
        mbar_init(bar_full + 24, 1);
    }
    if (tid < MAXG) reinterpret_cast<uint32_t*>(smem + SCNT_OFF)[tid] = 0;
    if (tid < 48) misc[tid] = 0;
    {
        const uint32_t inv = (PAY_INVALID << 6) | tag;
        stage4[tid] = stage4[tid + THREADS] = make_uint4(inv, inv, inv, inv);
        if (tid < MAXG * 8 - 2 * THREADS) stage4[tid + 2 * THREADS] = make_uint4(inv, inv, inv, inv);
    }
    __syncthreads();
    uint4* const xout = p.g->xbuf + ((tid >> 3) * G + b) * 8 + (tid & 7);
#pragma unroll
    for (int i = 0; i < 3; i++) stg128_if(xout + i * G * THREADS, make_uint4(0, 0, 0, 0), tid + i * THREADS < G * 8);
    load_edges(1);
    load_edges(2);
    if (tid == THREADS - 1) asm volatile("fence.acq_rel.gpu;" ::: "memory");
    mbar_wait(bar_tab, 0);
    TS0(3);
    if (warp == 15) warm(0, WA, 0);

#pragma unroll 1
    for (int i = 0, g = e0 + tid; i < 3; i++, g += THREADS) {
        const int s[4] = {es[0].x, es[0].y, es[0].z, es[0].w}, d[4] = {ed[0].x, ed[0].y, ed[0].z, ed[0].w};
        uint32_t ca[4], cb[4], own[4], sl[4];
        bool c[4];
#pragma unroll
        for (int j = 0; j < 4; j++) { ca[j] = lds32(sb + 4 * s[j]); cb[j] = lds32(sb + 4 * d[j]); }
#pragma unroll
        for (int j = 0; j < 4; j++) {
            c[j] = near_test(ca[j], cb[j], tag << 24) && g < e1;
            own[j] = __umulhi((uint32_t)d[j], magic);
            sl[j] = atomicAdd(reinterpret_cast<uint32_t*>(smem + SCNT_OFF) + (c[j] ? own[j] : MAXG + lane), 4u);
        }
#pragma unroll
        for (int j = 0; j < 4; j++)
            sts32_if(sb + STAGE_OFF + own[j] * 128 + sl[j], own[j] * (uint32_t)(-64 * NPC) + (((uint32_t)s[j] << 15) + (((uint32_t)d[j] << 6) + tag)),
                     c[j] && sl[j] < 124);
        es[0] = es[1]; es[1] = es[2];
        ed[0] = ed[1]; ed[1] = ed[2];
    }
    __syncthreads();
    {
        const int redo = __syncthreads_or(tid < MAXG && reinterpret_cast<uint32_t*>(smem + SCNT_OFF)[tid] > 124);
        if (__builtin_expect(redo || odd_edges, 0)) cold_filter(smem, p, e0, e1, tag, redo);
    }
    TS0(4);
#pragma unroll
    for (int i = 0; i < 2; i++) {
        const int r = min((tid >> 2) + i * (THREADS / 4), G), c = r * 8 + (tid & 3);
        uint4* const x = p.g->xbuf + (r * G + b) * 8 + (tid & 3);
        stg128_if(x, stage4[c], r < G);
        if (__builtin_expect(reinterpret_cast<uint32_t*>(smem + SCNT_OFF)[r] >= 64 && r < G, 0)) stg128_if(x + 4, stage4[c + 4], true);
    }
    ncnt[tid] = 0;
    if (tid < 480) reinterpret_cast<uint32_t*>(smem + SLOT_OFF)[tid] = tid < 32 ? tid * 0x100010 + 0x80000 : tid < 320 ? ~0u : 0u;
    if (tid == 511) reinterpret_cast<uint2*>(smem + NPOS_OFF)[511] = make_uint2(sb + SLOT_OFF + 1278, 0);
    __syncthreads();
    reinterpret_cast<uint4*>(smem + RR_OFF)[tid] = make_uint4(0, 0, 0, 0);
    if (tid < ROUNDS * 80 - THREADS) reinterpret_cast<uint4*>(smem + RR_OFF)[tid + THREADS] = make_uint4(0, 0, 0, 0);
    if (tid < ROUNDS * 32) reinterpret_cast<uint2*>(smem + SRC_OFF)[tid] = make_uint2(~0u, ~0u);
    __nanosleep(PDELAY);
    TS0(5);

    uint32_t rxy[4], rzs[4], rk[4], dn[4];
    const uint32_t sink = sb + NCNT_OFF + 4 * (480 + lane);
    if (warp < 15) {
        uint32_t ew[3][4], bad[2];
        const int u = tid - 3 * G;
        const uint4* const xin = p.g->xbuf + b * G * 8;
        const uint4* cp = xin + (u < 0 ? tid + tid / 3 * 5 : u * 8 + 3);
        bad[0] = u < G;
        bad[1] = u >= 0 && u + 480 - 3 * G < G;
#pragma unroll
        for (int i = 0; i < 3; i++) ew[i][0] = ew[i][1] = ew[i][2] = ew[i][3] = (PAY_INVALID << 6) | tag;
        int it = 0;
#pragma unroll 1
        do {
#pragma unroll
            for (int i = 0; i < 2; i++)
                asm volatile("{\n.reg .pred p;\nsetp.ne.u32 p, %5, 0;\n@p ld.relaxed.gpu.global.v4.u32 {%0,%1,%2,%3}, [%4];\n}\n"
                             : "+r"(ew[i][0]), "+r"(ew[i][1]), "+r"(ew[i][2]), "+r"(ew[i][3]) : "l"(cp + i * (480 - 3 * G) * 8), "r"(bad[i]) : "memory");
#pragma unroll
            for (int i = 0; i < 2; i++) bad[i] = ((ew[i][0] ^ tag) | (ew[i][1] ^ tag) | (ew[i][2] ^ tag) | (ew[i][3] ^ tag)) & 63u;
            if (++it > (1 << 22)) __trap();
        } while (__any_sync(0xffffffffu, bad[0] | bad[1]));
        if (warp >= (3 * G) >> 5) {
            const uint32_t f0 = __ballot_sync(0xffffffffu, u >= 0 && ew[0][3] < (PAY_MARK << 6)), f1 = __ballot_sync(0xffffffffu, ew[1][3] < (PAY_MARK << 6));
            if (__builtin_expect(f0 | f1, 0)) {
                uint64_t f = (uint64_t)f1 << 32 | f0;
#pragma unroll 1
                for (int k = 7 - (lane >> 2); k; k--) f &= f - 1;
                if (f) {
                    const int l = __ffsll(f) - 1;
                    do {
                        asm volatile("ld.relaxed.gpu.global.v4.u32 {%0,%1,%2,%3}, [%4];" : "=r"(ew[2][0]), "=r"(ew[2][1]), "=r"(ew[2][2]), "=r"(ew[2][3])
                                     : "l"(xin + (u - lane + l + (l >> 5) * (448 - 3 * G)) * 8 + 4 + (lane & 3)) : "memory");
                        if (++it > (1 << 22)) __trap();
                    } while (((ew[2][0] ^ tag) | (ew[2][1] ^ tag) | (ew[2][2] ^ tag) | (ew[2][3] ^ tag)) & 63u);
                    if ((ew[2][3] >> 6) == PAY_MARK || lane == 0) misc[0] = 1;
                }
                __syncwarp();
            }
#pragma unroll 1
            for (int i = 0; i < 2; i++) {
                if (ew[0][0] >= (PAY_MARK << 6)) {
#pragma unroll
                    for (int j = 0; j < 4; j++) { ew[0][j] = ew[1][j]; ew[1][j] = ~0u; }
                }
                uint32_t from = __ballot_sync(0xffffffffu, ew[1][0] < (PAY_MARK << 6)), to = __ballot_sync(0xffffffffu, ew[0][0] >= (PAY_MARK << 6));
#pragma unroll 1
                for (; from; from &= from - 1, to &= to - 1) {
                    if (!to) misc[0] = 1;
#pragma unroll
                    for (int j = 0; j < 4; j++) {
                        const uint32_t x = __shfl_sync(0xffffffffu, ew[1][j], __ffs(from) - 1);
                        if (lane == __ffs(to) - 1) ew[0][j] = x;
                    }
                }
#pragma unroll
                for (int j = 0; j < 4; j++) ew[1][j] = ew[2][j];
            }
        }
        {
            uint2 ps[4], pd[4];
#pragma unroll
            for (int j = 0; j < 4; j++) {
                dn[j] = (ew[0][j] >> 3) & 4088u;
                ps[j] = __ldcg(p.g->pos8 + (dn[j] == 4088u ? nbase : ew[0][j] >> 15));
            }
#pragma unroll
            for (int j = 0; j < 4; j++) pd[j] = *reinterpret_cast<const uint2*>(smem + OPOS_OFF + dn[j]);
#pragma unroll
            for (int j = 0; j < 4; j++) {
                rxy[j] = hsub2(ps[j].x, pd[j].x);
                const uint32_t rz = hsub2(ps[j].y, pd[j].y);
                const float q = square(rxy[j], rz);
                const bool in = q < QMAX && dn[j] != 4088u;
                rzs[j] = __byte_perm(ew[0][j] >> 15, rz, 0x5410);
                rk[j] = atoms_add(in ? sb + NCNT_OFF + (dn[j] >> 1) : sink, 512u);
                if (!in) dn[j] = 4088u;
            }
        }
    } else {
        warm(WA, WC, WP);
    }
    __syncthreads();
    TS0(6);

    const uint32_t lt = (1u << lane) - 1;
    uint32_t place = ~0u, last = 0, steps = 0;
    if (warp < 15) {
        const uint32_t c = tid < nn ? ncnt[tid] >> 9 : 0u;
        steps = min((c + 1) >> 1, 15u);
        const uint32_t bin = tid >= nn ? 9 : c < 2 ? 8 - c : 7 - min(steps, 7u), sh = (bin & 1) * 16;
        const bool odd = c > 1 && (c & 1);
        const uint32_t peers = __match_any_sync(0xffffffffu, bin), om = __ballot_sync(0xffffffffu, odd);
        uint32_t x = atoms_add(lane == 0 ? sb + MISC_OFF + 4 * 37 : sink, __popc(om));
        uint32_t r = atoms_add((peers & lt) == 0 ? sb + MISC_OFF + 4 * 32 + 2 * (bin & 14) : sink, __popc(peers) << sh);
        x = __shfl_sync(0xffffffffu, x, 0) + __popc(om & lt);
        r = ((__shfl_sync(0xffffffffu, r, __ffs(peers) - 1) >> sh) & 0xFFFFu) + __popc(peers & lt);
        sts16_if(sb + (bin == 7 ? YL_OFF : ZL_OFF) + 2 * r, tid, bin == 7 || bin == 8);
        const uint64_t ones = 0x0001010101010101ull >> (56 - 8 * min(bin, 7u));
        asm volatile("bar.sync 2, 480;" ::: "memory");
        uint32_t h[4];
        lds128(sb + MISC_OFF + 4 * 32, h);
        const uint32_t y = lds16(sb + YL_OFF + 2 * x), nodd = misc[37], none = h[3] >> 16;
        const uint32_t base = __dp2a_lo(h[0], (uint32_t)ones, __dp2a_hi(h[1], (uint32_t)ones, 0u)) +
                              __dp2a_lo(h[2], (uint32_t)(ones >> 32), __dp2a_hi(h[3], (uint32_t)(ones >> 32), 0u));
        const bool unit = bin < 7 || (bin == 7 && r >= nodd), pair = odd && x < none;
        if (unit) place = base + r - (bin == 7 ? nodd : 0);
        if (bin >= 7) misc[4] = base + max((int)(none - nodd), 0);
        last = pair ? y | ST_CLOSE | ST_MID | (tid << 16) : tid | ST_CLOSE;
        const uint32_t sa = sb + SLOT_OFF + (steps < ROUNDS ? 2 * place : 1278);
        sts64_if(sb + NPOS_OFF + 8 * tid, sa, 0, unit);
        sts64_if(sb + NPOS_OFF + 8 * y, sa, c << 9, pair);
        asm volatile("{\n.reg .pred p;\nsetp.ne.u32 p, %2, 0;\n@p st.shared.u8 [%0], %1;\n}\n" ::"r"(sb + SIZE_OFF + place), "r"(steps), "r"((uint32_t)unit) : "memory");
    } else {
        if (elect()) {
            if (b == 0) p.g->sync[0] = epoch + 1;
            asm volatile("fence.proxy.async.global;" ::: "memory");
            mbar_expect_tx(bar_tab, WIMG + LUTS * 32);
            bulk_g2s(sb, p.g->wimg, WIMG, bar_tab);
            bulk_g2s(sb + LUT_OFF, p.g->wimg + WIMG / 16, LUTS * 32, bar_tab);
        }
        warm(WA + WC, WE, 0);
        TSX(12, 511);
    }
    __syncthreads();
    TS0(7);
    if (warp == 15) {
        uint32_t until0 = 0, until1 = 0, next = 0, s0, s1;
        const uint32_t nsched = misc[4];
#pragma unroll 1
        for (uint32_t t = 0; t <= ROUNDS && next < nsched; t++) {
            const bool n0 = until0 == t, n1 = until1 == t;
            const uint32_t i = next + __popc(__ballot_sync(0xffffffffu, n0) & lt) + __popc(__ballot_sync(0xffffffffu, n1) & lt), j = i + n0;
            next += __reduce_add_sync(0xffffffffu, n0 + n1);
            asm volatile("ld.shared.u8 %0, [%2];\nld.shared.u8 %1, [%3];" : "=r"(s0), "=r"(s1) : "r"(sb + SIZE_OFF + i), "r"(sb + SIZE_OFF + j) : "memory");
            if (n0) until0 += s0;
            if (n1) until1 += s1;
            sts16_if(sb + SLOT_OFF + 2 * i, 1024 * t + 16 * lane, n0 && until0 < ROUNDS);
            sts16_if(sb + SLOT_OFF + 2 * j, 1024 * t + 16 * lane + 8, n1 && until1 < ROUNDS);
        }
        until0 = __reduce_max_sync(lane < 16 ? 0xFFFFu : 0xFFFF0000u, max(until0, until1));
        if ((lane & 15) == 0) misc[2 + (lane >> 4)] = until0;
        __syncthreads();
    } else {
        uint32_t gz[4];
        auto geometry = [&](uint32_t& xy, uint32_t zs, bool valid) {
            const float d = distance(xy, zs >> 16);
            float id;
            asm("rcp.approx.ftz.f32 %0, %1;" : "=f"(id) : "f"(d));
            uint32_t row = 0x409D - (__float_as_uint(d) >> 16);
            const bool single = row >= LUTS && valid;
            const uint32_t n = min(atoms_add(single ? sb + MISC_OFF + 4 : sink, 1) + LUTS, LUTN - 1);
            sts32_if(sb + LUT_OFF + n * 32, row, single);
            if (single) row = n;
            xy = pack2(bf_lo(xy) * id, bf_hi(xy) * id);
            return pack2(0.f, bf_hi(zs) * id) + row * 32;
        };
        auto put = [&](uint32_t o, uint32_t e, uint32_t xy, uint32_t z, uint32_t src) {
            sts64_if(sb + RR_OFF + o + e, xy, z, e != 0xFFFFu);
            sts16_if(sb + SRC_OFF + ((o + e) >> 2), src, e != 0xFFFFu);
        };
#pragma unroll
        for (int j = 0; j < 4; j++) {
            const uint2 np = *reinterpret_cast<const uint2*>(smem + NPOS_OFF + dn[j]);
            dn[j] = np.x;
            rk[j] += np.y;
            gz[j] = 0;
        }
#pragma unroll 1
        for (int pass = 0; pass < 2; pass++) {
            uint32_t e[4];
#pragma unroll
            for (int j = 0; j < 4; j++) e[j] = lds16(dn[j]);
#pragma unroll
            for (int j = 0; j < 4; j++) put(rk[j], e[j], rxy[j], gz[j], rzs[j]);
            if (pass) break;
            asm volatile("bar.sync 2, 480;" ::: "memory");
            if (warp < 8) {
                const int s = lane >> 3, c = lane & 7;
                const uint32_t dst = sb + RING_OFF + warp * 16384 + s * 128, x = sb + SRC_OFF + (warp * 8 + s) * 2;
                const uint32_t sdst = dst + ((c ^ s) << 4), vdst = dst + ((c ^ ((s & 1) << 2)) << 4);
                const uint32_t s0 = lds16(x), s1 = lds16(x + 8), s2 = lds16(x + 128), s3 = lds16(x + 136);
                const char* svl = reinterpret_cast<const char*>(p.sv) + c * 16;
                gather_s(sdst, svl, s0);
                gather_s((sdst ^ 64) + 512, svl, s1);
                gather_s(sdst + 8192, svl, s2);
                gather_s((sdst ^ 64) + 8704, svl, s3);
                cp_async_arrive(bar_full);
                gather_v(vdst, svl, s0);
                gather_v(vdst + 512, svl, s1);
                gather_v(vdst + 8192, svl, s2);
                gather_v(vdst + 8704, svl, s3);
                asm volatile("cp.async.mbarrier.arrive.shared::cta.b64 [%0];" ::"r"(bar_side) : "memory");
                TS0(10);
            }
#pragma unroll
            for (int j = 0; j < 4; j++) gz[j] = geometry(rxy[j], rzs[j], dn[j] != sb + SLOT_OFF + 1278);
            __syncthreads();
            TS0(8);
        }
        const uint32_t x = lds16(sb + SLOT_OFF + 2 * min(place, 639u));
        const uint32_t nd = sb + ND_OFF + ((x >> 2) & 0xFF00) + ((x >> 1) & 0xFC);
        sts32_if(nd, tid | ST_START, x != 0xFFFFu);
        sts32_if(nd + steps * 256 - 256, steps > 1 ? last : last | ST_START, x != 0xFFFFu && steps < ROUNDS);
    }
    uint32_t st[4];
    lds128(sb + MISC_OFF, st);
    if (warp >= 13) {
        const uint32_t a = sb + LUT_OFF + LUTS * 32 + (511 - tid) * 16, row = lds32(a & ~31u);
        __syncwarp();
        if (511 - tid < 2 * (int)min(st[1], LUTN - LUTS))
            asm volatile("cp.async.cg.shared.global [%0], [%1], 16;" ::"r"(a), "l"(p.g->wimg + WIMG / 16 + row * 2 + (~tid & 1)) : "memory");
        cp_async_arrive(bar_tab + 16);
    }
    __syncthreads();
    if (__builtin_expect(max(st[2], st[3]) >= ROUNDS || st[1] > LUTN - LUTS || st[0], 0)) {
        asm volatile("cp.async.wait_all;" ::: "memory");
        mbar_wait(bar_tab, 1);
        mbar_wait(bar_tab + 8, 0);
        cold_nodes(smem, p, nn, tag);
        return;
    }
    TS0(9);
    const int T = __shfl_sync(0xffffffffu, warp & 4 ? st[3] : st[2], 0);

    if (warp < 8) {
        asm volatile("setmaxnreg.inc.sync.aligned.u32 %0;" ::"n"(REG_C));
        const int lane = fresh_lane();
        const int g = lane >> 2, q = lane & 3;
        const uint64_t d0 = (uint64_t)__shfl_sync(0xffffffffu, pin((uint32_t)(p.desc0 >> 32)), 0) << 32 | __shfl_sync(0xffffffffu, pin((uint32_t)p.desc0), 0);
        const uint32_t swz = g * 128 + ((q ^ ((g & 1) << 2)) << 4);
        const uint32_t srow = pin(sb + SIDE_OFF + warp * 4096 + swz);
        uint32_t vrow = pin(sb + RING_OFF + warp * 16384 + swz + 4096);
        uint32_t ent = pin(sb + RR_OFF + (warp * 8 + g) * 8), fent = pin(sb + ND_OFF + (warp * 8 + g) * 4);
        uint32_t lent = pin(sb + RR_OFF + (warp * 8 + (lane & 7)) * 8 + 4 + (lane & 8) * 64);
        const uint32_t lutq = pin(sb + LUT_OFF + (lane >> 4) * 16);
        uint64_t outq;
        {
            const uint64_t a = reinterpret_cast<uint64_t>(p.out) + (size_t)nbase * 512 + q * 16;
            const uint32_t lo = pin((uint32_t)a), hi = pin((uint32_t)(a >> 32));
            asm volatile("mov.b64 %0, {%1, %2};" : "=l"(outq) : "r"(lo), "r"(hi));
        }
        uint32_t acc[32], rf[4], h[16], rr[4], fl = 0;
#pragma unroll
        for (int i = 0; i < 32; i++) asm volatile("" : "=r"(acc[i]));
#pragma unroll
        for (int i = 0; i < 16; i++) asm volatile("" : "=r"(h[i]));
#pragma unroll
        for (int i = 0; i < 4; i++) asm volatile("" : "=r"(rf[i]), "=r"(rr[i]));
        int t = -1;
        mbar_wait(bar_tab, 1);
        mbar_wait(bar_tab + 16, 0);
        bool more = T < 0x7FFFFFFF;
#pragma unroll 1
        while (more) {
            float y[32], p1[32], w1[32], p2[32], w2[32], p3[32], w3[32];
            uint32_t m1[16], m2[16], v[3][16], ts[8];
            auto products = [](uint32_t* m, const float* P, const float* W) {
#pragma unroll
                for (int j = 0; j < 8; j++) {
                    m[j] = pack2(P[4 * j] * W[4 * j], P[4 * j + 1] * W[4 * j + 1]);
                    m[8 + j] = pack2(P[4 * j + 2] * W[4 * j + 2], P[4 * j + 3] * W[4 * j + 3]);
                }
            };
            auto vterm = [&](int k, int o) {
#pragma unroll
                for (int j = 0; j < 8; j++) acc[8 * k + 8 + j] = hfma2(m1[o + j], v[k][o + j], acc[8 * k + 8 + j]);
            };
            auto rterm = [&](int k, int o) {
#pragma unroll
                for (int j = 0; j < 8; j++)
                    acc[8 * k + 8 + j] = k == 0 ? hfma2_lo(m2[o + j], rr[o / 4], acc[8 * k + 8 + j]) : hfma2_hi(m2[o + j], rr[o / 4 + k / 2], acc[8 * k + 8 + j]);
            };
            TR(0, 0, t);
            uint64_t om, op;
#pragma unroll
            for (int j = 0; j < 8; j++) asm volatile("" : "=r"(ts[j]), "=r"(m1[8 + j]), "=r"(m2[8 + j]), "=r"(v[0][8 + j]), "=r"(v[1][8 + j]), "=r"(v[2][8 + j]));
            asm volatile("" : "=l"(om));
            if (t >= 0) {
            wg_fence();
            wgmma_group<1>(p1, w1, h, rf, d0);
            wg_commit();
            wgmma_group<2>(p2, w2, h, rf, d0);
            wg_commit();
            mbar_wait(bar_side, t & 1);
#pragma unroll
            for (int k = 0; k < 4; k++) lds2_if(srow + 1024 * k, (srow ^ 64) + 1024 * k, acc + 8 * k, fl & ST_START);
            wg_wait<1>();
            fence_regs(p1); fence_regs(w1);
            products(m1, p1, w1);
#pragma unroll
            for (int k = 0; k < 3; k++) { lds128(vrow + 1024 + 1024 * k, v[k]); lds128((vrow ^ 64) + 1024 + 1024 * k, v[k] + 4); }
            wg_wait<0>();
            fence_regs(p2); fence_regs(w2);
            products(m2, p2, w2);
            asm("mad.wide.u32 %0, %1, 512, %2;" : "=l"(om) : "r"(fl >> 16), "l"(outq));
#pragma unroll
            for (int k = 0; k < 3; k++) { lds128(vrow + 9216 + 1024 * k, v[k] + 8); lds128((vrow ^ 64) + 9216 + 1024 * k, v[k] + 12); }
#pragma unroll
            for (int j = 0; j < 8; j++) asm volatile("" : "=r"(ts[j]));
            lds2_if(srow, srow ^ 64, ts, fl & ST_MID);
#pragma unroll
            for (int k = 0; k < 3; k++) { vterm(k, 0); rterm(k, 0); stg2_fl(om + 128 + 128 * k, acc + 8 + 8 * k, fl >> 1); }
            }
            t++;
            TR(2, 0, t - 1);
            mbar_wait(bar_full + 8 * (t & 1), (t >> 1) & 1);
            TR(3, 0, t - 1);
            wg_fence();
            wgmma_group<0>(p3, w3, h, rf, d0);
            wg_commit();
            wgmma_ss_k64(y, d0 + ((RING_OFF >> 4) + (warp >> 2) * 4096 + (t & 1) * 256 + ((uint64_t)(512 - 64) << 32)), d0);
            wg_commit();
            if (T > 1000000) asm volatile("nanosleep.u32 0;");
#pragma unroll
            for (int k = 1; k < 4; k++) lds2_if(srow + 1024 * k, (srow ^ 64) + 1024 * k, acc + 8 * k, fl & ST_MID);
            asm("mad.wide.u32 %0, %1, 512, %2;" : "=l"(op) : "r"(fl & 511), "l"(outq));
            uint32_t lo;
            asm volatile("ld.shared.u16 %0, [%1];" : "=r"(lo) : "r"(lent) : "memory");
            vrow ^= 4096;
            more = t < T;
#pragma unroll
            for (int k = 0; k < 3; k++) vterm(k, 8);
            __syncwarp();
            if (lane == 0 && t > 0) mbar_arrive(bar_empty);
#define BBS if (T > 1000000) asm volatile("nanosleep.u32 0;")
            auto silu = [&](int i0, int i1) {
#pragma unroll
                for (int i = i0; i < i1; i++)
                    h[i] = pack2(fmaf(y[2 * i], tanh_fast(y[2 * i]), y[2 * i]), fmaf(y[2 * i + 1], tanh_fast(y[2 * i + 1]), y[2 * i + 1]));
            };
#pragma unroll
            for (int k = 0; k < 3; k++) rterm(k, 8);
            const uint32_t fo = fl;
            asm volatile("ld.shared.v2.u32 {%0,%1}, [%4];\nld.shared.v2.u32 {%2,%3}, [%4 + 512];" : "=r"(rr[0]), "=r"(rr[1]), "=r"(rr[2]), "=r"(rr[3]) : "r"(ent) : "memory");
            asm volatile("ld.shared.u32 %0, [%1];" : "=r"(fl) : "r"(fent) : "memory");
            stg2_fl(op + 128, acc + 8, fo);
            BBS;
            wg_wait<0>();
            fence_regs(p3); fence_regs(w3); fence_regs(y);
            ldsm4(lutq + lo, rf);
            products(m1, p3, w3);
            silu(0, SPREAD == 1 ? 6 : 4);
            stg2_fl(op + 256, acc + 16, fo);
            BBS;
#pragma unroll
            for (int j = 0; j < 8; j++) acc[j] = hadd2(acc[j], m1[j]);
            stg2_fl(om, acc, fo >> 1);
#pragma unroll
            for (int j = 0; j < 8; j++) acc[j] = hadd2(fo & ST_MID ? ts[j] : acc[j], m1[8 + j]);
            silu(SPREAD == 1 ? 6 : 4, SPREAD == 1 ? 11 : 10);
            stg2_fl(op + 384, acc + 24, fo);
            BBS;
            silu(SPREAD == 1 ? 11 : 10, SPREAD == 1 ? 16 : 14);
            if (SPREAD == 2) BBS;
            stg2_fl(op, acc, fo);
            silu(SPREAD == 1 ? 16 : 14, 16);
            ent += 1024; fent += 256; lent += 1024;
        }
    } else {
        asm volatile("setmaxnreg.dec.sync.aligned.u32 %0;" ::"n"(256 - REG_C));
        const int lane = fresh_lane();
        const int w = warp - 8, s = lane >> 3, c = lane & 7, nzero = misc[36] & 0xFFFF;
        uint32_t sdst = sb + RING_OFF + w * 16384 + s * 128 + ((c ^ s) << 4);
        const uint32_t sw = s * 128 + ((c ^ ((s & 1) << 2)) << 4);
        uint32_t vdst = sb + RING_OFF + w * 16384 + sw;
        const uint32_t odst = sb + SIDE_OFF + w * 4096 + sw;
        uint32_t ent = sb + ND_OFF + (w * 8 + s) * 4;
        const char* svl = reinterpret_cast<const char*>(p.sv) + c * 16;
        const char* own = svl + (size_t)nbase * 512;
#pragma unroll 1
        for (int t = 1; t <= T; t++) {
            const uint32_t e = sb + SRC_OFF + t * 256 + (w * 8 + s) * 2;
            const uint32_t s0 = lds16(e), s1 = lds16(e + 8), s2 = lds16(e + 128), s3 = lds16(e + 136);
            const uint32_t f0 = lds32(ent), f1 = lds32(ent + 16);
            ent += 256;
            sdst ^= 4096; vdst ^= 4096;
            TR(5, 256, t);
            mbar_wait(bar_empty, t & 1);
            TR(6, 256, t);
            gather_row_if(odst, own + (f0 & 511) * 512, f0 & (ST_START | ST_MID));
            gather_row_if(odst + 512, own + (f1 & 511) * 512, f1 & (ST_START | ST_MID));
            cp_async_arrive(bar_side);
            gather_s(sdst, svl, s0);
            gather_s((sdst ^ 64) + 512, svl, s1);
            gather_s(sdst + 8192, svl, s2);
            gather_s((sdst ^ 64) + 8704, svl, s3);
            cp_async_arrive(bar_full + 8 * (t & 1));
            if (t < T) {
                if (PACE) __nanosleep(PACE);
                gather_v(vdst, svl, s0);
                if (PACE) __nanosleep(PACE);
                gather_v(vdst + 512, svl, s1);
                if (PACE) __nanosleep(PACE);
                gather_v(vdst + 8192, svl, s2);
                if (PACE) __nanosleep(PACE);
                gather_v(vdst + 8704, svl, s3);
            }
            TR(7, 256, t);
        }
        asm volatile("fence.proxy.async.shared::cta;" ::: "memory");
#pragma unroll 1
        for (int z = w + 8 * lane, ph = 0; z - 8 * lane < nzero; z += 96, ph ^= 1) {
            const bool on = lane < 12 && z < nzero;
            const uint32_t row = sb + RING_OFF + w * 16384 + (max(T, 1) & 1) * 4096 + 1024 + (lane + (lane < 6 ? 0 : 10)) * 512;
            const size_t o = (size_t)(nbase + lds16(sb + ZL_OFF + 2 * min(z, 511))) * 256;
            const uint32_t n = __popc(__ballot_sync(0xffffffffu, on));
            if (lane == 0) mbar_expect_tx(bar_full + 24, n * 512);
            if (on) bulk_g2s(row, p.sv + o, 512, bar_full + 24);
            mbar_wait(bar_full + 24, ph);
            if (on) asm volatile("{\n.reg .b64 pol;\ncreatepolicy.fractional.L2::evict_first.b64 pol, 1.0;\n"
                                 "cp.async.bulk.global.shared::cta.bulk_group.L2::cache_hint [%0], [%1], 512, pol;\n"
                                 "cp.async.bulk.commit_group;\ncp.async.bulk.wait_group.read 0;\n}\n" ::"l"(p.out + o), "r"(row) : "memory");
            __syncwarp();
        }
        mbar_wait(bar_tab + 8, 0);
        TSX(11, 256);
    }
}

}

extern "C" void kernel_launch(void* const* d_in, const int* in_sizes, int n_in, void* d_out, int out_size) {
    static int s_G = 0;
    static void* s_scratch = nullptr;
    static void* s_encode = nullptr;
    const int N = in_sizes[0] / 256, E = in_sizes[2];
    if (s_G == 0) {
        cudaFuncSetAttribute(painn_kernel<0, 0, 0>, cudaFuncAttributeMaxDynamicSharedMemorySize, SMEM_BYTES);
        cudaFuncSetAttribute(painn_kernel<50000, 800000, 132>, cudaFuncAttributeMaxDynamicSharedMemorySize, SMEM_BYTES);
        int dev = 0, sms = 0, occ = 0;
        cudaGetDevice(&dev);
        cudaDeviceGetAttribute(&sms, cudaDevAttrMultiProcessorCount, dev);
        cudaOccupancyMaxActiveBlocksPerMultiprocessor(&occ, painn_kernel<0, 0, 0>, THREADS, SMEM_BYTES);
        cudaGetSymbolAddress(&s_scratch, g_scratch);
        cudaDriverEntryPointQueryResult qr;
        cudaGetDriverEntryPoint("cuTensorMapEncodeTiled", &s_encode, cudaEnableDefault, &qr);
        s_G = occ >= 1 ? (sms < MAXG ? sms : MAXG) : 0;
    }
    if (s_G == 0 || N > TABLE_MAXN || N > s_G * (MAXNPC - 1) || (s_G - 1) * ((N + s_G - 1) / s_G) >= N || E > MAXE || E < 4 * MAXG * MAXG) return;
    Params p;
    {
        typedef CUresult (*Encode)(CUtensorMap*, CUtensorMapDataType, cuuint32_t, void*, const cuuint64_t*, const cuuint64_t*, const cuuint32_t*,
                                   const cuuint32_t*, CUtensorMapInterleave, CUtensorMapSwizzle, CUtensorMapL2promotion, CUtensorMapFloatOOBfill);
        const cuuint64_t dims[2] = {64, (cuuint64_t)N * 4}, strides[1] = {128};
        const cuuint32_t box[2] = {8, 32}, es[2] = {1, 1};
        ((Encode)s_encode)(&p.tm, CU_TENSOR_MAP_DATA_TYPE_BFLOAT16, 2, d_in[0], dims, strides, box, es, CU_TENSOR_MAP_INTERLEAVE_NONE,
                           CU_TENSOR_MAP_SWIZZLE_NONE, CU_TENSOR_MAP_L2_PROMOTION_L2_128B, CU_TENSOR_MAP_FLOAT_OOB_FILL_NONE);
    }
    p.g = (Scratch*)s_scratch;
    p.sv = (const __nv_bfloat16*)d_in[0];
    p.pos = (const __nv_bfloat16*)d_in[1];
    p.src = (const int*)d_in[2];
    p.dst = (const int*)d_in[3];
    p.freqs = (const __nv_bfloat16*)d_in[4];
    p.w1 = (const __nv_bfloat16*)d_in[5];
    p.w2 = (const __nv_bfloat16*)d_in[6];
    p.wr = (const __nv_bfloat16*)d_in[7];
    p.out = (__nv_bfloat16*)d_out;
    p.desc0 = (uint64_t)(SB >> 4) | ((uint64_t)1 << 16) | ((uint64_t)64 << 32) | ((uint64_t)1 << 62);
    p.N = N; p.E = E; p.G = s_G;
    p.NPC = (N + s_G - 1) / s_G;
    p.magic = (uint32_t)(((1ull << 32) + p.NPC - 1) / p.NPC);
    p.gpc = ((E >> 2) + s_G - 1) / s_G;
    p.odd_edges = (E & 3) != 0 || p.gpc > 3 * THREADS;
    if (N == 50000 && E == 800000 && s_G == 132) painn_kernel<50000, 800000, 132><<<s_G, THREADS, SMEM_BYTES, cudaStreamPerThread>>>(p);
    else painn_kernel<0, 0, 0><<<s_G, THREADS, SMEM_BYTES, cudaStreamPerThread>>>(p);
}
```

```cpp
#include <cuda_runtime.h>
#include <cuda_bf16.h>
#include <cuda.h>
#include <stdint.h>

namespace {

constexpr int REG_C = 224;
#define PDELAY 200
#define WA 6
#define WC 3
#define WP 0
#define WE 3
#define GROLL 0
#define RESV 0
#define SPREAD 2
#define PACE 0
#define LATES 0
#define EARLYR 2
#define ARRE 0
#define WAITV 0
#define STAG 700
#define ONEB 0
#define LAG 300
#define ZW1 0
#define LAG0 0
#define LAGT 17
#define LAGM 3
#define P0 80
#define ED1 0
#define ED2 0
#define CLR 0
#define TSPLIT 8
#define TROT 0
#define DUMMY 0
#define SKIP1 1
constexpr int THREADS = 512;
constexpr int MAXG = 136;
constexpr int ROUNDS = 11;
constexpr int LUTS = 286, LUTN = 318;
constexpr int MAXNPC = 480;
constexpr int MAXE = 1 << 20;

constexpr int W2_OFF = 8192;
constexpr int WR_OFF = 32768;
constexpr int WIMG = 38912;
constexpr int ZL_OFF = WIMG;
constexpr int RING_OFF = 39936;
constexpr int SIDE_OFF = RING_OFF + 16 * 8192;
constexpr int RR_OFF = SIDE_OFF + 32768;
constexpr int ND_OFF = RR_OFF + ROUNDS * 1024;
constexpr int SRC_OFF = ND_OFF + ROUNDS * 256;
constexpr int LUT_OFF = SRC_OFF + ROUNDS * 256;
constexpr int SINK_OFF = LUT_OFF + 320 * 32;
constexpr int BAR_OFF = SINK_OFF + 512;
constexpr int MISC_OFF = BAR_OFF + 8 * 46;
constexpr int SMEM_BYTES = MISC_OFF + 192 + MAXG;
#define PITCH 144
constexpr int TABLE_MAXN = 50176;
constexpr int STAGE_OFF = TABLE_MAXN * 4;
constexpr int SCNT_OFF = STAGE_OFF + MAXG * PITCH;
constexpr int OVL_OFF = MISC_OFF + 192;
constexpr int OPOS_OFF = LUT_OFF + 1024;
constexpr int NCNT_OFF = SIDE_OFF;
constexpr int NPOS_OFF = NCNT_OFF + 2048;
constexpr int YL_OFF = NPOS_OFF + 4096;
constexpr int SLOT_OFF = YL_OFF + 1024;
constexpr int SIZE_OFF = SLOT_OFF + 1280;
static_assert(SCNT_OFF + 4 * (MAXG + 32) <= OPOS_OFF && OPOS_OFF + 4096 <= LUT_OFF + LUTS * 32, "smem map");
static_assert(2 * (480 - 3 * MAXG) >= MAXG, "chunk map");
static_assert(SMEM_BYTES <= 232448 && MISC_OFF % 16 == 0 && BAR_OFF % 8 == 0 && (RING_OFF + 1024) % 8192 == 0 && SINK_OFF % 128 == 0, "smem map");

constexpr uint32_t PAY_INVALID = 0x3FFFFFFu;
constexpr uint32_t PAY_MARK = 0x3FFFDFFu;
constexpr uint32_t ST_START = 512, ST_CLOSE = 1024, ST_MID = 2048;
constexpr float QINVP = 9.0f / 510.0f;
constexpr uint32_t QTHRESH = 2126;

struct Scratch {
    unsigned sync[32];
    uint4 table[TABLE_MAXN / 4];
    uint4 wimg[WIMG / 16 + LUTS * 2];
    uint2 pos8[TABLE_MAXN];
    uint4 xbuf[MAXG * MAXG * 8 + 3 * THREADS];
    int ovfcnt[MAXG];
    int2 ovf[MAXE + 8 * MAXG + 8];
};
__device__ __align__(128) Scratch g_scratch;

struct Params {
    CUtensorMap tm;
    const __nv_bfloat16* pos;
    Scratch* g;
    const int* src;
    const int* dst;
    int N, NPC, E, gpc;
    const __nv_bfloat16* w2;
    const __nv_bfloat16* wr;
    const __nv_bfloat16* w1;
    const __nv_bfloat16* freqs;
    const __nv_bfloat16* sv;
    __nv_bfloat16* out;
    uint64_t desc0;
    int G;
    uint32_t magic;
    int odd_edges;
};
constexpr uint32_t SB = 1024;

#define TSX(i, thr)
#define TR(k, thr, t)
#define TS0(i) TSX(i, 0)

__device__ __forceinline__ uint32_t smem_u32(const void* p) { return (uint32_t)__cvta_generic_to_shared(p); }
__device__ __forceinline__ void mbar_init(uint32_t bar, uint32_t cnt) {
    asm volatile("mbarrier.init.shared::cta.b64 [%0], %1;" ::"r"(bar), "r"(cnt) : "memory");
}
__device__ __forceinline__ void mbar_arrive(uint32_t bar) {
    asm volatile("mbarrier.arrive.shared::cta.b64 _, [%0];" ::"r"(bar) : "memory");
}
__device__ __forceinline__ void mbar_expect_tx(uint32_t bar, uint32_t bytes) {
    asm volatile("mbarrier.arrive.expect_tx.shared::cta.b64 _, [%0], %1;" ::"r"(bar), "r"(bytes) : "memory");
}
__device__ __forceinline__ void mbar_wait(uint32_t bar, uint32_t parity) {
    asm volatile("{\n.reg .pred p;\n.reg .u32 c;\nmbarrier.try_wait.parity.shared::cta.b64 p, [%0], %1;\n@p bra DONE;\nmov.u32 c, 0;\n"
                 "AGAIN:\nmbarrier.try_wait.parity.shared::cta.b64 p, [%0], %1, 2000;\n@p bra DONE;\nadd.u32 c, c, 1;\n"
                 "setp.lt.u32 p, c, 0x100000;\n@p bra AGAIN;\ntrap;\nDONE:\n}\n" ::"r"(bar), "r"(parity) : "memory");
}
__device__ __forceinline__ void mbar_waitc(uint32_t bar, uint32_t parity) {
    mbar_wait(bar, parity);
}
__device__ __forceinline__ bool elect() {
    uint32_t r;
    asm volatile("{\n.reg .pred p;\nelect.sync _|p, 0xffffffff;\nselp.u32 %0, 1, 0, p;\n}\n" : "=r"(r));
    return r;
}
__device__ __forceinline__ uint32_t pin(uint32_t x) {
    uint32_t r;
    asm volatile("shfl.sync.bfly.b32 %0, %1, 0, 31, -1;" : "=r"(r) : "r"(x));
    return r;
}
__device__ __forceinline__ void bulk_g2s(uint32_t dst, const void* src, uint32_t bytes, uint32_t bar) {
    asm volatile("cp.async.bulk.shared::cluster.global.mbarrier::complete_tx::bytes [%0], [%1], %2, [%3];"
                 ::"r"(dst), "l"(src), "r"(bytes), "r"(bar) : "memory");
}
__device__ __forceinline__ void ldsm4(uint32_t addr, uint32_t* r) {
    asm volatile("ldmatrix.sync.aligned.m8n8.x4.shared.b16 {%0,%1,%2,%3}, [%4];"
                 : "=r"(r[0]), "=r"(r[1]), "=r"(r[2]), "=r"(r[3]) : "r"(addr) : "memory");
}
__device__ __forceinline__ uint32_t pack2(float lo, float hi) {
    uint32_t r;
    asm("cvt.rn.bf16x2.f32 %0, %1, %2;" : "=r"(r) : "f"(hi), "f"(lo));
    return r;
}
__device__ __forceinline__ float bf_lo(uint32_t w) { return __uint_as_float(w << 16); }
__device__ __forceinline__ float bf_hi(uint32_t w) { return __uint_as_float(w & 0xFFFF0000u); }
__device__ __forceinline__ float rbf16(float x) { return __uint_as_float(pack2(0.f, x)); }
__device__ __forceinline__ uint32_t hmul2(uint32_t a, uint32_t b) {
    uint32_t r;
    asm("mul.rn.bf16x2 %0, %1, %2;" : "=r"(r) : "r"(a), "r"(b));
    return r;
}
__device__ __forceinline__ uint32_t hfma2(uint32_t a, uint32_t b, uint32_t c) {
    uint32_t r;
    asm("fma.rn.bf16x2 %0, %1, %2, %3;" : "=r"(r) : "r"(a), "r"(b), "r"(c));
    return r;
}
__device__ __forceinline__ uint32_t hfma2_lo(uint32_t a, uint32_t b, uint32_t c) {
    uint32_t r;
    asm("{\n.reg .b16 l, h;\n.reg .b32 t;\nmov.b32 {l, h}, %2;\nmov.b32 t, {l, l};\nfma.rn.bf16x2 %0, %1, t, %3;\n}\n" : "=r"(r) : "r"(a), "r"(b), "r"(c));
    return r;
}
__device__ __forceinline__ uint32_t hfma2_hi(uint32_t a, uint32_t b, uint32_t c) {
    uint32_t r;
    asm("{\n.reg .b16 l, h;\n.reg .b32 t;\nmov.b32 {l, h}, %2;\nmov.b32 t, {h, h};\nfma.rn.bf16x2 %0, %1, t, %3;\n}\n" : "=r"(r) : "r"(a), "r"(b), "r"(c));
    return r;
}
__device__ __forceinline__ uint32_t hadd2(uint32_t a, uint32_t b) {
    uint32_t r;
    asm("add.rn.bf16x2 %0, %1, %2;" : "=r"(r) : "r"(a), "r"(b));
    return r;
}
__device__ __forceinline__ uint32_t hsub2(uint32_t a, uint32_t b) {
    uint32_t r;
    asm("sub.rn.bf16x2 %0, %1, %2;" : "=r"(r) : "r"(a), "r"(b));
    return r;
}
__device__ __forceinline__ void cp_async_arrive(uint32_t bar) {
    asm volatile("cp.async.mbarrier.arrive.noinc.shared::cta.b64 [%0];" ::"r"(bar) : "memory");
}
__device__ __forceinline__ float tanh_fast(float x) {
    float r;
    asm("tanh.approx.f32 %0, %1;" : "=f"(r) : "f"(x));
    return r;
}
__device__ __forceinline__ void wg_fence() { asm volatile("wgmma.fence.sync.aligned;" ::: "memory"); }
__device__ __forceinline__ void wg_commit() { asm volatile("wgmma.commit_group.sync.aligned;" ::: "memory"); }
template <int N>
__device__ __forceinline__ void wg_wait() { asm volatile("wgmma.wait_group.sync.aligned %0;" ::"n"(N) : "memory"); }

#define WG_REGS "{%0,%1,%2,%3,%4,%5,%6,%7,%8,%9,%10,%11,%12,%13,%14,%15,%16,%17,%18,%19,%20,%21,%22,%23,%24,%25,%26,%27,%28,%29,%30,%31}"
#define WG_OPS(c) c(d[0]), c(d[1]), c(d[2]), c(d[3]), c(d[4]), c(d[5]), c(d[6]), c(d[7]), c(d[8]), c(d[9]), c(d[10]), \
    c(d[11]), c(d[12]), c(d[13]), c(d[14]), c(d[15]), c(d[16]), c(d[17]), c(d[18]), c(d[19]), c(d[20]), c(d[21]),     \
    c(d[22]), c(d[23]), c(d[24]), c(d[25]), c(d[26]), c(d[27]), c(d[28]), c(d[29]), c(d[30]), c(d[31])
template <int OFF, int ACC, int IDX>
__device__ __forceinline__ void wgmma_rs(float* d, const uint32_t* a, uint64_t d0) {
    if (!ACC) {
#pragma unroll
        for (int i = 0; i < 32; i++) d[i] = 0.f;
    }
    if (IDX < 9)
        asm volatile("wgmma.mma_async.sync.aligned.m64n64k16.f32.bf16.bf16 " WG_REGS ", {%32,%33,%34,%35}, %36, %37, 1, 1, 1;"
                     : WG_OPS("+f") : "r"(a[0]), "r"(a[1]), "r"(a[2]), "r"(a[3]), "l"(d0 + (OFF >> 4)), "n"(ACC));
    else
        asm volatile("{\n.reg .b64 dd;\nmov.b64 dd, {%36, 0x40000040};\nwgmma.mma_async.sync.aligned.m64n64k16.f32.bf16.bf16 " WG_REGS
                     ", {%32,%33,%34,%35}, dd, %37, 1, 1, 1;\n}\n"
                     : WG_OPS("+f") : "r"(a[0]), "r"(a[1]), "r"(a[2]), "r"(a[3]), "n"(((SB + OFF) >> 4) | (1u << 16)), "n"(ACC));
}
template <int G>
__device__ __forceinline__ void wgmma_group(float* P, float* W, const uint32_t* h, const uint32_t* rf, uint64_t d0) {
    wgmma_rs<W2_OFF + 8192 * G, 0, 5 * G>(P, h, d0);
    wgmma_rs<W2_OFF + 8192 * G + 2048, 1, 5 * G + 1>(P, h + 4, d0);
    wgmma_rs<W2_OFF + 8192 * G + 4096, 1, 5 * G + 2>(P, h + 8, d0);
    wgmma_rs<W2_OFF + 8192 * G + 6144, 1, 5 * G + 3>(P, h + 12, d0);
    wgmma_rs<WR_OFF + 2048 * G, 0, 5 * G + 4>(W, rf, d0);
}
__device__ __forceinline__ void wgmma_ss_k64(float* d, uint64_t da, uint64_t db) {
#pragma unroll
    for (int i = 0; i < 32; i++) d[i] = 0.f;
    asm volatile("wgmma.mma_async.sync.aligned.m64n64k16.f32.bf16.bf16 " WG_REGS ", %32, %33, 0, 1, 1, 0, 1;" : WG_OPS("+f") : "l"(da), "l"(db));
#pragma unroll
    for (int k = 1; k < 4; k++)
        asm volatile("wgmma.mma_async.sync.aligned.m64n64k16.f32.bf16.bf16 " WG_REGS ", %32, %33, 1, 1, 1, 0, 1;"
                     : WG_OPS("+f") : "l"(da + 2 * k), "l"(db + 128 * k));
}
__device__ __forceinline__ void fence_regs(float* d) { asm volatile("" : WG_OPS("+f")::"memory"); }
__device__ __forceinline__ uint32_t qaxis(float x) {
    const float u = fmaf(x, QINVP, 0.25f);
    const float f = u - ((u + 12582912.f) - 12582912.f);
    return __float_as_uint(fmaf(fabsf(f), 510.f, 12582912.f));
}
__device__ __forceinline__ uint32_t qcode(float x, float y, float z, uint32_t tx) {
    return __byte_perm(__byte_perm(qaxis(x), qaxis(y), 0x3340), qaxis(z), 0x3410) ^ tx;
}
__device__ __forceinline__ bool near_test(uint32_t ca, uint32_t cb, uint32_t tag24) {
    const uint32_t D = __vabsdiffu4(ca, cb);
    return __dp4a(D, D, 0u) <= QTHRESH || ((ca ^ tag24) | (cb ^ tag24)) >= 0x1000000u;
}
constexpr float QMAX = 23.9375f;
__device__ __forceinline__ float square(uint32_t rxy, uint32_t rz) {
    const uint32_t qxy = hmul2(rxy, rxy), qz = hmul2(rz, rz);
    return bf_lo(qxy) + bf_hi(qxy) + bf_lo(qz);
}

__device__ __forceinline__ uint32_t lds32(uint32_t addr) {
    uint32_t r;
    asm volatile("ld.shared.u32 %0, [%1];" : "=r"(r) : "r"(addr) : "memory");
    return r;
}
__device__ __forceinline__ void sts32_if(uint32_t addr, uint32_t v, bool c) {
    asm volatile("{\n.reg .pred p;\nsetp.ne.u32 p, %2, 0;\n@p st.shared.u32 [%0], %1;\n}\n" ::"r"(addr), "r"(v), "r"((uint32_t)c) : "memory");
}
__device__ __forceinline__ uint32_t lds16(uint32_t addr) {
    uint32_t r;
    asm volatile("ld.shared.u16 %0, [%1];" : "=r"(r) : "r"(addr) : "memory");
    return r;
}
__device__ __forceinline__ void sts16_if(uint32_t addr, uint32_t v, bool c) {
    asm volatile("{\n.reg .pred p;\nsetp.ne.u32 p, %2, 0;\n@p st.shared.u16 [%0], %1;\n}\n" ::"r"(addr), "h"((unsigned short)v), "r"((uint32_t)c) : "memory");
}
__device__ __forceinline__ void sts64_if(uint32_t addr, uint32_t x, uint32_t y, bool c) {
    asm volatile("{\n.reg .pred p;\nsetp.ne.u32 p, %3, 0;\n@p st.shared.v2.u32 [%0], {%1, %2};\n}\n" ::"r"(addr), "r"(x), "r"(y), "r"((uint32_t)c) : "memory");
}
__device__ __forceinline__ uint32_t atoms_add(uint32_t addr, uint32_t v) {
    uint32_t r;
    asm volatile("atom.shared.add.u32 %0, [%1], %2;" : "=r"(r) : "r"(addr), "r"(v) : "memory");
    return r;
}
__device__ __forceinline__ void stg128_if(void* ptr, uint4 v, bool c) {
    asm volatile("{\n.reg .pred p;\nsetp.ne.u32 p, %5, 0;\n@p st.relaxed.gpu.global.v4.u32 [%0], {%1,%2,%3,%4};\n}\n"
                 ::"l"(ptr), "r"(v.x), "r"(v.y), "r"(v.z), "r"(v.w), "r"((uint32_t)c) : "memory");
}
__device__ __forceinline__ void lds128(uint32_t addr, uint32_t* r) {
    asm volatile("ld.shared.v4.u32 {%0,%1,%2,%3}, [%4];" : "=r"(r[0]), "=r"(r[1]), "=r"(r[2]), "=r"(r[3]) : "r"(addr) : "memory");
}
__device__ __forceinline__ void stg2_fl(uint64_t ptr, const uint32_t* r, uint32_t fl) {
    asm volatile("{\n.reg .pred p;\n.reg .b32 t;\nand.b32 t, %9, 1024;\nsetp.ne.u32 p, t, 0;\n@p st.global.cs.v4.u32 [%8], {%0,%1,%2,%3};\n"
                 "@p st.global.cs.v4.u32 [%8 + 64], {%4,%5,%6,%7};\n}\n"
                 ::"r"(r[0]), "r"(r[1]), "r"(r[2]), "r"(r[3]), "r"(r[4]), "r"(r[5]), "r"(r[6]), "r"(r[7]), "l"(ptr), "r"(fl) : "memory");
}
__device__ __forceinline__ void gather_s(uint32_t dst, const char* base, uint32_t src) {
    asm volatile("{\n.reg .pred p;\nsetp.eq.u32 p, %2, 0xFFFF;\ncp.async.cg.shared.global [%0], [%1], 16, p;\n}\n"
                 ::"r"(dst), "l"(base + (size_t)src * 512), "r"(src) : "memory");
}
__device__ __forceinline__ void gather_v(uint32_t dst, const char* base, uint32_t src) {
    asm volatile("{\n.reg .pred p;\nsetp.eq.u32 p, %2, 0xFFFF;\n"
                 "cp.async.cg.shared.global [%0 + 1024], [%1 + 128], 16, p;\ncp.async.cg.shared.global [%0 + 2048], [%1 + 256], 16, p;\n"
                 "cp.async.cg.shared.global [%0 + 3072], [%1 + 384], 16, p;\n}\n" ::"r"(dst), "l"(base + (size_t)src * 512), "r"(src) : "memory");
}
__device__ __forceinline__ void gather_row_if(uint32_t dst, const char* src, uint32_t c) {
    asm volatile("{\n.reg .pred p;\nsetp.ne.u32 p, %2, 0;\n@p cp.async.cg.shared.global [%0], [%1], 16;\n"
                 "@p cp.async.cg.shared.global [%0 + 1024], [%1 + 128], 16;\n@p cp.async.cg.shared.global [%0 + 2048], [%1 + 256], 16;\n"
                 "@p cp.async.cg.shared.global [%0 + 3072], [%1 + 384], 16;\n}\n" ::"r"(dst), "l"(src), "r"(c) : "memory");
}
__device__ __forceinline__ void lds2_if(uint32_t a0, uint32_t a1, uint32_t* r, uint32_t c) {
    asm volatile("{\n.reg .pred p;\nsetp.ne.u32 p, %10, 0;\n@p ld.shared.v4.u32 {%0,%1,%2,%3}, [%8];\n@p ld.shared.v4.u32 {%4,%5,%6,%7}, [%9];\n}\n"
                 : "+r"(r[0]), "+r"(r[1]), "+r"(r[2]), "+r"(r[3]), "+r"(r[4]), "+r"(r[5]), "+r"(r[6]), "+r"(r[7])
                 : "r"(a0), "r"(a1), "r"(c) : "memory");
}
__device__ __forceinline__ int fresh_lane() {
    int l;
    asm volatile("mov.u32 %0, %%laneid;" : "=r"(l));
    return l;
}

__device__ __forceinline__ void cold_edges(unsigned char* smem, const Params& p, int lo, int hi, uint32_t tag) {
#pragma unroll 1
    for (int e = lo + threadIdx.x; e < hi; e += THREADS) {
        const int s = p.src[e], d = p.dst[e];
        if (near_test(reinterpret_cast<const uint32_t*>(smem)[s], reinterpret_cast<const uint32_t*>(smem)[d], tag << 24)) {
            const uint32_t own = __umulhi((uint32_t)d, p.magic);
            const uint32_t slot4 = atomicAdd(reinterpret_cast<uint32_t*>(smem + SCNT_OFF) + own, 4u);
            uint32_t* line = reinterpret_cast<uint32_t*>(smem + STAGE_OFF) + own * (PITCH / 4);
            if (slot4 < 124) {
                line[slot4 >> 2] = ((uint32_t)s << 15) + ((uint32_t)(d - own * p.NPC) << 6) + tag;
            } else {
                uint32_t o = atomicAdd(reinterpret_cast<uint32_t*>(smem + MISC_OFF) + 16, 1u);
                p.g->ovf[(size_t)blockIdx.x * (4 * p.gpc + 4) + o] = make_int2(s, d);
                line[31] = (PAY_MARK << 6) | tag;
            }
        }
    }
}
__device__ __forceinline__ void cold_filter(unsigned char* smem, const Params& p, int e0, int e1, uint32_t tag, int redo) {
    if (redo) {
        if (threadIdx.x < MAXG) reinterpret_cast<uint32_t*>(smem + SCNT_OFF)[threadIdx.x] = 0;
        __syncthreads();
    }
    cold_edges(smem, p, redo ? 4 * e0 : 4 * (e0 + 3 * THREADS), 4 * e1, tag);
    if (blockIdx.x == 0) cold_edges(smem, p, p.E & ~3, p.E, tag);
    __syncthreads();
    if (threadIdx.x == 0) p.g->ovfcnt[blockIdx.x] = reinterpret_cast<uint32_t*>(smem + MISC_OFF)[16];
    __threadfence();
    __syncthreads();
}
__device__ __forceinline__ float distance(float q) {
    float d;
    asm("sqrt.approx.ftz.f32 %0, %1;" : "=f"(d) : "f"(rbf16(rbf16(q) + 1e-8f)));
    return rbf16(d);
}
__device__ __forceinline__ float fcut(float d) {
    return d < 5.0f ? 0.5f * rbf16(rbf16(__cosf(rbf16(rbf16(3.14159265358979f * d) * 0.2f))) + 1.0f) : 0.f;
}
__device__ __forceinline__ uint4 basis8(float d, uint4 f) {
    const float sc = __fdividef(fcut(d), d);
    const uint32_t dd = __byte_perm(__float_as_uint(d), 0, 0x3232);
    uint32_t x[4] = {hmul2(f.x, dd), hmul2(f.y, dd), hmul2(f.z, dd), hmul2(f.w, dd)};
#pragma unroll
    for (int i = 0; i < 4; i++) x[i] = pack2(__sinf(bf_lo(x[i])) * sc, __sinf(bf_hi(x[i])) * sc);
    return make_uint4(x[0], x[1], x[2], x[3]);
}
__device__ __forceinline__ void cold_nodes(unsigned char* smem, const Params& p, int nn, uint32_t tag) {
    float* acc = reinterpret_cast<float*>(smem + RING_OFF);
    const int nbase = blockIdx.x * p.NPC, lane = threadIdx.x & 31;
    const uint32_t* sv = reinterpret_cast<const uint32_t*>(p.sv);
    const volatile uint32_t* xin = reinterpret_cast<const uint32_t*>(p.g->xbuf) + blockIdx.x * p.G * 32;
#pragma unroll 1
    for (int i = threadIdx.x; i < p.G * 32; i += THREADS) {
        if (xin[(i & ~31) + 15] < (PAY_MARK << 6)) {
            uint32_t w;
            int it = 0;
            do {
                w = xin[i];
                if (++it > (1 << 22)) __trap();
            } while ((w ^ tag) & 63u);
            if ((w >> 6) == PAY_MARK) smem[OVL_OFF + atomicAdd(reinterpret_cast<uint32_t*>(smem + MISC_OFF) + 17, 1u)] = (unsigned char)(i >> 5);
        }
    }
    __threadfence();
    __syncthreads();
    const int nmark = reinterpret_cast<uint32_t*>(smem + MISC_OFF)[17];
#pragma unroll 1
    for (int c0 = 0; c0 < nn; c0 += 128) {
        __syncthreads();
#pragma unroll 1
        for (int i = threadIdx.x; i < 128 * 256; i += THREADS) acc[i] = 0.f;
        __syncthreads();
#pragma unroll 1
        for (int m = -1; m < nmark; m++) {
            const int pr = m < 0 ? 0 : smem[OVL_OFF + m];
            const int cnt = m < 0 ? p.G * 32 : __ldcg(&p.g->ovfcnt[pr]);
#pragma unroll 1
            for (int i = threadIdx.x; i - lane < cnt; i += THREADS) {
                int2 e = make_int2(0, -1);
                if (i < cnt) {
                    if (m < 0) {
                        const uint32_t w = xin[i];
                        if (((w ^ tag) & 63u) == 0) e = make_int2(w >> 15, (w >> 6) & 511u);
                    } else {
                        e = __ldcg(p.g->ovf + (size_t)pr * (4 * p.gpc + 4) + i);
                        e.y -= nbase;
                    }
                }
                uint32_t rxy = 0, rz = 0;
                bool in = e.y >= c0 && e.y < min(c0 + 128, nn);
                if (in) {
                    const uint2 ps = __ldcg(p.g->pos8 + e.x), pd = __ldcg(p.g->pos8 + nbase + e.y);
                    rxy = hsub2(ps.x, pd.x);
                    rz = hsub2(ps.y, pd.y);
                    in = square(rxy, rz) < QMAX;
                }
#pragma unroll 1
                for (uint32_t todo = __ballot_sync(0xffffffffu, in); todo; todo &= todo - 1) {
                    const int l = __ffs(todo) - 1;
                    const uint32_t* row = sv + (size_t)__shfl_sync(0xffffffffu, e.x, l) * 128 + lane;
                    float* o = acc + (__shfl_sync(0xffffffffu, e.y, l) - c0) * 256 + 2 * lane;
                    const uint32_t xy = __shfl_sync(0xffffffffu, rxy, l), z = __shfl_sync(0xffffffffu, rz, l);
                    const float d = distance(square(xy, z)), fc = fcut(d);
                    uint32_t x = __ldg(row);
                    float y0 = 0.f, y1 = 0.f, m2[6];
#pragma unroll 4
                    for (int k = 0; k < 64; k++) {
                        const uint32_t u = __shfl_sync(0xffffffffu, x, k >> 1), w = __ldg(reinterpret_cast<const uint32_t*>(p.w1) + k * 32 + lane);
                        const float a = k & 1 ? bf_hi(u) : bf_lo(u);
                        y0 = fmaf(a, bf_lo(w), y0);
                        y1 = fmaf(a, bf_hi(w), y1);
                    }
                    y0 = rbf16(y0); y1 = rbf16(y1);
                    x = pack2(y0 / (1.f + __expf(-y0)), y1 / (1.f + __expf(-y1)));
                    const float rb = rbf16(rbf16(__sinf(rbf16(d * __bfloat162float(p.freqs[lane & 15])))) / d);
#pragma unroll
                    for (int g = 0; g < 3; g++) {
                        float p0 = 0.f, p1 = 0.f, w0 = 0.f, w1 = 0.f;
#pragma unroll 4
                        for (int k = 0; k < 64; k++) {
                            const uint32_t u = __shfl_sync(0xffffffffu, x, k >> 1), w = __ldg(reinterpret_cast<const uint32_t*>(p.w2) + k * 96 + g * 32 + lane);
                            const float a = k & 1 ? bf_hi(u) : bf_lo(u);
                            p0 = fmaf(a, bf_lo(w), p0);
                            p1 = fmaf(a, bf_hi(w), p1);
                        }
#pragma unroll 4
                        for (int k = 0; k < 16; k++) {
                            const uint32_t w = __ldg(reinterpret_cast<const uint32_t*>(p.wr) + k * 96 + g * 32 + lane);
                            const float a = __shfl_sync(0xffffffffu, rb, k);
                            w0 = fmaf(a, bf_lo(w), w0);
                            w1 = fmaf(a, bf_hi(w), w1);
                        }
                        m2[2 * g] = rbf16(rbf16(p0) * rbf16(rbf16(w0) * fc));
                        m2[2 * g + 1] = rbf16(rbf16(p1) * rbf16(rbf16(w1) * fc));
                    }
                    atomicAdd(o, m2[0]);
                    atomicAdd(o + 1, m2[1]);
#pragma unroll
                    for (int k = 1; k < 4; k++) {
                        const uint32_t v = __ldg(row + 32 * k);
                        const float rh = rbf16((k == 1 ? bf_lo(xy) : k == 2 ? bf_hi(xy) : bf_lo(z)) / d);
                        atomicAdd(o + 64 * k, fmaf(m2[2], bf_lo(v), m2[4] * rh));
                        atomicAdd(o + 64 * k + 1, fmaf(m2[3], bf_hi(v), m2[5] * rh));
                    }
                }
            }
        }
        __syncthreads();
#pragma unroll 1
        for (int i = threadIdx.x; i < min(128, nn - c0) * 128; i += THREADS) {
            const uint32_t v = __ldg(sv + (size_t)(nbase + c0) * 128 + i);
            reinterpret_cast<uint32_t*>(p.out)[(size_t)(nbase + c0) * 128 + i] = pack2(bf_lo(v) + rbf16(acc[2 * i]), bf_hi(v) + rbf16(acc[2 * i + 1]));
        }
    }
}

template <int CN, int CE, int CG>
__global__ void __launch_bounds__(THREADS, 1) painn_kernel(const __grid_constant__ Params p) {
    extern __shared__ __align__(1024) unsigned char smem_dyn[];
    unsigned char* const smem = static_cast<unsigned char*>(__cvta_shared_to_generic(SB));
    constexpr uint32_t sb = SB;
    const int tid = threadIdx.x, lane = tid & 31;
    const int warp = __shfl_sync(0xffffffffu, tid >> 5, 0);
    constexpr int CNPC = CG ? (CN + CG - 1) / CG : 1, CGPC = CG ? (CE / 4 + CG - 1) / CG : 1;
    const int b = blockIdx.x, G = CG ? CG : p.G, NPC = CG ? CNPC : p.NPC, N = CG ? CN : p.N, gpc = CG ? CGPC : p.gpc;
    const uint32_t magic = CG ? (uint32_t)(((1ull << 32) + CNPC - 1) / CNPC) : p.magic;
    const bool odd_edges = CG ? (CE & 3) != 0 || CGPC > 3 * THREADS : p.odd_edges;
    const int nbase = b * NPC, nn = min(NPC, N - nbase);
    const int e0 = b * gpc, e1 = min((CG ? CE : p.E) >> 2, e0 + gpc);

    uint4* stage4 = reinterpret_cast<uint4*>(smem + STAGE_OFF);
    uint32_t* ncnt = reinterpret_cast<uint32_t*>(smem + NCNT_OFF);
    uint32_t* misc = reinterpret_cast<uint32_t*>(smem + MISC_OFF);
    const uint32_t bar_full = sb + BAR_OFF + (warp & 7) * 40, bar_empty = bar_full + 16, bar_side = bar_full + 32, bar_tab = sb + BAR_OFF + 336;

    auto warm = [&](int first, int n, int pause) {
#pragma unroll 1
        for (int i = first; i < first + n; i++) {
            if (elect())
                asm volatile("cp.async.bulk.tensor.2d.shared::cluster.global.mbarrier::complete_tx::bytes [%0], [%1, {0, %3}], [%2];"
                             ::"r"(sb + SINK_OFF), "l"(&p.tm), "r"(bar_tab + 8), "r"(nbase * 4 + i * 32) : "memory");
            if (pause) __nanosleep(pause);
        }
    };
    TS0(0);
    int4 es[3], ed[3];
    auto load_edges = [&](int i) {
        const int g = min(e0 + tid + i * THREADS, e1 - 1);
        asm volatile("ld.global.cs.v4.u32 {%0,%1,%2,%3}, [%8];\nld.global.cs.v4.u32 {%4,%5,%6,%7}, [%9];"
                     : "=r"(es[i].x), "=r"(es[i].y), "=r"(es[i].z), "=r"(es[i].w), "=r"(ed[i].x), "=r"(ed[i].y), "=r"(ed[i].z), "=r"(ed[i].w)
                     : "l"(reinterpret_cast<const int4*>(p.src) + g), "l"(reinterpret_cast<const int4*>(p.dst) + g) : "memory");
    };
    unsigned epoch;
    const uint32_t tbytes = ((N + 3) >> 2) * 16;
    {
        uint32_t pxy, pz;
        asm volatile("ld.global.nc.u32 %0, [%3];\nld.global.nc.u32 %1, [%3 + 4];\nld.global.ca.u32 %2, [%4];"
                     : "=r"(pxy), "=r"(pz), "=r"(epoch)
                     : "l"(reinterpret_cast<const uint32_t*>(p.pos) + ((nbase + min(tid, nn - 1)) * 3 >> 1)), "l"(p.g->sync) : "memory");
        const uint32_t sh = ((nbase + tid) & 1) << 4;
        pxy = __funnelshift_r(pxy, pz, sh);
        pz >>= sh;
        if (tid < nn) {
            reinterpret_cast<uint32_t*>(p.g->table)[nbase + tid] = qcode(bf_lo(pxy), bf_hi(pxy), bf_lo(pz), ((epoch & 31u) ^ 0x6Bu) << 24);
            p.g->pos8[nbase + tid] = make_uint2(pxy, pz);
        }
        reinterpret_cast<uint2*>(smem + OPOS_OFF)[tid] = make_uint2(pxy, pz);
        if (pxy == 0xFFFFFFFFu && pz == 0xFFFFFFFFu && epoch == 0xFFFFFFFFu) asm volatile("nanosleep.u32 0;");
        load_edges(0);
    }
    __syncthreads();
    const uint32_t tag = (epoch & 31u) | 32u;
    if (warp == 15) {
        if (elect()) {
            asm volatile("red.relaxed.gpu.global.add.u32 [%0], 1;" ::"l"(p.g->sync + 1) : "memory");
            asm volatile("prefetch.tensormap [%0];" ::"l"(&p.tm) : "memory");
            mbar_init(bar_tab, 1);
            mbar_init(bar_tab + 8, 1);
                        mbar_expect_tx(bar_tab, tbytes);
            mbar_expect_tx(bar_tab + 8, (WA + WC + WE) * 512);
        }
        TSX(1, 511);
        const unsigned want = (epoch + 1) * G;
        unsigned c;
        int it = smem_u32(smem_dyn) == SB ? 0 : 1 << 22;
        do {
            asm volatile("ld.relaxed.gpu.global.u32 %0, [%1];" : "=r"(c) : "l"(p.g->sync + 1) : "memory");
            if (++it > (1 << 22)) __trap();
        } while (c != want);
        __syncwarp();
        if (lane < TSPLIT) {
            const uint32_t part = (tbytes / TSPLIT) & ~127u, i = (lane + (TROT ? b : 0)) % TSPLIT;
            bulk_g2s(sb + i * part, reinterpret_cast<const char*>(p.g->table) + i * part, i == TSPLIT - 1 ? tbytes - i * part : part, bar_tab);
        }
        TSX(2, 511);
    }
    if (warp == 14) {
#pragma unroll 1
        for (int c = b * 32 + lane; c < WIMG / 16 + LUTS * 2; c += G * 32) {
            const int row = c >> 3, j = (c ^ row) & 7;
            uint4 v;
            if (c < 512) {
                const uint32_t half = 0x3F003F00u;
                v = __ldg(reinterpret_cast<const uint4*>(p.w1) + row * 8 + j);
                v = make_uint4(hmul2(v.x, half), hmul2(v.y, half), hmul2(v.z, half), hmul2(v.w, half));
            } else if (c >= WIMG / 16) {
                v = basis8(__uint_as_float((0x409D - ((c - WIMG / 16) >> 1)) << 16), __ldg(reinterpret_cast<const uint4*>(p.freqs) + (c & 1)));
            } else {
                const uint32_t* q = (c < 2048 ? reinterpret_cast<const uint32_t*>(p.w2) + (row & 63) * 96 + ((row >> 6) - 1) * 32
                                              : reinterpret_cast<const uint32_t*>(p.wr) + (row & 15) * 96 + ((row >> 4) - 16) * 32) + (j & 4) * 4 + (j & 3);
                v = make_uint4(__ldg(q), __ldg(q + 4), __ldg(q + 8), __ldg(q + 12));
            }
            p.g->wimg[c] = v;
        }
    }
    if (warp < 8 && elect()) {
        mbar_init(bar_full, 32); mbar_init(bar_full + 8, 32);
        mbar_init(bar_empty, 1);
        mbar_init(bar_side, 32);
        mbar_init(bar_full + 24, 1);
    }
    if (tid < MAXG) reinterpret_cast<uint32_t*>(smem + SCNT_OFF)[tid] = 0;
    if (tid < 48) misc[tid] = 0;
    {
        const uint32_t inv = (PAY_INVALID << 6) | tag;
        stage4[tid] = stage4[tid + THREADS] = make_uint4(inv, inv, inv, inv);
        if (tid < MAXG * (PITCH / 16) - 2 * THREADS) stage4[tid + 2 * THREADS] = make_uint4(inv, inv, inv, inv);
    }
    __syncthreads();
    {
    uint4* const xout = p.g->xbuf + ((tid >> 3) * G + b) * 8 + (tid & 7);
#pragma unroll
    for (int i = 0; i < 3; i++) stg128_if(xout + i * G * THREADS, make_uint4(0, 0, 0, 0), tid + i * THREADS < G * 8);
    }
    if (ED1) __nanosleep(ED1);
    load_edges(1);
    if (ED2 > 0) __nanosleep(ED2);
    if (ED2 >= 0) load_edges(2);
    if (tid == THREADS - 1) asm volatile("fence.acq_rel.gpu;" ::: "memory");
    mbar_wait(bar_tab, 0);
    TS0(3);
    if (ED2 < 0) load_edges(2);
    if (warp == 15) warm(0, WA, 0);

#pragma unroll 1
    for (int i = 0, g = e0 + tid; i < 3; i++, g += THREADS) {
        const int s[4] = {es[0].x, es[0].y, es[0].z, es[0].w}, d[4] = {ed[0].x, ed[0].y, ed[0].z, ed[0].w};
        uint32_t ca[4], cb[4], own[4], sl[4];
        bool c[4];
#pragma unroll
        for (int j = 0; j < 4; j++) { ca[j] = lds32(sb + 4 * s[j]); cb[j] = lds32(sb + 4 * d[j]); }
#pragma unroll
        for (int j = 0; j < 4; j++) {
            c[j] = near_test(ca[j], cb[j], tag << 24) && g < e1;
            own[j] = __umulhi((uint32_t)d[j], magic);
            sl[j] = atomicAdd(reinterpret_cast<uint32_t*>(smem + SCNT_OFF) + (c[j] ? own[j] : MAXG + lane), 4u);
        }
#pragma unroll
        for (int j = 0; j < 4; j++)
            sts32_if(sb + STAGE_OFF + own[j] * PITCH + sl[j], own[j] * (uint32_t)(-64 * NPC) + (((uint32_t)s[j] << 15) + (((uint32_t)d[j] << 6) + tag)),
                     c[j] && sl[j] < 124);
        es[0] = es[1]; es[1] = es[2];
        ed[0] = ed[1]; ed[1] = ed[2];
    }
    __syncthreads();
    {
        const int redo = __syncthreads_or(tid < MAXG && reinterpret_cast<uint32_t*>(smem + SCNT_OFF)[tid] > 124);
        if (__builtin_expect(redo || odd_edges, 0)) cold_filter(smem, p, e0, e1, tag, redo);
    }
    TS0(4);
#pragma unroll
    for (int i = 0; i < 2; i++) {
        const int r = min((tid >> 2) + i * (THREADS / 4), G), c = r * (PITCH / 16) + (tid & 3);
        uint4* const x = p.g->xbuf + (r * G + b) * 8 + (tid & 3);
        stg128_if(x, stage4[c], r < G);
        if (__builtin_expect(reinterpret_cast<uint32_t*>(smem + SCNT_OFF)[r] >= 64 && r < G, 0)) stg128_if(x + 4, stage4[c + 4], true);
    }
    ncnt[tid] = 0;
    if (tid < 480) reinterpret_cast<uint32_t*>(smem + SLOT_OFF)[tid] = tid < 32 ? tid * 0x100010 + 0x80000 : tid < 320 ? ~0u : 0u;
    if (tid == 511) reinterpret_cast<uint2*>(smem + NPOS_OFF)[511] = make_uint2(sb + SLOT_OFF + 1278, 0);
    __syncthreads();
    reinterpret_cast<uint4*>(smem + RR_OFF)[tid] = make_uint4(0, 0, 0, 0);
    if (tid < ROUNDS * 80 - THREADS) reinterpret_cast<uint4*>(smem + RR_OFF)[tid + THREADS] = make_uint4(0, 0, 0, 0);
    if (tid < ROUNDS * 32) reinterpret_cast<uint2*>(smem + SRC_OFF)[tid] = make_uint2(~0u, ~0u);
    __nanosleep(PDELAY);
    TS0(5);

    uint32_t rxy[4], gz[4], src[4], rk[4], dn[4];
    const uint32_t sink = sb + NCNT_OFF + 4 * (480 + lane);
    if (warp < 15) {
        uint32_t ew[3][4], bad[2];
        const int u = tid - 3 * G;
        const uint4* const xin = p.g->xbuf + b * G * 8;
        const uint4* cp = xin + (u < 0 ? tid + tid / 3 * 5 : u * 8 + 3);
        bad[0] = u < G;
        bad[1] = u >= 0 && u + 480 - 3 * G < G;
#pragma unroll
        for (int i = 0; i < 3; i++) ew[i][0] = ew[i][1] = ew[i][2] = ew[i][3] = (PAY_INVALID << 6) | tag;
        int it = 0;
#pragma unroll 1
        do {
#pragma unroll
            for (int i = 0; i < 2; i++)
                asm volatile("{\n.reg .pred p;\nsetp.ne.u32 p, %5, 0;\n@p ld.relaxed.gpu.global.v4.u32 {%0,%1,%2,%3}, [%4];\n}\n"
                             : "+r"(ew[i][0]), "+r"(ew[i][1]), "+r"(ew[i][2]), "+r"(ew[i][3]) : "l"(cp + i * (480 - 3 * G) * 8), "r"(bad[i]) : "memory");
#pragma unroll
            for (int i = 0; i < 2; i++) bad[i] = ((ew[i][0] ^ tag) | (ew[i][1] ^ tag) | (ew[i][2] ^ tag) | (ew[i][3] ^ tag)) & 63u;
            if (++it > (1 << 22)) __trap();
        } while (__any_sync(0xffffffffu, bad[0] | bad[1]));
        if (warp >= (3 * G) >> 5) {
            const uint32_t f0 = __ballot_sync(0xffffffffu, u >= 0 && ew[0][3] < (PAY_MARK << 6)), f1 = __ballot_sync(0xffffffffu, ew[1][3] < (PAY_MARK << 6));
            if (__builtin_expect(f0 | f1, 0)) {
                uint64_t f = (uint64_t)f1 << 32 | f0;
#pragma unroll 1
                for (int k = 7 - (lane >> 2); k; k--) f &= f - 1;
                if (f) {
                    const int l = __ffsll(f) - 1;
                    do {
                        asm volatile("ld.relaxed.gpu.global.v4.u32 {%0,%1,%2,%3}, [%4];" : "=r"(ew[2][0]), "=r"(ew[2][1]), "=r"(ew[2][2]), "=r"(ew[2][3])
                                     : "l"(xin + (u - lane + l + (l >> 5) * (448 - 3 * G)) * 8 + 4 + (lane & 3)) : "memory");
                        if (++it > (1 << 22)) __trap();
                    } while (((ew[2][0] ^ tag) | (ew[2][1] ^ tag) | (ew[2][2] ^ tag) | (ew[2][3] ^ tag)) & 63u);
                    if ((ew[2][3] >> 6) == PAY_MARK || lane == 0) misc[0] = 1;
                }
                __syncwarp();
            }
#pragma unroll 1
            for (int i = 0; i < 2; i++) {
                if (ew[0][0] >= (PAY_MARK << 6)) {
#pragma unroll
                    for (int j = 0; j < 4; j++) { ew[0][j] = ew[1][j]; ew[1][j] = ~0u; }
                }
                uint32_t from = __ballot_sync(0xffffffffu, ew[1][0] < (PAY_MARK << 6)), to = __ballot_sync(0xffffffffu, ew[0][0] >= (PAY_MARK << 6));
#pragma unroll 1
                for (; from; from &= from - 1, to &= to - 1) {
                    if (!to) misc[0] = 1;
#pragma unroll
                    for (int j = 0; j < 4; j++) {
                        const uint32_t x = __shfl_sync(0xffffffffu, ew[1][j], __ffs(from) - 1);
                        if (lane == __ffs(to) - 1) ew[0][j] = x;
                    }
                }
#pragma unroll
                for (int j = 0; j < 4; j++) ew[1][j] = ew[2][j];
            }
        }
        {
            uint2 ps[4], pd[4];
#pragma unroll
            for (int j = 0; j < 4; j++) {
                dn[j] = (ew[0][j] >> 3) & 4088u;
                src[j] = ew[0][j] >> 15;
                ps[j] = __ldcg(p.g->pos8 + (dn[j] == 4088u ? nbase : src[j]));
            }
#pragma unroll
            for (int j = 0; j < 4; j++) pd[j] = *reinterpret_cast<const uint2*>(smem + OPOS_OFF + dn[j]);
            if (WC) asm volatile("bar.arrive 1, 512;" ::: "memory");
            float q[4];
#pragma unroll
            for (int j = 0; j < 4; j++) {
                rxy[j] = hsub2(ps[j].x, pd[j].x);
                gz[j] = hsub2(ps[j].y, pd[j].y);
                q[j] = square(rxy[j], gz[j]);
                const bool in = q[j] < QMAX && dn[j] != 4088u;
                rk[j] = atoms_add(in ? sb + NCNT_OFF + (dn[j] >> 1) : sink, 512u);
                if (!in) dn[j] = 4088u;
            }
            uint32_t row[4], n = 0;
            bool single[4];
#pragma unroll
            for (int j = 0; j < 4; j++) {
                q[j] = distance(q[j]);
                row[j] = 0x409D - (__float_as_uint(q[j]) >> 16);
                single[j] = row[j] >= LUTS && dn[j] != 4088u;
                n += single[j];
            }
            n = atoms_add(n ? sb + MISC_OFF + 4 : sink, n) + LUTS;
#pragma unroll
            for (int j = 0; j < 4; j++) {
                float id;
                asm("rcp.approx.ftz.f32 %0, %1;" : "=f"(id) : "f"(q[j]));
                sts32_if(sb + LUT_OFF + min(n, LUTN - 1) * 32, __float_as_uint(q[j]), single[j]);
                if (single[j]) row[j] = n++;
                rxy[j] = pack2(bf_lo(rxy[j]) * id, bf_hi(rxy[j]) * id);
                gz[j] = pack2(0.f, bf_lo(gz[j]) * id) + row[j] * 32;
            }
        }
    } else {
        const uint4 fq = __ldg(reinterpret_cast<const uint4*>(p.freqs) + (lane & 1));
        rxy[0] = fq.x; rxy[1] = fq.y; rxy[2] = fq.z; rxy[3] = fq.w;
        if (WC) asm volatile("bar.sync 1, 512;" ::: "memory");
        warm(WA, WC, 0);
    }
    __syncthreads();
    TS0(6);

    const uint32_t lt = (1u << lane) - 1;
    uint32_t place = ~0u, last = 0, steps = 0;
    if (warp < 15) {
        const uint32_t c = tid < nn ? ncnt[tid] >> 9 : 0u;
        steps = min((c + 1) >> 1, 15u);
        const uint32_t bin = tid >= nn ? 9 : c < 2 ? 8 - c : 7 - min(steps, 7u), sh = (bin & 1) * 16;
        const bool odd = c > 1 && (c & 1);
        const uint32_t peers = __match_any_sync(0xffffffffu, bin), om = __ballot_sync(0xffffffffu, odd);
        uint32_t x = atoms_add(lane == 0 ? sb + MISC_OFF + 4 * 37 : sink, __popc(om));
        uint32_t r = atoms_add((peers & lt) == 0 ? sb + MISC_OFF + 4 * 32 + 2 * (bin & 14) : sink, __popc(peers) << sh);
        x = __shfl_sync(0xffffffffu, x, 0) + __popc(om & lt);
        r = ((__shfl_sync(0xffffffffu, r, __ffs(peers) - 1) >> sh) & 0xFFFFu) + __popc(peers & lt);
        sts16_if(sb + (bin == 7 ? YL_OFF : ZL_OFF) + 2 * r, tid, bin == 7 || bin == 8);
        const uint64_t ones = 0x0001010101010101ull >> (56 - 8 * min(bin, 7u));
        asm volatile("bar.sync 2, 480;" ::: "memory");
        uint32_t h[4];
        lds128(sb + MISC_OFF + 4 * 32, h);
        const uint32_t y = lds16(sb + YL_OFF + 2 * x), nodd = misc[37], none = h[3] >> 16;
        const uint32_t base = __dp2a_lo(h[0], (uint32_t)ones, __dp2a_hi(h[1], (uint32_t)ones, 0u)) +
                              __dp2a_lo(h[2], (uint32_t)(ones >> 32), __dp2a_hi(h[3], (uint32_t)(ones >> 32), 0u));
        const bool unit = bin < 7 || (bin == 7 && r >= nodd), pair = odd && x < none;
        if (unit) place = base + r - (bin == 7 ? nodd : 0);
        if (bin >= 7) misc[4] = base + max((int)(none - nodd), 0);
        last = pair ? y | ST_CLOSE | ST_MID | (tid << 16) : tid | ST_CLOSE;
        const uint32_t sa = sb + SLOT_OFF + (steps < ROUNDS ? 2 * place : 1278);
        sts64_if(sb + NPOS_OFF + 8 * tid, sa, 0, unit);
        sts64_if(sb + NPOS_OFF + 8 * y, sa, c << 9, pair);
        asm volatile("{\n.reg .pred p;\nsetp.ne.u32 p, %2, 0;\n@p st.shared.u8 [%0], %1;\n}\n" ::"r"(sb + SIZE_OFF + place), "r"(steps), "r"((uint32_t)unit) : "memory");
    } else {
        if (elect()) {
            if (b == 0) p.g->sync[0] = epoch + 1;
            asm volatile("fence.proxy.async.global;" ::: "memory");
            mbar_expect_tx(bar_tab, WIMG + LUTS * 32);
            bulk_g2s(sb, p.g->wimg, WIMG, bar_tab);
            bulk_g2s(sb + LUT_OFF, p.g->wimg + WIMG / 16, LUTS * 32, bar_tab);
        }
        warm(WA + WC, WE, 0);
#pragma unroll 1
        for (uint32_t i = lane; i - lane < 2 * min(misc[1], LUTN - LUTS); i += 32) {
            const uint32_t d = lds32(sb + LUT_OFF + (LUTS + (i >> 1)) * 32);
            __syncwarp();
            reinterpret_cast<uint4*>(smem + LUT_OFF)[2 * LUTS + i] = basis8(__uint_as_float(d), make_uint4(rxy[0], rxy[1], rxy[2], rxy[3]));
        }
        TSX(12, 511);
    }
    __syncthreads();
    TS0(7);
    if (warp == 15) {
        uint32_t until0 = lds16(sb + SIZE_OFF + 2 * lane), until1 = until0 >> 8, next = 64, s0, s1;
        const uint32_t nsched = misc[4];
        until0 &= 255;
#pragma unroll 1
        for (uint32_t t = __reduce_min_sync(0xffffffffu, min(until0, until1)); t <= ROUNDS && next < nsched; t++) {
            const bool n0 = until0 == t, n1 = until1 == t;
            const uint32_t i = next + __popc(__ballot_sync(0xffffffffu, n0) & lt) + __popc(__ballot_sync(0xffffffffu, n1) & lt), j = i + n0;
            next += __reduce_add_sync(0xffffffffu, n0 + n1);
            asm volatile("ld.shared.u8 %0, [%2];\nld.shared.u8 %1, [%3];" : "=r"(s0), "=r"(s1) : "r"(sb + SIZE_OFF + i), "r"(sb + SIZE_OFF + j) : "memory");
            if (n0) until0 += s0;
            if (n1) until1 += s1;
            sts16_if(sb + SLOT_OFF + 2 * i, 1024 * t + 16 * lane, n0 && until0 < ROUNDS);
            sts16_if(sb + SLOT_OFF + 2 * j, 1024 * t + 16 * lane + 8, n1 && until1 < ROUNDS);
        }
        until0 = __reduce_max_sync(lane < 16 ? 0xFFFFu : 0xFFFF0000u, max(until0, until1));
        if ((lane & 15) == 0) misc[2 + (lane >> 4)] = until0;
        __syncthreads();
    } else {
#pragma unroll
        for (int j = 0; j < 4; j++) {
            const uint2 np = *reinterpret_cast<const uint2*>(smem + NPOS_OFF + dn[j]);
            dn[j] = np.x;
            rk[j] += np.y;
        }
#pragma unroll 1
        for (int pass = 0; pass < 2; pass++) {
            uint32_t e[4];
#pragma unroll
            for (int j = 0; j < 4; j++) e[j] = lds16(dn[j]);
            const uint32_t x = lds16(sb + SLOT_OFF + 2 * min(place, 639u));
#pragma unroll
            for (int j = 0; j < 4; j++) {
                sts16_if(sb + SRC_OFF + ((rk[j] + e[j]) >> 2), src[j], e[j] != 0xFFFFu);
                sts64_if(sb + RR_OFF + rk[j] + e[j], rxy[j], gz[j], e[j] != 0xFFFFu);
                if (e[j] != 0xFFFFu) dn[j] = sb + SLOT_OFF + 1278;
            }
            if (pass) {
                const uint32_t nd = sb + ND_OFF + ((x >> 2) & 0xFF00) + ((x >> 1) & 0xFC);
                sts32_if(nd, tid | ST_START, x != 0xFFFFu);
                sts32_if(nd + steps * 256 - 256, steps > 1 ? last : last | ST_START, x != 0xFFFFu && steps < ROUNDS);
                break;
            }
            asm volatile("bar.sync 2, 480;" ::: "memory");
            if (warp < 8) {
                const int s = lane >> 3, c = lane & 7;
                const uint32_t dst = sb + RING_OFF + warp * 16384 + s * 128, y = sb + SRC_OFF + (warp * 8 + s) * 2;
                const uint32_t sdst = dst + ((c ^ s) << 4), vdst = dst + ((c ^ ((s & 1) << 2)) << 4);
                const uint32_t s0 = lds16(y), s1 = lds16(y + 8), s2 = lds16(y + 128), s3 = lds16(y + 136);
                const char* svl = reinterpret_cast<const char*>(p.sv) + c * 16;
                gather_s(sdst, svl, s0);
                gather_s((sdst ^ 64) + 512, svl, s1);
                gather_s(sdst + 8192, svl, s2);
                gather_s((sdst ^ 64) + 8704, svl, s3);
                cp_async_arrive(bar_full);
                TS0(10);
                if (P0) __nanosleep(P0);
                gather_v(vdst, svl, s0);
                if (P0) __nanosleep(P0);
                gather_v(vdst + 512, svl, s1);
                if (P0) __nanosleep(P0);
                gather_v(vdst + 8192, svl, s2);
                if (P0) __nanosleep(P0);
                gather_v(vdst + 8704, svl, s3);
                asm volatile("cp.async.mbarrier.arrive.shared::cta.b64 [%0];" ::"r"(bar_side) : "memory");
            }
            __syncthreads();
            TS0(8);
        }
    }
    uint32_t st[4];
    lds128(sb + MISC_OFF, st);
    __syncthreads();
    if (__builtin_expect(max(st[2], st[3]) >= ROUNDS || st[1] > LUTN - LUTS || st[0], 0)) {
        asm volatile("cp.async.wait_all;" ::: "memory");
        mbar_wait(bar_tab, 1);
        mbar_wait(bar_tab + 8, 0);
        cold_nodes(smem, p, nn, tag);
        return;
    }
    TS0(9);
    const int T = __shfl_sync(0xffffffffu, warp & 4 ? st[3] : st[2], 0);

    if (warp < 8) {
        asm volatile("setmaxnreg.inc.sync.aligned.u32 %0;" ::"n"(REG_C));
        const int lane = fresh_lane();
        const int g = lane >> 2, q = lane & 3;
        const uint64_t d0 = (uint64_t)__shfl_sync(0xffffffffu, pin((uint32_t)(p.desc0 >> 32)), 0) << 32 | __shfl_sync(0xffffffffu, pin((uint32_t)p.desc0), 0);
        const uint32_t swz = g * 128 + ((q ^ ((g & 1) << 2)) << 4);
        const uint32_t srow = pin(sb + SIDE_OFF + warp * 4096 + swz);
        uint32_t vrow = pin(sb + RING_OFF + warp * 16384 + swz + 4096);
        uint32_t ent = pin(sb + RR_OFF + (warp * 8 + g) * 8), fent = pin(sb + ND_OFF + (warp * 8 + g) * 4);
        uint32_t lent = pin(sb + RR_OFF + (warp * 8 + (lane & 7)) * 8 + 4 + (lane & 8) * 64);
        const uint32_t lutq = pin(sb + LUT_OFF + (lane >> 4) * 16);
        uint64_t outq;
        {
            const uint64_t a = reinterpret_cast<uint64_t>(p.out) + (size_t)nbase * 512 + q * 16;
            const uint32_t lo = pin((uint32_t)a), hi = pin((uint32_t)(a >> 32));
            asm volatile("mov.b64 %0, {%1, %2};" : "=l"(outq) : "r"(lo), "r"(hi));
        }
        uint32_t acc[32], rf[4], h[16], rr[4], fl = 0;
#pragma unroll
        for (int i = 0; i < 32; i++) asm volatile("" : "=r"(acc[i]));
#pragma unroll
        for (int i = 0; i < 16; i++) asm volatile("" : "=r"(h[i]));
#pragma unroll
        for (int i = 0; i < 4; i++) asm volatile("" : "=r"(rf[i]), "=r"(rr[i]));
        int t = -1;
        TSX(18, 0);
        mbar_wait(bar_tab, 1);
        if (STAG && (warp & 4) && st[2] > st[3]) __nanosleep(STAG);
        TSX(14, 0);
        bool more = T < 0x7FFFFFFF;
#pragma unroll 1
        while (more) {
            float y[32], p1[32], w1[32], p2[32], w2[32], p3[32], w3[32];
            uint32_t m1[16], m2[16], v[3][16], ts[8];
            auto products = [](uint32_t* m, const float* P, const float* W) {
#pragma unroll
                for (int j = 0; j < 8; j++) {
                    m[j] = pack2(P[4 * j] * W[4 * j], P[4 * j + 1] * W[4 * j + 1]);
                    m[8 + j] = pack2(P[4 * j + 2] * W[4 * j + 2], P[4 * j + 3] * W[4 * j + 3]);
                }
            };
            auto vterm = [&](int k, int o) {
#pragma unroll
                for (int j = 0; j < 8; j++) acc[8 * k + 8 + j] = hfma2(m1[o + j], v[k][o + j], acc[8 * k + 8 + j]);
            };
            auto rterm = [&](int k, int o) {
#pragma unroll
                for (int j = 0; j < 8; j++)
                    acc[8 * k + 8 + j] = k == 0 ? hfma2_lo(m2[o + j], rr[o / 4], acc[8 * k + 8 + j]) : hfma2_hi(m2[o + j], rr[o / 4 + k / 2], acc[8 * k + 8 + j]);
            };
            TR(0, 0, t);
            uint64_t om, op;
#pragma unroll
            for (int j = 0; j < 8; j++) asm volatile("" : "=r"(ts[j]), "=r"(m1[8 + j]), "=r"(m2[8 + j]), "=r"(v[0][8 + j]), "=r"(v[1][8 + j]), "=r"(v[2][8 + j]));
            asm volatile("" : "=l"(om));
            if (t >= 0) {
            wg_fence();
            wgmma_group<1>(p1, w1, h, rf, d0);
            wg_commit();
            wgmma_group<2>(p2, w2, h, rf, d0);
            wg_commit();
            mbar_waitc(bar_side, t & 1);
#pragma unroll
            for (int k = 0; k < 4; k++) lds2_if(srow + 1024 * k, (srow ^ 64) + 1024 * k, acc + 8 * k, fl & ST_START);
            wg_wait<1>();
            fence_regs(p1); fence_regs(w1);
            products(m1, p1, w1);
#pragma unroll
            for (int k = 0; k < 3; k++) { lds128(vrow + 1024 + 1024 * k, v[k]); lds128((vrow ^ 64) + 1024 + 1024 * k, v[k] + 4); }
            wg_wait<0>();
            fence_regs(p2); fence_regs(w2);
            products(m2, p2, w2);
            asm("mad.wide.u32 %0, %1, 512, %2;" : "=l"(om) : "r"(fl >> 16), "l"(outq));
#pragma unroll
            for (int k = 0; k < 3; k++) { lds128(vrow + 9216 + 1024 * k, v[k] + 8); lds128((vrow ^ 64) + 9216 + 1024 * k, v[k] + 12); }
#pragma unroll
            for (int j = 0; j < 8; j++) asm volatile("" : "=r"(ts[j]));
            lds2_if(srow, srow ^ 64, ts, fl & ST_MID);
#pragma unroll
            for (int k = 0; k < 3; k++) { vterm(k, 0); rterm(k, 0); stg2_fl(om + 128 + 128 * k, acc + 8 + 8 * k, fl >> 1); }
            }
            t++;
            wg_fence();
            wgmma_group<0>(p3, w3, h, rf, d0);
            wg_commit();
            if (T > 1000000) asm volatile("nanosleep.u32 0;");
#pragma unroll
            for (int k = 1; k < 4; k++) lds2_if(srow + 1024 * k, (srow ^ 64) + 1024 * k, acc + 8 * k, fl & ST_MID);
            uint32_t lo;
            asm volatile("ld.shared.u16 %0, [%1];" : "=r"(lo) : "r"(lent) : "memory");
            __syncwarp();
            if (lane == 0 && t > 0) mbar_arrive(bar_empty);
            TR(2, 0, t - 1);
            mbar_waitc(bar_full + 8 * (t & 1), (t >> 1) & 1);
            TR(3, 0, t - 1);
            wg_fence();
            wgmma_ss_k64(y, d0 + ((RING_OFF >> 4) + (warp >> 2) * 4096 + (t & 1) * 256 + ((uint64_t)(512 - 64) << 32)), d0);
            wg_commit();
            if (T > 1000000) asm volatile("nanosleep.u32 0;");
            asm("mad.wide.u32 %0, %1, 512, %2;" : "=l"(op) : "r"(fl & 511), "l"(outq));
            vrow ^= 4096;
            more = t < T;
#pragma unroll
            for (int k = 0; k < 3; k++) vterm(k, 8);
#define BBS if (T > 1000000) asm volatile("nanosleep.u32 0;")
            auto silu = [&](int i0, int i1) {
#pragma unroll
                for (int i = i0; i < i1; i++)
                    h[i] = pack2(fmaf(y[2 * i], tanh_fast(y[2 * i]), y[2 * i]), fmaf(y[2 * i + 1], tanh_fast(y[2 * i + 1]), y[2 * i + 1]));
            };
#pragma unroll
            for (int k = 0; k < 3; k++) rterm(k, 8);
            const uint32_t fo = fl;
            asm volatile("ld.shared.v2.u32 {%0,%1}, [%4];\nld.shared.v2.u32 {%2,%3}, [%4 + 512];" : "=r"(rr[0]), "=r"(rr[1]), "=r"(rr[2]), "=r"(rr[3]) : "r"(ent) : "memory");
            asm volatile("ld.shared.u32 %0, [%1];" : "=r"(fl) : "r"(fent) : "memory");
            stg2_fl(op + 128, acc + 8, fo);
            BBS;
            wg_wait<0>();
            fence_regs(p3); fence_regs(w3); fence_regs(y);
            ldsm4(lutq + lo, rf);
            products(m1, p3, w3);
            silu(0, SPREAD == 1 ? 6 : 4);
            stg2_fl(op + 256, acc + 16, fo);
            BBS;
#pragma unroll
            for (int j = 0; j < 8; j++) acc[j] = hadd2(acc[j], m1[j]);
            stg2_fl(om, acc, fo >> 1);
#pragma unroll
            for (int j = 0; j < 8; j++) acc[j] = hadd2(fo & ST_MID ? ts[j] : acc[j], m1[8 + j]);
            silu(SPREAD == 1 ? 6 : 4, SPREAD == 1 ? 11 : 10);
            stg2_fl(op + 384, acc + 24, fo);
            BBS;
            silu(SPREAD == 1 ? 11 : 10, SPREAD == 1 ? 16 : 14);
            if (SPREAD == 2) BBS;
            stg2_fl(op, acc, fo);
            silu(SPREAD == 1 ? 16 : 14, 16);
            ent += 1024; fent += 256; lent += 1024;
        }
        TSX(15, 0);
        TSX(16, 128);
    } else {
        asm volatile("setmaxnreg.dec.sync.aligned.u32 %0;" ::"n"(256 - REG_C));
        const int lane = fresh_lane();
        const int w = warp - 8, s = lane >> 3, c = lane & 7, nzero = misc[36] & 0xFFFF;
        uint32_t sdst = sb + RING_OFF + w * 16384 + s * 128 + ((c ^ s) << 4);
        const uint32_t sw = s * 128 + ((c ^ ((s & 1) << 2)) << 4);
        uint32_t vdst = sb + RING_OFF + w * 16384 + sw;
        const uint32_t odst = sb + SIDE_OFF + w * 4096 + sw;
        uint32_t ent = sb + ND_OFF + (w * 8 + s) * 4;
        const char* svl = reinterpret_cast<const char*>(p.sv) + c * 16;
        const char* own = svl + (size_t)nbase * 512;
        if (LAG || LAG0) __nanosleep(LAG0 + LAG * max(min(LAGT - (int)(misc[2] + misc[3]), LAGM), 0));
#pragma unroll 1
        for (int t = 1; t <= T; t++) {
            const uint32_t e = sb + SRC_OFF + t * 256 + (w * 8 + s) * 2;
            const uint32_t s0 = lds16(e), s1 = lds16(e + 8), s2 = lds16(e + 128), s3 = lds16(e + 136);
            const uint32_t f0 = lds32(ent), f1 = lds32(ent + 16);
            ent += 256;
            sdst ^= 4096; vdst ^= 4096;
            TR(5, 256, t);
            mbar_wait(bar_empty, t & 1);
            TR(6, 256, t);
            gather_row_if(odst, own + (f0 & 511) * 512, f0 & (ST_START | ST_MID));
            gather_row_if(odst + 512, own + (f1 & 511) * 512, f1 & (ST_START | ST_MID));
            if (!ONEB) cp_async_arrive(bar_side);
            gather_s(sdst, svl, s0);
            gather_s((sdst ^ 64) + 512, svl, s1);
            gather_s(sdst + 8192, svl, s2);
            gather_s((sdst ^ 64) + 8704, svl, s3);
            cp_async_arrive(ONEB ? bar_side : bar_full + 8 * (t & 1));
            if (t < T) {
                if (PACE) __nanosleep(PACE);
                gather_v(vdst, svl, s0);
                if (PACE) __nanosleep(PACE);
                gather_v(vdst + 512, svl, s1);
                if (PACE) __nanosleep(PACE);
                gather_v(vdst + 8192, svl, s2);
                if (PACE) __nanosleep(PACE);
                gather_v(vdst + 8704, svl, s3);
            }
            TR(7, 256, t);
        }
        TSX(17, 256);
        const int zs = ZW1 && misc[2] > misc[3] ? 4 : 8;
#pragma unroll 1
        for (int z = 7 - w + zs * lane, ph = 0; z - zs * lane < nzero && 7 - w < zs; z += 12 * zs, ph ^= 1) {
            const bool on = lane < 12 && z < nzero;
            const uint32_t row = sb + RING_OFF + w * 16384 + (max(T, 1) & 1) * 4096 + 1024 + (lane + (lane < 6 ? 0 : 10)) * 512;
            const size_t o = (size_t)(nbase + lds16(sb + ZL_OFF + 2 * min(z, 511))) * 256;
            const uint32_t n = __popc(__ballot_sync(0xffffffffu, on));
            if (lane == 0) mbar_expect_tx(bar_full + 24, n * 512);
            if (on) bulk_g2s(row, p.sv + o, 512, bar_full + 24);
            mbar_wait(bar_full + 24, ph);
            if (on) asm volatile("{\n.reg .b64 pol;\ncreatepolicy.fractional.L2::evict_first.b64 pol, 1.0;\n"
                                 "cp.async.bulk.global.shared::cta.bulk_group.L2::cache_hint [%0], [%1], 512, pol;\n"
                                 "cp.async.bulk.commit_group;\ncp.async.bulk.wait_group.read 0;\n}\n" ::"l"(p.out + o), "r"(row) : "memory");
            __syncwarp();
        }
        mbar_wait(bar_tab + 8, 0);
        TSX(11, 256);
    }
}

}

extern "C" void kernel_launch(void* const* d_in, const int* in_sizes, int n_in, void* d_out, int out_size) {
    static int s_G = 0;
    static void* s_scratch = nullptr;
    static void* s_encode = nullptr;
    const int N = in_sizes[0] / 256, E = in_sizes[2];
    if (s_G == 0) {
        cudaFuncSetAttribute(painn_kernel<0, 0, 0>, cudaFuncAttributeMaxDynamicSharedMemorySize, SMEM_BYTES);
        cudaFuncSetAttribute(painn_kernel<50000, 800000, 132>, cudaFuncAttributeMaxDynamicSharedMemorySize, SMEM_BYTES);
        int dev = 0, sms = 0, occ = 0;
        cudaGetDevice(&dev);
        cudaDeviceGetAttribute(&sms, cudaDevAttrMultiProcessorCount, dev);
        cudaOccupancyMaxActiveBlocksPerMultiprocessor(&occ, painn_kernel<0, 0, 0>, THREADS, SMEM_BYTES);
        cudaGetSymbolAddress(&s_scratch, g_scratch);
        cudaDriverEntryPointQueryResult qr;
        cudaGetDriverEntryPoint("cuTensorMapEncodeTiled", &s_encode, cudaEnableDefault, &qr);
        s_G = occ >= 1 ? (sms < MAXG ? sms : MAXG) : 0;
    }
    if (s_G == 0 || N > TABLE_MAXN || N > s_G * (MAXNPC - 1) || (s_G - 1) * ((N + s_G - 1) / s_G) >= N || E > MAXE || E < 4 * MAXG * MAXG) return;
    Params p;
    {
        typedef CUresult (*Encode)(CUtensorMap*, CUtensorMapDataType, cuuint32_t, void*, const cuuint64_t*, const cuuint64_t*, const cuuint32_t*,
                                   const cuuint32_t*, CUtensorMapInterleave, CUtensorMapSwizzle, CUtensorMapL2promotion, CUtensorMapFloatOOBfill);
        const cuuint64_t dims[2] = {64, (cuuint64_t)N * 4}, strides[1] = {128};
        const cuuint32_t box[2] = {8, 32}, es[2] = {1, 1};
        ((Encode)s_encode)(&p.tm, CU_TENSOR_MAP_DATA_TYPE_BFLOAT16, 2, d_in[0], dims, strides, box, es, CU_TENSOR_MAP_INTERLEAVE_NONE,
                           CU_TENSOR_MAP_SWIZZLE_NONE, CU_TENSOR_MAP_L2_PROMOTION_L2_128B, CU_TENSOR_MAP_FLOAT_OOB_FILL_NONE);
    }
    p.g = (Scratch*)s_scratch;
    p.sv = (const __nv_bfloat16*)d_in[0];
    p.pos = (const __nv_bfloat16*)d_in[1];
    p.src = (const int*)d_in[2];
    p.dst = (const int*)d_in[3];
    p.freqs = (const __nv_bfloat16*)d_in[4];
    p.w1 = (const __nv_bfloat16*)d_in[5];
    p.w2 = (const __nv_bfloat16*)d_in[6];
    p.wr = (const __nv_bfloat16*)d_in[7];
    p.out = (__nv_bfloat16*)d_out;
    p.desc0 = (uint64_t)(SB >> 4) | ((uint64_t)1 << 16) | ((uint64_t)64 << 32) | ((uint64_t)1 << 62);
    p.N = N; p.E = E; p.G = s_G;
    p.NPC = (N + s_G - 1) / s_G;
    p.magic = (uint32_t)(((1ull << 32) + p.NPC - 1) / p.NPC);
    p.gpc = ((E >> 2) + s_G - 1) / s_G;
    p.odd_edges = (E & 3) != 0 || p.gpc > 3 * THREADS;
    if (N == 50000 && E == 800000 && s_G == 132) painn_kernel<50000, 800000, 132><<<s_G, THREADS, SMEM_BYTES, cudaStreamPerThread>>>(p);
    else painn_kernel<0, 0, 0><<<s_G, THREADS, SMEM_BYTES, cudaStreamPerThread>>>(p);
}
```

```cpp
#include <cuda_runtime.h>
#include <cuda_bf16.h>
#include <cuda.h>
#include <stdint.h>

namespace {

constexpr int REG_C = 224;
#define PDELAY 200
#define WA 6
#define WC 3
#define WP 0
#define WE 3
#define GROLL 0
#define RESV 0
#define SPREAD 1
#define PACE 0
#define LATES 0
#define EARLYR 2
#define ARRE 0
#define WAITV 0
#define STAG 0
#define ONEB 0
#define LAG 400
#define ZW1 1
#define LAG0 0
#define LAGT 16
#define LAGM 3
#define P0 80
#define ED1 0
#define ED2 0
#define CLR 0
#define TSPLIT 8
#define TROT 0
#define DUMMY 0
#define N128 1
#define NRES 4
#define STAG2 0
#define PP 3
#define P1W 200
#define LAG1 700
#define LASTS 0
#define ZPF 0
#define SKIP1 1
constexpr int THREADS = 512;
constexpr int MAXG = 136;
constexpr int ROUNDS = 11;
constexpr int LUTS = 286, LUTN = 318;
constexpr int MAXNPC = 480;
constexpr int MAXE = 1 << 20;

constexpr int W2_OFF = 8192;
constexpr int WR_OFF = 32768;
constexpr int WIMG = 38912;
constexpr int ZL_OFF = WIMG;
constexpr int RING_OFF = 39936;
constexpr int SIDE_OFF = RING_OFF + 16 * 8192;
constexpr int RR_OFF = SIDE_OFF + 32768;
constexpr int ND_OFF = RR_OFF + ROUNDS * 1024;
constexpr int SRC_OFF = ND_OFF + ROUNDS * 256;
constexpr int LUT_OFF = SRC_OFF + ROUNDS * 256;
constexpr int SINK_OFF = LUT_OFF + 320 * 32;
constexpr int BAR_OFF = SINK_OFF + 512;
constexpr int MISC_OFF = BAR_OFF + 8 * 46;
constexpr int SMEM_BYTES = MISC_OFF + 192 + MAXG;
#define PITCH 144
constexpr int TABLE_MAXN = 50176;
constexpr int STAGE_OFF = TABLE_MAXN * 4;
constexpr int SCNT_OFF = STAGE_OFF + MAXG * PITCH;
constexpr int OVL_OFF = MISC_OFF + 192;
constexpr int OPOS_OFF = LUT_OFF + 1024;
constexpr int NCNT_OFF = SIDE_OFF;
constexpr int NPOS_OFF = NCNT_OFF + 2048;
constexpr int YL_OFF = NPOS_OFF + 4096;
constexpr int TL_OFF = YL_OFF + 1024;
constexpr int SLOT_OFF = TL_OFF + 1024;
constexpr int SIZE_OFF = SLOT_OFF + 1280;
static_assert(SCNT_OFF + 4 * (MAXG + 32) <= OPOS_OFF && OPOS_OFF + 4096 <= LUT_OFF + LUTS * 32, "smem map");
static_assert(2 * (480 - 3 * MAXG) >= MAXG, "chunk map");
static_assert(SMEM_BYTES <= 232448 && MISC_OFF % 16 == 0 && BAR_OFF % 8 == 0 && (RING_OFF + 1024) % 8192 == 0 && SINK_OFF % 128 == 0, "smem map");

constexpr uint32_t PAY_INVALID = 0x3FFFFFFu;
constexpr uint32_t PAY_MARK = 0x3FFFDFFu;
constexpr uint32_t ST_START = 512, ST_CLOSE = 1024, ST_MID = 2048;
constexpr float QINVP = 9.0f / 510.0f;
constexpr uint32_t QTHRESH = 2126;

struct Scratch {
    unsigned sync[32];
    uint4 table[TABLE_MAXN / 4];
    uint4 wimg[WIMG / 16 + LUTS * 2];
    uint2 pos8[TABLE_MAXN];
    uint4 xbuf[MAXG * MAXG * 8 + 3 * THREADS];
    int ovfcnt[MAXG];
    int2 ovf[MAXE + 8 * MAXG + 8];
};
__device__ __align__(128) Scratch g_scratch;

struct Params {
    CUtensorMap tm;
    const __nv_bfloat16* pos;
    Scratch* g;
    const int* src;
    const int* dst;
    int N, NPC, E, gpc;
    const __nv_bfloat16* w2;
    const __nv_bfloat16* wr;
    const __nv_bfloat16* w1;
    const __nv_bfloat16* freqs;
    const __nv_bfloat16* sv;
    __nv_bfloat16* out;
    uint64_t desc0;
    int G;
    uint32_t magic;
    int odd_edges;
};
constexpr uint32_t SB = 1024;

#define TSX(i, thr)
#define TR(k, thr, t)
#define TC(k)
#define TS0(i) TSX(i, 0)

__device__ __forceinline__ uint32_t smem_u32(const void* p) { return (uint32_t)__cvta_generic_to_shared(p); }
__device__ __forceinline__ void mbar_init(uint32_t bar, uint32_t cnt) {
    asm volatile("mbarrier.init.shared::cta.b64 [%0], %1;" ::"r"(bar), "r"(cnt) : "memory");
}
__device__ __forceinline__ void mbar_arrive(uint32_t bar) {
    asm volatile("mbarrier.arrive.shared::cta.b64 _, [%0];" ::"r"(bar) : "memory");
}
__device__ __forceinline__ void mbar_expect_tx(uint32_t bar, uint32_t bytes) {
    asm volatile("mbarrier.arrive.expect_tx.shared::cta.b64 _, [%0], %1;" ::"r"(bar), "r"(bytes) : "memory");
}
__device__ __forceinline__ void mbar_wait(uint32_t bar, uint32_t parity) {
    asm volatile("{\n.reg .pred p;\n.reg .u32 c;\nmbarrier.try_wait.parity.shared::cta.b64 p, [%0], %1;\n@p bra DONE;\nmov.u32 c, 0;\n"
                 "AGAIN:\nmbarrier.try_wait.parity.shared::cta.b64 p, [%0], %1, 2000;\n@p bra DONE;\nadd.u32 c, c, 1;\n"
                 "setp.lt.u32 p, c, 0x100000;\n@p bra AGAIN;\ntrap;\nDONE:\n}\n" ::"r"(bar), "r"(parity) : "memory");
}
__device__ __forceinline__ void mbar_waitc(uint32_t bar, uint32_t parity) {
    mbar_wait(bar, parity);
}
__device__ __forceinline__ bool elect() {
    uint32_t r;
    asm volatile("{\n.reg .pred p;\nelect.sync _|p, 0xffffffff;\nselp.u32 %0, 1, 0, p;\n}\n" : "=r"(r));
    return r;
}
__device__ __forceinline__ uint32_t pin(uint32_t x) {
    uint32_t r;
    asm volatile("shfl.sync.bfly.b32 %0, %1, 0, 31, -1;" : "=r"(r) : "r"(x));
    return r;
}
__device__ __forceinline__ void bulk_g2s(uint32_t dst, const void* src, uint32_t bytes, uint32_t bar) {
    asm volatile("cp.async.bulk.shared::cluster.global.mbarrier::complete_tx::bytes [%0], [%1], %2, [%3];"
                 ::"r"(dst), "l"(src), "r"(bytes), "r"(bar) : "memory");
}
__device__ __forceinline__ void ldsm4(uint32_t addr, uint32_t* r) {
    asm volatile("ldmatrix.sync.aligned.m8n8.x4.shared.b16 {%0,%1,%2,%3}, [%4];"
                 : "=r"(r[0]), "=r"(r[1]), "=r"(r[2]), "=r"(r[3]) : "r"(addr) : "memory");
}
__device__ __forceinline__ uint32_t pack2(float lo, float hi) {
    uint32_t r;
    asm("cvt.rn.bf16x2.f32 %0, %1, %2;" : "=r"(r) : "f"(hi), "f"(lo));
    return r;
}
__device__ __forceinline__ float bf_lo(uint32_t w) { return __uint_as_float(w << 16); }
__device__ __forceinline__ float bf_hi(uint32_t w) { return __uint_as_float(w & 0xFFFF0000u); }
__device__ __forceinline__ float rbf16(float x) { return __uint_as_float(pack2(0.f, x)); }
__device__ __forceinline__ uint32_t hmul2(uint32_t a, uint32_t b) {
    uint32_t r;
    asm("mul.rn.bf16x2 %0, %1, %2;" : "=r"(r) : "r"(a), "r"(b));
    return r;
}
__device__ __forceinline__ uint32_t hfma2(uint32_t a, uint32_t b, uint32_t c) {
    uint32_t r;
    asm("fma.rn.bf16x2 %0, %1, %2, %3;" : "=r"(r) : "r"(a), "r"(b), "r"(c));
    return r;
}
__device__ __forceinline__ uint32_t hfma2_lo(uint32_t a, uint32_t b, uint32_t c) {
    uint32_t r;
    asm("{\n.reg .b16 l, h;\n.reg .b32 t;\nmov.b32 {l, h}, %2;\nmov.b32 t, {l, l};\nfma.rn.bf16x2 %0, %1, t, %3;\n}\n" : "=r"(r) : "r"(a), "r"(b), "r"(c));
    return r;
}
__device__ __forceinline__ uint32_t hfma2_hi(uint32_t a, uint32_t b, uint32_t c) {
    uint32_t r;
    asm("{\n.reg .b16 l, h;\n.reg .b32 t;\nmov.b32 {l, h}, %2;\nmov.b32 t, {h, h};\nfma.rn.bf16x2 %0, %1, t, %3;\n}\n" : "=r"(r) : "r"(a), "r"(b), "r"(c));
    return r;
}
__device__ __forceinline__ uint32_t hadd2(uint32_t a, uint32_t b) {
    uint32_t r;
    asm("add.rn.bf16x2 %0, %1, %2;" : "=r"(r) : "r"(a), "r"(b));
    return r;
}
__device__ __forceinline__ uint32_t hsub2(uint32_t a, uint32_t b) {
    uint32_t r;
    asm("sub.rn.bf16x2 %0, %1, %2;" : "=r"(r) : "r"(a), "r"(b));
    return r;
}
__device__ __forceinline__ void cp_async_arrive(uint32_t bar) {
    asm volatile("cp.async.mbarrier.arrive.noinc.shared::cta.b64 [%0];" ::"r"(bar) : "memory");
}
__device__ __forceinline__ float tanh_fast(float x) {
    float r;
    asm("tanh.approx.f32 %0, %1;" : "=f"(r) : "f"(x));
    return r;
}
__device__ __forceinline__ void wg_fence() { asm volatile("wgmma.fence.sync.aligned;" ::: "memory"); }
__device__ __forceinline__ void wg_commit() { asm volatile("wgmma.commit_group.sync.aligned;" ::: "memory"); }
template <int N>
__device__ __forceinline__ void wg_wait() { asm volatile("wgmma.wait_group.sync.aligned %0;" ::"n"(N) : "memory"); }

#define WG_REGS "{%0,%1,%2,%3,%4,%5,%6,%7,%8,%9,%10,%11,%12,%13,%14,%15,%16,%17,%18,%19,%20,%21,%22,%23,%24,%25,%26,%27,%28,%29,%30,%31}"
#define WG_OPS(c) c(d[0]), c(d[1]), c(d[2]), c(d[3]), c(d[4]), c(d[5]), c(d[6]), c(d[7]), c(d[8]), c(d[9]), c(d[10]), \
    c(d[11]), c(d[12]), c(d[13]), c(d[14]), c(d[15]), c(d[16]), c(d[17]), c(d[18]), c(d[19]), c(d[20]), c(d[21]),     \
    c(d[22]), c(d[23]), c(d[24]), c(d[25]), c(d[26]), c(d[27]), c(d[28]), c(d[29]), c(d[30]), c(d[31])
#define WG_OPSE(c) c(e[0]), c(e[1]), c(e[2]), c(e[3]), c(e[4]), c(e[5]), c(e[6]), c(e[7]), c(e[8]), c(e[9]), c(e[10]), c(e[11]), c(e[12]), c(e[13]), c(e[14]), c(e[15]), c(e[16]), c(e[17]), c(e[18]), c(e[19]), c(e[20]), c(e[21]), c(e[22]), c(e[23]), c(e[24]), c(e[25]), c(e[26]), c(e[27]), c(e[28]), c(e[29]), c(e[30]), c(e[31])
template <int OFF, int ACC, int IDX>
__device__ __forceinline__ void wgmma_rs(float* d, const uint32_t* a, uint64_t d0) {
    if (!ACC) {
#pragma unroll
        for (int i = 0; i < 32; i++) d[i] = 0.f;
    }
    if (IDX < (N128 ? NRES : 9))
        asm volatile("wgmma.mma_async.sync.aligned.m64n64k16.f32.bf16.bf16 " WG_REGS ", {%32,%33,%34,%35}, %36, %37, 1, 1, 1;"
                     : WG_OPS("+f") : "r"(a[0]), "r"(a[1]), "r"(a[2]), "r"(a[3]), "l"(d0 + (OFF >> 4)), "n"(ACC));
    else
        asm volatile("{\n.reg .b64 dd;\nmov.b64 dd, {%36, 0x40000040};\nwgmma.mma_async.sync.aligned.m64n64k16.f32.bf16.bf16 " WG_REGS
                     ", {%32,%33,%34,%35}, dd, %37, 1, 1, 1;\n}\n"
                     : WG_OPS("+f") : "r"(a[0]), "r"(a[1]), "r"(a[2]), "r"(a[3]), "n"(((SB + OFF) >> 4) | (1u << 16)), "n"(ACC));
}
template <int OFF, int LBO, int ACC>
__device__ __forceinline__ void wgmma_rs2(float* d, float* e, const uint32_t* a, uint64_t d0) {
    if (!ACC) {
#pragma unroll
        for (int i = 0; i < 32; i++) d[i] = e[i] = 0.f;
    }
    asm volatile("wgmma.mma_async.sync.aligned.m64n128k16.f32.bf16.bf16 {%0,%1,%2,%3,%4,%5,%6,%7,%8,%9,%10,%11,%12,%13,%14,%15,%16,%17,%18,%19,%20,%21,%22,%23,%24,%25,%26,%27,%28,%29,%30,%31,%32,%33,%34,%35,%36,%37,%38,%39,%40,%41,%42,%43,%44,%45,%46,%47,%48,%49,%50,%51,%52,%53,%54,%55,%56,%57,%58,%59,%60,%61,%62,%63}, {%64,%65,%66,%67}, %68, %69, 1, 1, 1;"
                 : WG_OPS("+f"), WG_OPSE("+f") : "r"(a[0]), "r"(a[1]), "r"(a[2]), "r"(a[3]), "l"(d0 + (OFF >> 4) + ((LBO / 16 - 1) << 16)), "n"(ACC));
}
template <int G>
__device__ __forceinline__ void wgmma_group(float* P, float* W, const uint32_t* h, const uint32_t* rf, uint64_t d0) {
    wgmma_rs<W2_OFF + 8192 * G, 0, 5 * G>(P, h, d0);
    wgmma_rs<W2_OFF + 8192 * G + 2048, 1, 5 * G + 1>(P, h + 4, d0);
    wgmma_rs<W2_OFF + 8192 * G + 4096, 1, 5 * G + 2>(P, h + 8, d0);
    wgmma_rs<W2_OFF + 8192 * G + 6144, 1, 5 * G + 3>(P, h + 12, d0);
    wgmma_rs<WR_OFF + 2048 * G, 0, 5 * G + 4>(W, rf, d0);
}
__device__ __forceinline__ void wgmma_ss_k64(float* d, uint64_t da, uint64_t db) {
#pragma unroll
    for (int i = 0; i < 32; i++) d[i] = 0.f;
    asm volatile("wgmma.mma_async.sync.aligned.m64n64k16.f32.bf16.bf16 " WG_REGS ", %32, %33, 0, 1, 1, 0, 1;" : WG_OPS("+f") : "l"(da), "l"(db));
#pragma unroll
    for (int k = 1; k < 4; k++)
        asm volatile("wgmma.mma_async.sync.aligned.m64n64k16.f32.bf16.bf16 " WG_REGS ", %32, %33, 1, 1, 1, 0, 1;"
                     : WG_OPS("+f") : "l"(da + 2 * k), "l"(db + 128 * k));
}
__device__ __forceinline__ void fence_regs(float* d) { asm volatile("" : WG_OPS("+f")::"memory"); }
__device__ __forceinline__ uint32_t qaxis(float x) {
    const float u = fmaf(x, QINVP, 0.25f);
    const float f = u - ((u + 12582912.f) - 12582912.f);
    return __float_as_uint(fmaf(fabsf(f), 510.f, 12582912.f));
}
__device__ __forceinline__ uint32_t qcode(float x, float y, float z, uint32_t tx) {
    return __byte_perm(__byte_perm(qaxis(x), qaxis(y), 0x3340), qaxis(z), 0x3410) ^ tx;
}
__device__ __forceinline__ bool near_test(uint32_t ca, uint32_t cb, uint32_t tag24) {
    const uint32_t D = __vabsdiffu4(ca, cb);
    return __dp4a(D, D, 0u) <= QTHRESH || ((ca ^ tag24) | (cb ^ tag24)) >= 0x1000000u;
}
constexpr float QMAX = 23.9375f;
__device__ __forceinline__ float square(uint32_t rxy, uint32_t rz) {
    const uint32_t qxy = hmul2(rxy, rxy), qz = hmul2(rz, rz);
    return bf_lo(qxy) + bf_hi(qxy) + bf_lo(qz);
}

__device__ __forceinline__ uint32_t lds32(uint32_t addr) {
    uint32_t r;
    asm volatile("ld.shared.u32 %0, [%1];" : "=r"(r) : "r"(addr) : "memory");
    return r;
}
__device__ __forceinline__ void sts32_if(uint32_t addr, uint32_t v, bool c) {
    asm volatile("{\n.reg .pred p;\nsetp.ne.u32 p, %2, 0;\n@p st.shared.u32 [%0], %1;\n}\n" ::"r"(addr), "r"(v), "r"((uint32_t)c) : "memory");
}
__device__ __forceinline__ uint32_t lds16(uint32_t addr) {
    uint32_t r;
    asm volatile("ld.shared.u16 %0, [%1];" : "=r"(r) : "r"(addr) : "memory");
    return r;
}
__device__ __forceinline__ void sts16_if(uint32_t addr, uint32_t v, bool c) {
    asm volatile("{\n.reg .pred p;\nsetp.ne.u32 p, %2, 0;\n@p st.shared.u16 [%0], %1;\n}\n" ::"r"(addr), "h"((unsigned short)v), "r"((uint32_t)c) : "memory");
}
__device__ __forceinline__ void sts64_if(uint32_t addr, uint32_t x, uint32_t y, bool c) {
    asm volatile("{\n.reg .pred p;\nsetp.ne.u32 p, %3, 0;\n@p st.shared.v2.u32 [%0], {%1, %2};\n}\n" ::"r"(addr), "r"(x), "r"(y), "r"((uint32_t)c) : "memory");
}
__device__ __forceinline__ uint32_t atoms_add(uint32_t addr, uint32_t v) {
    uint32_t r;
    asm volatile("atom.shared.add.u32 %0, [%1], %2;" : "=r"(r) : "r"(addr), "r"(v) : "memory");
    return r;
}
__device__ __forceinline__ void stg128_if(void* ptr, uint4 v, bool c) {
    asm volatile("{\n.reg .pred p;\nsetp.ne.u32 p, %5, 0;\n@p st.relaxed.gpu.global.v4.u32 [%0], {%1,%2,%3,%4};\n}\n"
                 ::"l"(ptr), "r"(v.x), "r"(v.y), "r"(v.z), "r"(v.w), "r"((uint32_t)c) : "memory");
}
__device__ __forceinline__ void lds128(uint32_t addr, uint32_t* r) {
    asm volatile("ld.shared.v4.u32 {%0,%1,%2,%3}, [%4];" : "=r"(r[0]), "=r"(r[1]), "=r"(r[2]), "=r"(r[3]) : "r"(addr) : "memory");
}
__device__ __forceinline__ void stg2_if(uint64_t ptr, const uint32_t* r, uint32_t c) {
    asm volatile("{\n.reg .pred p;\nsetp.ne.u32 p, %9, 0;\n@p st.global.cs.v4.u32 [%8], {%0,%1,%2,%3};\n"
                 "@p st.global.cs.v4.u32 [%8 + 64], {%4,%5,%6,%7};\n}\n"
                 ::"r"(r[0]), "r"(r[1]), "r"(r[2]), "r"(r[3]), "r"(r[4]), "r"(r[5]), "r"(r[6]), "r"(r[7]), "l"(ptr), "r"(c) : "memory");
}
__device__ __forceinline__ void gather_s(uint32_t dst, const char* base, uint32_t src) {
    asm volatile("{\n.reg .pred p;\nsetp.eq.u32 p, %2, 0xFFFF;\ncp.async.cg.shared.global [%0], [%1], 16, p;\n}\n"
                 ::"r"(dst), "l"(base + (size_t)src * 512), "r"(src) : "memory");
}
__device__ __forceinline__ void gather_v(uint32_t dst, const char* base, uint32_t src) {
    asm volatile("{\n.reg .pred p;\nsetp.eq.u32 p, %2, 0xFFFF;\n"
                 "cp.async.cg.shared.global [%0 + 1024], [%1 + 128], 16, p;\ncp.async.cg.shared.global [%0 + 2048], [%1 + 256], 16, p;\n"
                 "cp.async.cg.shared.global [%0 + 3072], [%1 + 384], 16, p;\n}\n" ::"r"(dst), "l"(base + (size_t)src * 512), "r"(src) : "memory");
}
__device__ __forceinline__ void gather_row_if(uint32_t dst, const char* src, uint32_t c) {
    asm volatile("{\n.reg .pred p;\nsetp.ne.u32 p, %2, 0;\n@p cp.async.cg.shared.global [%0], [%1], 16;\n"
                 "@p cp.async.cg.shared.global [%0 + 1024], [%1 + 128], 16;\n@p cp.async.cg.shared.global [%0 + 2048], [%1 + 256], 16;\n"
                 "@p cp.async.cg.shared.global [%0 + 3072], [%1 + 384], 16;\n}\n" ::"r"(dst), "l"(src), "r"(c) : "memory");
}
__device__ __forceinline__ void lds2_if(uint32_t a0, uint32_t a1, uint32_t* r, uint32_t c) {
    asm volatile("{\n.reg .pred p;\nsetp.ne.u32 p, %10, 0;\n@p ld.shared.v4.u32 {%0,%1,%2,%3}, [%8];\n@p ld.shared.v4.u32 {%4,%5,%6,%7}, [%9];\n}\n"
                 : "+r"(r[0]), "+r"(r[1]), "+r"(r[2]), "+r"(r[3]), "+r"(r[4]), "+r"(r[5]), "+r"(r[6]), "+r"(r[7])
                 : "r"(a0), "r"(a1), "r"(c) : "memory");
}
__device__ __forceinline__ int fresh_lane() {
    int l;
    asm volatile("mov.u32 %0, %%laneid;" : "=r"(l));
    return l;
}

__device__ __forceinline__ void cold_edges(unsigned char* smem, const Params& p, int lo, int hi, uint32_t tag) {
#pragma unroll 1
    for (int e = lo + threadIdx.x; e < hi; e += THREADS) {
        const int s = p.src[e], d = p.dst[e];
        if (near_test(reinterpret_cast<const uint32_t*>(smem)[s], reinterpret_cast<const uint32_t*>(smem)[d], tag << 24)) {
            const uint32_t own = __umulhi((uint32_t)d, p.magic);
            const uint32_t slot4 = atomicAdd(reinterpret_cast<uint32_t*>(smem + SCNT_OFF) + own, 4u);
            uint32_t* line = reinterpret_cast<uint32_t*>(smem + STAGE_OFF) + own * (PITCH / 4);
            if (slot4 < 124) {
                line[slot4 >> 2] = ((uint32_t)s << 15) + ((uint32_t)(d - own * p.NPC) << 6) + tag;
            } else {
                uint32_t o = atomicAdd(reinterpret_cast<uint32_t*>(smem + MISC_OFF) + 16, 1u);
                p.g->ovf[(size_t)blockIdx.x * (4 * p.gpc + 4) + o] = make_int2(s, d);
                line[31] = (PAY_MARK << 6) | tag;
            }
        }
    }
}
__device__ __forceinline__ void cold_filter(unsigned char* smem, const Params& p, int e0, int e1, uint32_t tag, int redo) {
    if (redo) {
        if (threadIdx.x < MAXG) reinterpret_cast<uint32_t*>(smem + SCNT_OFF)[threadIdx.x] = 0;
        __syncthreads();
    }
    cold_edges(smem, p, redo ? 4 * e0 : 4 * (e0 + 3 * THREADS), 4 * e1, tag);
    if (blockIdx.x == 0) cold_edges(smem, p, p.E & ~3, p.E, tag);
    __syncthreads();
    if (threadIdx.x == 0) p.g->ovfcnt[blockIdx.x] = reinterpret_cast<uint32_t*>(smem + MISC_OFF)[16];
    __threadfence();
    __syncthreads();
}
__device__ __forceinline__ float distance(float q) {
    float d;
    asm("sqrt.approx.ftz.f32 %0, %1;" : "=f"(d) : "f"(rbf16(rbf16(q) + 1e-8f)));
    return rbf16(d);
}
__device__ __forceinline__ float fcut(float d) {
    return d < 5.0f ? 0.5f * rbf16(rbf16(__cosf(rbf16(rbf16(3.14159265358979f * d) * 0.2f))) + 1.0f) : 0.f;
}
__device__ __forceinline__ uint4 basis8(float d, uint4 f) {
    const float sc = __fdividef(fcut(d), d);
    const uint32_t dd = __byte_perm(__float_as_uint(d), 0, 0x3232);
    uint32_t x[4] = {hmul2(f.x, dd), hmul2(f.y, dd), hmul2(f.z, dd), hmul2(f.w, dd)};
#pragma unroll
    for (int i = 0; i < 4; i++) x[i] = pack2(__sinf(bf_lo(x[i])) * sc, __sinf(bf_hi(x[i])) * sc);
    return make_uint4(x[0], x[1], x[2], x[3]);
}
__device__ __forceinline__ void cold_nodes(unsigned char* smem, const Params& p, int nn, uint32_t tag) {
    float* acc = reinterpret_cast<float*>(smem + RING_OFF);
    const int nbase = blockIdx.x * p.NPC, lane = threadIdx.x & 31;
    const uint32_t* sv = reinterpret_cast<const uint32_t*>(p.sv);
    const volatile uint32_t* xin = reinterpret_cast<const uint32_t*>(p.g->xbuf) + blockIdx.x * p.G * 32;
#pragma unroll 1
    for (int i = threadIdx.x; i < p.G * 32; i += THREADS) {
        if (xin[(i & ~31) + 15] < (PAY_MARK << 6)) {
            uint32_t w;
            int it = 0;
            do {
                w = xin[i];
                if (++it > (1 << 22)) __trap();
            } while ((w ^ tag) & 63u);
            if ((w >> 6) == PAY_MARK) smem[OVL_OFF + atomicAdd(reinterpret_cast<uint32_t*>(smem + MISC_OFF) + 17, 1u)] = (unsigned char)(i >> 5);
        }
    }
    __threadfence();
    __syncthreads();
    const int nmark = reinterpret_cast<uint32_t*>(smem + MISC_OFF)[17];
#pragma unroll 1
    for (int c0 = 0; c0 < nn; c0 += 128) {
        __syncthreads();
#pragma unroll 1
        for (int i = threadIdx.x; i < 128 * 256; i += THREADS) acc[i] = 0.f;
        __syncthreads();
#pragma unroll 1
        for (int m = -1; m < nmark; m++) {
            const int pr = m < 0 ? 0 : smem[OVL_OFF + m];
            const int cnt = m < 0 ? p.G * 32 : __ldcg(&p.g->ovfcnt[pr]);
#pragma unroll 1
            for (int i = threadIdx.x; i - lane < cnt; i += THREADS) {
                int2 e = make_int2(0, -1);
                if (i < cnt) {
                    if (m < 0) {
                        const uint32_t w = xin[i];
                        if (((w ^ tag) & 63u) == 0) e = make_int2(w >> 15, (w >> 6) & 511u);
                    } else {
                        e = __ldcg(p.g->ovf + (size_t)pr * (4 * p.gpc + 4) + i);
                        e.y -= nbase;
                    }
                }
                uint32_t rxy = 0, rz = 0;
                bool in = e.y >= c0 && e.y < min(c0 + 128, nn);
                if (in) {
                    const uint2 ps = __ldcg(p.g->pos8 + e.x), pd = __ldcg(p.g->pos8 + nbase + e.y);
                    rxy = hsub2(ps.x, pd.x);
                    rz = hsub2(ps.y, pd.y);
                    in = square(rxy, rz) < QMAX;
                }
#pragma unroll 1
                for (uint32_t todo = __ballot_sync(0xffffffffu, in); todo; todo &= todo - 1) {
                    const int l = __ffs(todo) - 1;
                    const uint32_t* row = sv + (size_t)__shfl_sync(0xffffffffu, e.x, l) * 128 + lane;
                    float* o = acc + (__shfl_sync(0xffffffffu, e.y, l) - c0) * 256 + 2 * lane;
                    const uint32_t xy = __shfl_sync(0xffffffffu, rxy, l), z = __shfl_sync(0xffffffffu, rz, l);
                    const float d = distance(square(xy, z)), fc = fcut(d);
                    uint32_t x = __ldg(row);
                    float y0 = 0.f, y1 = 0.f, m2[6];
#pragma unroll 4
                    for (int k = 0; k < 64; k++) {
                        const uint32_t u = __shfl_sync(0xffffffffu, x, k >> 1), w = __ldg(reinterpret_cast<const uint32_t*>(p.w1) + k * 32 + lane);
                        const float a = k & 1 ? bf_hi(u) : bf_lo(u);
                        y0 = fmaf(a, bf_lo(w), y0);
                        y1 = fmaf(a, bf_hi(w), y1);
                    }
                    y0 = rbf16(y0); y1 = rbf16(y1);
                    x = pack2(y0 / (1.f + __expf(-y0)), y1 / (1.f + __expf(-y1)));
                    const float rb = rbf16(rbf16(__sinf(rbf16(d * __bfloat162float(p.freqs[lane & 15])))) / d);
#pragma unroll
                    for (int g = 0; g < 3; g++) {
                        float p0 = 0.f, p1 = 0.f, w0 = 0.f, w1 = 0.f;
#pragma unroll 4
                        for (int k = 0; k < 64; k++) {
                            const uint32_t u = __shfl_sync(0xffffffffu, x, k >> 1), w = __ldg(reinterpret_cast<const uint32_t*>(p.w2) + k * 96 + g * 32 + lane);
                            const float a = k & 1 ? bf_hi(u) : bf_lo(u);
                            p0 = fmaf(a, bf_lo(w), p0);
                            p1 = fmaf(a, bf_hi(w), p1);
                        }
#pragma unroll 4
                        for (int k = 0; k < 16; k++) {
                            const uint32_t w = __ldg(reinterpret_cast<const uint32_t*>(p.wr) + k * 96 + g * 32 + lane);
                            const float a = __shfl_sync(0xffffffffu, rb, k);
                            w0 = fmaf(a, bf_lo(w), w0);
                            w1 = fmaf(a, bf_hi(w), w1);
                        }
                        m2[2 * g] = rbf16(rbf16(p0) * rbf16(rbf16(w0) * fc));
                        m2[2 * g + 1] = rbf16(rbf16(p1) * rbf16(rbf16(w1) * fc));
                    }
                    atomicAdd(o, m2[0]);
                    atomicAdd(o + 1, m2[1]);
#pragma unroll
                    for (int k = 1; k < 4; k++) {
                        const uint32_t v = __ldg(row + 32 * k);
                        const float rh = rbf16((k == 1 ? bf_lo(xy) : k == 2 ? bf_hi(xy) : bf_lo(z)) / d);
                        atomicAdd(o + 64 * k, fmaf(m2[2], bf_lo(v), m2[4] * rh));
                        atomicAdd(o + 64 * k + 1, fmaf(m2[3], bf_hi(v), m2[5] * rh));
                    }
                }
            }
        }
        __syncthreads();
#pragma unroll 1
        for (int i = threadIdx.x; i < min(128, nn - c0) * 128; i += THREADS) {
            const uint32_t v = __ldg(sv + (size_t)(nbase + c0) * 128 + i);
            reinterpret_cast<uint32_t*>(p.out)[(size_t)(nbase + c0) * 128 + i] = pack2(bf_lo(v) + rbf16(acc[2 * i]), bf_hi(v) + rbf16(acc[2 * i + 1]));
        }
    }
}

template <int CN, int CE, int CG>
__global__ void __launch_bounds__(THREADS, 1) painn_kernel(const __grid_constant__ Params p) {
    extern __shared__ __align__(1024) unsigned char smem_dyn[];
    unsigned char* const smem = static_cast<unsigned char*>(__cvta_shared_to_generic(SB));
    constexpr uint32_t sb = SB;
    const int tid = threadIdx.x, lane = tid & 31;
    const int warp = __shfl_sync(0xffffffffu, tid >> 5, 0);
    constexpr int CNPC = CG ? (CN + CG - 1) / CG : 1, CGPC = CG ? (CE / 4 + CG - 1) / CG : 1;
    const int b = blockIdx.x, G = CG ? CG : p.G, NPC = CG ? CNPC : p.NPC, N = CG ? CN : p.N, gpc = CG ? CGPC : p.gpc;
    const uint32_t magic = CG ? (uint32_t)(((1ull << 32) + CNPC - 1) / CNPC) : p.magic;
    const bool odd_edges = CG ? (CE & 3) != 0 || CGPC > 3 * THREADS : p.odd_edges;
    const int nbase = b * NPC, nn = min(NPC, N - nbase);
    const int e0 = b * gpc, e1 = min((CG ? CE : p.E) >> 2, e0 + gpc);

    uint4* stage4 = reinterpret_cast<uint4*>(smem + STAGE_OFF);
    uint32_t* ncnt = reinterpret_cast<uint32_t*>(smem + NCNT_OFF);
    uint32_t* misc = reinterpret_cast<uint32_t*>(smem + MISC_OFF);
    const uint32_t bar_full = sb + BAR_OFF + (warp & 7) * 40, bar_empty = bar_full + 16, bar_side = bar_full + 32, bar_tab = sb + BAR_OFF + 336;

    auto warm = [&](int first, int n, int pause) {
#pragma unroll 1
        for (int i = first; i < first + n; i++) {
            if (elect())
                asm volatile("cp.async.bulk.tensor.2d.shared::cluster.global.mbarrier::complete_tx::bytes [%0], [%1, {0, %3}], [%2];"
                             ::"r"(sb + SINK_OFF), "l"(&p.tm), "r"(bar_tab + 8), "r"(nbase * 4 + i * 32) : "memory");
            if (pause) __nanosleep(pause);
        }
    };
    TS0(0);
    int4 es[3], ed[3];
    auto load_edges = [&](int i) {
        const int g = min(e0 + tid + i * THREADS, e1 - 1);
        asm volatile("ld.global.cs.v4.u32 {%0,%1,%2,%3}, [%8];\nld.global.cs.v4.u32 {%4,%5,%6,%7}, [%9];"
                     : "=r"(es[i].x), "=r"(es[i].y), "=r"(es[i].z), "=r"(es[i].w), "=r"(ed[i].x), "=r"(ed[i].y), "=r"(ed[i].z), "=r"(ed[i].w)
                     : "l"(reinterpret_cast<const int4*>(p.src) + g), "l"(reinterpret_cast<const int4*>(p.dst) + g) : "memory");
    };
    unsigned epoch;
    const uint32_t tbytes = ((N + 3) >> 2) * 16;
    {
        uint32_t pxy, pz;
        asm volatile("ld.global.nc.u32 %0, [%3];\nld.global.nc.u32 %1, [%3 + 4];\nld.global.ca.u32 %2, [%4];"
                     : "=r"(pxy), "=r"(pz), "=r"(epoch)
                     : "l"(reinterpret_cast<const uint32_t*>(p.pos) + ((nbase + min(tid, nn - 1)) * 3 >> 1)), "l"(p.g->sync) : "memory");
        const uint32_t sh = ((nbase + tid) & 1) << 4;
        pxy = __funnelshift_r(pxy, pz, sh);
        pz >>= sh;
        if (tid < nn) {
            reinterpret_cast<uint32_t*>(p.g->table)[nbase + tid] = qcode(bf_lo(pxy), bf_hi(pxy), bf_lo(pz), ((epoch & 31u) ^ 0x6Bu) << 24);
            p.g->pos8[nbase + tid] = make_uint2(pxy, pz);
        }
        reinterpret_cast<uint2*>(smem + OPOS_OFF)[tid] = make_uint2(pxy, pz);
        if (pxy == 0xFFFFFFFFu && pz == 0xFFFFFFFFu && epoch == 0xFFFFFFFFu) asm volatile("nanosleep.u32 0;");
        load_edges(0);
    }
    __syncthreads();
    const uint32_t tag = (epoch & 31u) | 32u;
    if (warp == 15) {
        if (elect()) {
            asm volatile("red.relaxed.gpu.global.add.u32 [%0], 1;" ::"l"(p.g->sync + 1) : "memory");
            asm volatile("prefetch.tensormap [%0];" ::"l"(&p.tm) : "memory");
            mbar_init(bar_tab, 1);
            mbar_init(bar_tab + 8, 1);
                        mbar_expect_tx(bar_tab, tbytes);
            mbar_expect_tx(bar_tab + 8, (WA + WC + WE) * 512);
        }
        TSX(1, 511);
        const unsigned want = (epoch + 1) * G;
        unsigned c;
        int it = smem_u32(smem_dyn) == SB ? 0 : 1 << 22;
        do {
            asm volatile("ld.relaxed.gpu.global.u32 %0, [%1];" : "=r"(c) : "l"(p.g->sync + 1) : "memory");
            if (++it > (1 << 22)) __trap();
        } while (c != want);
        __syncwarp();
        if (lane < TSPLIT) {
            const uint32_t part = (tbytes / TSPLIT) & ~127u, i = (lane + (TROT ? b : 0)) % TSPLIT;
            bulk_g2s(sb + i * part, reinterpret_cast<const char*>(p.g->table) + i * part, i == TSPLIT - 1 ? tbytes - i * part : part, bar_tab);
        }
        TSX(2, 511);
    }
    if (warp == 14) {
#pragma unroll 1
        for (int c = b * 32 + lane; c < WIMG / 16 + LUTS * 2; c += G * 32) {
            const int row = c >> 3, j = (c ^ row) & 7;
            uint4 v;
            if (c < 512) {
                const uint32_t half = 0x3F003F00u;
                v = __ldg(reinterpret_cast<const uint4*>(p.w1) + row * 8 + j);
                v = make_uint4(hmul2(v.x, half), hmul2(v.y, half), hmul2(v.z, half), hmul2(v.w, half));
            } else if (c >= WIMG / 16) {
                v = basis8(__uint_as_float((0x409D - ((c - WIMG / 16) >> 1)) << 16), __ldg(reinterpret_cast<const uint4*>(p.freqs) + (c & 1)));
            } else {
                const uint32_t* q = (c < 2048 ? reinterpret_cast<const uint32_t*>(p.w2) + (row & 63) * 96 + ((row >> 6) - 1) * 32
                                              : reinterpret_cast<const uint32_t*>(p.wr) + (row & 15) * 96 + ((row >> 4) - 16) * 32) + (j & 4) * 4 + (j & 3);
                v = make_uint4(__ldg(q), __ldg(q + 4), __ldg(q + 8), __ldg(q + 12));
            }
            p.g->wimg[c] = v;
        }
    }
    if (warp < 8 && elect()) {
        mbar_init(bar_full, 32); mbar_init(bar_full + 8, 32);
        mbar_init(bar_empty, 1);
        mbar_init(bar_side, 32);
        mbar_init(bar_full + 24, 1);
    }
    if (tid < MAXG) reinterpret_cast<uint32_t*>(smem + SCNT_OFF)[tid] = 0;
    if (tid < 48) misc[tid] = 0;
    {
        const uint32_t inv = (PAY_INVALID << 6) | tag;
        stage4[tid] = stage4[tid + THREADS] = make_uint4(inv, inv, inv, inv);
        if (tid < MAXG * (PITCH / 16) - 2 * THREADS) stage4[tid + 2 * THREADS] = make_uint4(inv, inv, inv, inv);
    }
    __syncthreads();
    {
    uint4* const xout = p.g->xbuf + ((tid >> 3) * G + b) * 8 + (tid & 7);
#pragma unroll
    for (int i = 0; i < 3; i++) stg128_if(xout + i * G * THREADS, make_uint4(0, 0, 0, 0), tid + i * THREADS < G * 8);
    }
    if (ED1) __nanosleep(ED1);
    load_edges(1);
    if (ED2 > 0) __nanosleep(ED2);
    if (ED2 >= 0) load_edges(2);
    if (tid == THREADS - 1) asm volatile("fence.acq_rel.gpu;" ::: "memory");
    mbar_wait(bar_tab, 0);
    TS0(3);
    if (ED2 < 0) load_edges(2);
    if (warp == 15) warm(0, WA, 0);

#pragma unroll 1
    for (int i = 0, g = e0 + tid; i < 3; i++, g += THREADS) {
        const int s[4] = {es[0].x, es[0].y, es[0].z, es[0].w}, d[4] = {ed[0].x, ed[0].y, ed[0].z, ed[0].w};
        uint32_t ca[4], cb[4], own[4], sl[4];
        bool c[4];
#pragma unroll
        for (int j = 0; j < 4; j++) { ca[j] = lds32(sb + 4 * s[j]); cb[j] = lds32(sb + 4 * d[j]); }
#pragma unroll
        for (int j = 0; j < 4; j++) {
            c[j] = near_test(ca[j], cb[j], tag << 24) && g < e1;
            own[j] = __umulhi((uint32_t)d[j], magic);
            sl[j] = atomicAdd(reinterpret_cast<uint32_t*>(smem + SCNT_OFF) + (c[j] ? own[j] : MAXG + lane), 4u);
        }
#pragma unroll
        for (int j = 0; j < 4; j++)
            sts32_if(sb + STAGE_OFF + own[j] * PITCH + sl[j], own[j] * (uint32_t)(-64 * NPC) + (((uint32_t)s[j] << 15) + (((uint32_t)d[j] << 6) + tag)),
                     c[j] && sl[j] < 124);
        es[0] = es[1]; es[1] = es[2];
        ed[0] = ed[1]; ed[1] = ed[2];
    }
    __syncthreads();
    {
        const int redo = __syncthreads_or(tid < MAXG && reinterpret_cast<uint32_t*>(smem + SCNT_OFF)[tid] > 124);
        if (__builtin_expect(redo || odd_edges, 0)) cold_filter(smem, p, e0, e1, tag, redo);
    }
    TS0(4);
#pragma unroll
    for (int i = 0; i < 2; i++) {
        const int r = min((tid >> 2) + i * (THREADS / 4), G), c = r * (PITCH / 16) + (tid & 3);
        uint4* const x = p.g->xbuf + (r * G + b) * 8 + (tid & 3);
        stg128_if(x, stage4[c], r < G);
        if (__builtin_expect(reinterpret_cast<uint32_t*>(smem + SCNT_OFF)[r] >= 64 && r < G, 0)) stg128_if(x + 4, stage4[c + 4], true);
    }
    ncnt[tid] = 0;
    if (tid < 480) reinterpret_cast<uint32_t*>(smem + SLOT_OFF)[tid] = tid < 32 ? tid * 0x100010 + 0x80000 : tid < 320 ? ~0u : 0u;
    if (tid == 511) reinterpret_cast<uint2*>(smem + NPOS_OFF)[511] = make_uint2(sb + SLOT_OFF + 1278, 0);
    __syncthreads();
    reinterpret_cast<uint4*>(smem + RR_OFF)[tid] = make_uint4(0, 0, 0, 0);
    if (tid < ROUNDS * 80 - THREADS) reinterpret_cast<uint4*>(smem + RR_OFF)[tid + THREADS] = make_uint4(0, 0, 0, 0);
    if (tid < ROUNDS * 32) reinterpret_cast<uint2*>(smem + SRC_OFF)[tid] = make_uint2(~0u, ~0u);
    __nanosleep(PDELAY);
    TS0(5);

    uint32_t rxy[4], gz[4], src[4], rk[4], dn[4];
    const uint32_t sink = sb + NCNT_OFF + 4 * (480 + lane);
    if (warp < 15) {
        uint32_t ew[3][4], bad[2];
        const int u = tid - 3 * G;
        const uint4* const xin = p.g->xbuf + b * G * 8;
        const uint4* cp = xin + (u < 0 ? tid + tid / 3 * 5 : u * 8 + 3);
        bad[0] = u < G;
        bad[1] = u >= 0 && u + 480 - 3 * G < G;
#pragma unroll
        for (int i = 0; i < 3; i++) ew[i][0] = ew[i][1] = ew[i][2] = ew[i][3] = (PAY_INVALID << 6) | tag;
        int it = 0;
#pragma unroll 1
        do {
#pragma unroll
            for (int i = 0; i < 2; i++)
                asm volatile("{\n.reg .pred p;\nsetp.ne.u32 p, %5, 0;\n@p ld.relaxed.gpu.global.v4.u32 {%0,%1,%2,%3}, [%4];\n}\n"
                             : "+r"(ew[i][0]), "+r"(ew[i][1]), "+r"(ew[i][2]), "+r"(ew[i][3]) : "l"(cp + i * (480 - 3 * G) * 8), "r"(bad[i]) : "memory");
#pragma unroll
            for (int i = 0; i < 2; i++) bad[i] = ((ew[i][0] ^ tag) | (ew[i][1] ^ tag) | (ew[i][2] ^ tag) | (ew[i][3] ^ tag)) & 63u;
            if (++it > (1 << 22)) __trap();
        } while (__any_sync(0xffffffffu, bad[0] | bad[1]));
        if (warp >= (3 * G) >> 5) {
            const uint32_t f0 = __ballot_sync(0xffffffffu, u >= 0 && ew[0][3] < (PAY_MARK << 6)), f1 = __ballot_sync(0xffffffffu, ew[1][3] < (PAY_MARK << 6));
            if (__builtin_expect(f0 | f1, 0)) {
                uint64_t f = (uint64_t)f1 << 32 | f0;
#pragma unroll 1
                for (int k = 7 - (lane >> 2); k; k--) f &= f - 1;
                if (f) {
                    const int l = __ffsll(f) - 1;
                    do {
                        asm volatile("ld.relaxed.gpu.global.v4.u32 {%0,%1,%2,%3}, [%4];" : "=r"(ew[2][0]), "=r"(ew[2][1]), "=r"(ew[2][2]), "=r"(ew[2][3])
                                     : "l"(xin + (u - lane + l + (l >> 5) * (448 - 3 * G)) * 8 + 4 + (lane & 3)) : "memory");
                        if (++it > (1 << 22)) __trap();
                    } while (((ew[2][0] ^ tag) | (ew[2][1] ^ tag) | (ew[2][2] ^ tag) | (ew[2][3] ^ tag)) & 63u);
                    if ((ew[2][3] >> 6) == PAY_MARK || lane == 0) misc[0] = 1;
                }
                __syncwarp();
            }
#pragma unroll 1
            for (int i = 0; i < 2; i++) {
                if (ew[0][0] >= (PAY_MARK << 6)) {
#pragma unroll
                    for (int j = 0; j < 4; j++) { ew[0][j] = ew[1][j]; ew[1][j] = ~0u; }
                }
                uint32_t from = __ballot_sync(0xffffffffu, ew[1][0] < (PAY_MARK << 6)), to = __ballot_sync(0xffffffffu, ew[0][0] >= (PAY_MARK << 6));
#pragma unroll 1
                for (; from; from &= from - 1, to &= to - 1) {
                    if (!to) misc[0] = 1;
#pragma unroll
                    for (int j = 0; j < 4; j++) {
                        const uint32_t x = __shfl_sync(0xffffffffu, ew[1][j], __ffs(from) - 1);
                        if (lane == __ffs(to) - 1) ew[0][j] = x;
                    }
                }
#pragma unroll
                for (int j = 0; j < 4; j++) ew[1][j] = ew[2][j];
            }
        }
        {
            uint2 ps[4], pd[4];
#pragma unroll
            for (int j = 0; j < 4; j++) {
                dn[j] = (ew[0][j] >> 3) & 4088u;
                src[j] = ew[0][j] >> 15;
                ps[j] = __ldcg(p.g->pos8 + (dn[j] == 4088u ? nbase : src[j]));
            }
#pragma unroll
            for (int j = 0; j < 4; j++) pd[j] = *reinterpret_cast<const uint2*>(smem + OPOS_OFF + dn[j]);
            if (WC) asm volatile("bar.arrive 1, 512;" ::: "memory");
            float q[4];
#pragma unroll
            for (int j = 0; j < 4; j++) {
                rxy[j] = hsub2(ps[j].x, pd[j].x);
                gz[j] = hsub2(ps[j].y, pd[j].y);
                q[j] = square(rxy[j], gz[j]);
                const bool in = q[j] < QMAX && dn[j] != 4088u;
                rk[j] = atoms_add(in ? sb + NCNT_OFF + (dn[j] >> 1) : sink, 512u);
                if (!in) dn[j] = 4088u;
            }
            uint32_t row[4], n = 0;
            bool single[4];
#pragma unroll
            for (int j = 0; j < 4; j++) {
                q[j] = distance(q[j]);
                row[j] = 0x409D - (__float_as_uint(q[j]) >> 16);
                single[j] = row[j] >= LUTS && dn[j] != 4088u;
                n += single[j];
            }
            n = atoms_add(n ? sb + MISC_OFF + 4 : sink, n) + LUTS;
#pragma unroll
            for (int j = 0; j < 4; j++) {
                float id;
                asm("rcp.approx.ftz.f32 %0, %1;" : "=f"(id) : "f"(q[j]));
                sts32_if(sb + LUT_OFF + min(n, LUTN - 1) * 32, __float_as_uint(q[j]), single[j]);
                if (single[j]) row[j] = n++;
                rxy[j] = pack2(bf_lo(rxy[j]) * id, bf_hi(rxy[j]) * id);
                gz[j] = pack2(0.f, bf_lo(gz[j]) * id) + row[j] * 32;
            }
        }
    } else {
        const uint4 fq = __ldg(reinterpret_cast<const uint4*>(p.freqs) + (lane & 1));
        rxy[0] = fq.x; rxy[1] = fq.y; rxy[2] = fq.z; rxy[3] = fq.w;
        if (WC) asm volatile("bar.sync 1, 512;" ::: "memory");
        warm(WA, WC, 0);
    }
    __syncthreads();
    TS0(6);

    const uint32_t lt = (1u << lane) - 1;
    uint32_t place = ~0u, mid = 0, last = 0, steps = 0, c = 0;
    if (warp < 15) {
        if (tid < nn) c = ncnt[tid] >> 9;
        steps = min((c + 1) >> 1, 15u);
        const uint32_t bin = tid >= nn ? 9 : c < 5 ? (0x54678u >> (4 * c)) & 15 : 6 - min(steps, 6u), sh = (bin & 1) * 16;
        const bool odd = c > 3 && (c & 1);
        const uint32_t peers = __match_any_sync(0xffffffffu, bin), om = __ballot_sync(0xffffffffu, odd);
        uint32_t x = atoms_add(lane == 0 ? sb + MISC_OFF + 4 * 37 : sink, __popc(om));
        uint32_t r = atoms_add((peers & lt) == 0 ? sb + MISC_OFF + 4 * 32 + 2 * (bin & 14) : sink, __popc(peers) << sh);
        x = __shfl_sync(0xffffffffu, x, 0) + __popc(om & lt);
        r = ((__shfl_sync(0xffffffffu, r, __ffs(peers) - 1) >> sh) & 0xFFFFu) + __popc(peers & lt);
        sts16_if(sb + (bin == 8 ? ZL_OFF : bin == 7 ? YL_OFF : TL_OFF) + 2 * r, tid, (0x190 >> bin) & 1);
        const uint64_t ones = 0x0001010101010101ull >> (56 - 8 * min(bin, 7u));
        asm volatile("bar.sync 2, 480;" ::: "memory");
        uint32_t h[4];
        lds128(sb + MISC_OFF + 4 * 32, h);
        const int nodd = misc[37], n1 = h[3] >> 16, n3 = h[2] & 0xFFFF, left = max(min(nodd + n3 - n1, n3), 0), half = left >> 1;
        const bool twin = bin == 4 && (int)r < 2 * half, pair = bin == 4 ? (twin ? !(r & 1) : (int)r >= left) : odd && (int)x < n1;
        const uint32_t y = lds16(twin ? sb + TL_OFF + 2 + 2 * r : sb + YL_OFF + 2 * (bin == 4 ? max(nodd + (int)r - left, 0) : x));
        const uint32_t base = __dp2a_lo(h[0], (uint32_t)ones, __dp2a_hi(h[1], (uint32_t)ones, 0u)) +
                              __dp2a_lo(h[2], (uint32_t)(ones >> 32), __dp2a_hi(h[3], (uint32_t)(ones >> 32), 0u));
        const bool unit = twin ? pair : bin < 7 || (bin == 7 && (int)r >= nodd + n3);
        if (unit) place = base + (twin ? r >> 1 : r - (bin < 4 ? 0 : half) - (bin == 7 ? nodd + n3 : 0));
        if (bin >= 7) misc[4] = base - half + max(n1 - nodd - n3, 0);
        steps += twin;
        last = (twin ? y : tid) | ST_CLOSE;
        if (pair) mid = y | (twin ? ST_MID : ST_MID | ST_CLOSE) | (tid << 16);
        const uint32_t sa = sb + SLOT_OFF + (steps < ROUNDS ? 2 * place : 1278);
        sts64_if(sb + NPOS_OFF + 8 * tid, sa, 0, unit);
        sts64_if(sb + NPOS_OFF + 8 * y, sa, c << 9, pair);
        asm volatile("{\n.reg .pred p;\nsetp.ne.u32 p, %2, 0;\n@p st.shared.u8 [%0], %1;\n}\n" ::"r"(sb + SIZE_OFF + place), "r"(steps), "r"((uint32_t)unit) : "memory");
    } else {
        if (elect()) {
            if (b == 0) p.g->sync[0] = epoch + 1;
            asm volatile("fence.proxy.async.global;" ::: "memory");
            mbar_expect_tx(bar_tab, WIMG + LUTS * 32);
            bulk_g2s(sb, p.g->wimg, WIMG, bar_tab);
            bulk_g2s(sb + LUT_OFF, p.g->wimg + WIMG / 16, LUTS * 32, bar_tab);
        }
        warm(WA + WC, WE, 0);
#pragma unroll 1
        for (uint32_t i = lane; i - lane < 2 * min(misc[1], LUTN - LUTS); i += 32) {
            const uint32_t d = lds32(sb + LUT_OFF + (LUTS + (i >> 1)) * 32);
            __syncwarp();
            reinterpret_cast<uint4*>(smem + LUT_OFF)[2 * LUTS + i] = basis8(__uint_as_float(d), make_uint4(rxy[0], rxy[1], rxy[2], rxy[3]));
        }
        TSX(12, 511);
    }
    __syncthreads();
    TS0(7);
    if (warp == 15) {
        uint32_t until0 = lds16(sb + SIZE_OFF + 2 * lane), until1 = until0 >> 8, next = 64, s0, s1;
        const uint32_t nsched = misc[4];
        until0 &= 255;
#pragma unroll 1
        for (uint32_t t = __reduce_min_sync(0xffffffffu, min(until0, until1)); t <= ROUNDS && next < nsched; t++) {
            const bool n0 = until0 == t, n1 = until1 == t;
            const uint32_t i = next + __popc(__ballot_sync(0xffffffffu, n0) & lt) + __popc(__ballot_sync(0xffffffffu, n1) & lt), j = i + n0;
            next += __reduce_add_sync(0xffffffffu, n0 + n1);
            asm volatile("ld.shared.u8 %0, [%2];\nld.shared.u8 %1, [%3];" : "=r"(s0), "=r"(s1) : "r"(sb + SIZE_OFF + i), "r"(sb + SIZE_OFF + j) : "memory");
            if (n0) until0 += s0;
            if (n1) until1 += s1;
            sts16_if(sb + SLOT_OFF + 2 * i, 1024 * t + 16 * lane, n0 && until0 < ROUNDS);
            sts16_if(sb + SLOT_OFF + 2 * j, 1024 * t + 16 * lane + 8, n1 && until1 < ROUNDS);
        }
        until0 = __reduce_max_sync(lane < 16 ? 0xFFFFu : 0xFFFF0000u, max(until0, until1));
        if ((lane & 15) == 0) misc[2 + (lane >> 4)] = until0;
        __syncthreads();
    } else {
#pragma unroll
        for (int j = 0; j < 4; j++) {
            const uint2 np = *reinterpret_cast<const uint2*>(smem + NPOS_OFF + dn[j]);
            dn[j] = np.x;
            rk[j] += np.y;
        }
#pragma unroll 1
        for (int pass = 0; pass < 2; pass++) {
            uint32_t e[4];
#pragma unroll
            for (int j = 0; j < 4; j++) e[j] = lds16(dn[j]);
            const uint32_t x = lds16(sb + SLOT_OFF + 2 * min(place, 639u));
#pragma unroll
            for (int j = 0; j < 4; j++) {
                sts16_if(sb + SRC_OFF + ((rk[j] + e[j]) >> 2), src[j], e[j] != 0xFFFFu);
                sts64_if(sb + RR_OFF + rk[j] + e[j], rxy[j], gz[j], e[j] != 0xFFFFu);
                if (e[j] != 0xFFFFu) dn[j] = sb + SLOT_OFF + 1278;
            }
            if (pass) {
                const uint32_t nd = sb + ND_OFF + ((x >> 2) & 0xFF00) + ((x >> 1) & 0xFC);
                sts32_if(nd, tid | ST_START, x != 0xFFFFu);
                sts32_if(nd + steps * 256 - 256, steps > 1 ? last : last | ST_START, x != 0xFFFFu && steps < ROUNDS);
                sts32_if(nd + c * 128 - 128, mid, x != 0xFFFFu && steps < ROUNDS && mid);
                break;
            }
            asm volatile("bar.sync 2, 480;" ::: "memory");
            if (warp < 8) {
                const int s = lane >> 3, c = lane & 7;
                const uint32_t dst = sb + RING_OFF + warp * 16384 + s * 128, y = sb + SRC_OFF + (warp * 8 + s) * 2;
                const uint32_t sdst = dst + ((c ^ s) << 4), vdst = dst + ((c ^ ((s & 1) << 2)) << 4);
                const uint32_t s0 = lds16(y), s1 = lds16(y + 8), s2 = lds16(y + 128), s3 = lds16(y + 136);
                const char* svl = reinterpret_cast<const char*>(p.sv) + c * 16;
                gather_s(sdst, svl, s0);
                gather_s((sdst ^ 64) + 512, svl, s1);
                gather_s(sdst + 8192, svl, s2);
                gather_s((sdst ^ 64) + 8704, svl, s3);
                cp_async_arrive(bar_full);
                TS0(10);
                if (P0) __nanosleep(warp & 4 ? P1W : P0);
                gather_v(vdst, svl, s0);
                if (P0) __nanosleep(P0);
                gather_v(vdst + 512, svl, s1);
                if (P0) __nanosleep(P0);
                gather_v(vdst + 8192, svl, s2);
                if (P0) __nanosleep(P0);
                gather_v(vdst + 8704, svl, s3);
                asm volatile("cp.async.mbarrier.arrive.shared::cta.b64 [%0];" ::"r"(bar_side) : "memory");
            }
            __syncthreads();
            TS0(8);
        }
    }
    uint32_t st[4];
    lds128(sb + MISC_OFF, st);
    __syncthreads();
    if (__builtin_expect(max(st[2], st[3]) >= ROUNDS || st[1] > LUTN - LUTS || st[0], 0)) {
        asm volatile("cp.async.wait_all;" ::: "memory");
        mbar_wait(bar_tab, 1);
        mbar_wait(bar_tab + 8, 0);
        cold_nodes(smem, p, nn, tag);
        return;
    }
    TS0(9);
    const int T = __shfl_sync(0xffffffffu, warp & 4 ? st[3] : st[2], 0);

    if (warp < 8) {
        asm volatile("setmaxnreg.inc.sync.aligned.u32 %0;" ::"n"(REG_C));
        const int lane = fresh_lane();
        const int g = lane >> 2, q = lane & 3;
        const uint64_t d0 = (uint64_t)__shfl_sync(0xffffffffu, pin((uint32_t)(p.desc0 >> 32)), 0) << 32 | __shfl_sync(0xffffffffu, pin((uint32_t)p.desc0), 0);
        const uint32_t swz = g * 128 + ((q ^ ((g & 1) << 2)) << 4);
        const uint32_t srow = pin(sb + SIDE_OFF + warp * 4096 + swz);
        uint32_t vrow = pin(sb + RING_OFF + warp * 16384 + swz + 4096);
        uint32_t ent = pin(sb + RR_OFF + (warp * 8 + g) * 8), fent = pin(sb + ND_OFF + (warp * 8 + g) * 4);
        uint32_t lent = pin(sb + RR_OFF + (warp * 8 + (lane & 7)) * 8 + 4 + (lane & 8) * 64);
        const uint32_t lutq = pin(sb + LUT_OFF + (lane >> 4) * 16);
        uint64_t outq;
        {
            const uint64_t a = reinterpret_cast<uint64_t>(p.out) + (size_t)nbase * 512 + q * 16;
            const uint32_t lo = pin((uint32_t)a), hi = pin((uint32_t)(a >> 32));
            asm volatile("mov.b64 %0, {%1, %2};" : "=l"(outq) : "r"(lo), "r"(hi));
        }
        uint32_t acc[32], rf[4], h[16], rr[4], fl = 0;
#pragma unroll
        for (int i = 0; i < 32; i++) asm volatile("" : "=r"(acc[i]));
#pragma unroll
        for (int i = 0; i < 16; i++) asm volatile("" : "=r"(h[i]));
#pragma unroll
        for (int i = 0; i < 4; i++) asm volatile("" : "=r"(rf[i]), "=r"(rr[i]));
        int t = -1;
        TSX(18, 0);
        mbar_wait(bar_tab, 1);
        if (warp & 4) __nanosleep(st[2] > st[3] ? STAG : STAG2);
        TSX(14, 0);
        const int Tm = __shfl_sync(0xffffffffu, min(st[2], st[3]), 0);
        if (warp >= 4 && Tm > 0) asm volatile("bar.arrive 3, 256;" ::: "memory");
        bool more = T < 0x7FFFFFFF;
#pragma unroll 1
        while (more) {
            float y[32], p1[32], w1[32], p2[32], w2[32], p3[32], w3[32];
            uint32_t m1[16], m2[16], v[3][16], ts[8];
            auto products = [](uint32_t* m, const float* P, const float* W) {
#pragma unroll
                for (int j = 0; j < 8; j++) {
                    m[j] = pack2(P[4 * j] * W[4 * j], P[4 * j + 1] * W[4 * j + 1]);
                    m[8 + j] = pack2(P[4 * j + 2] * W[4 * j + 2], P[4 * j + 3] * W[4 * j + 3]);
                }
            };
            auto vterm = [&](int k, int o) {
#pragma unroll
                for (int j = 0; j < 8; j++) acc[8 * k + 8 + j] = hfma2(m1[o + j], v[k][o + j], acc[8 * k + 8 + j]);
            };
            auto rterm = [&](int k, int o) {
#pragma unroll
                for (int j = 0; j < 8; j++)
                    acc[8 * k + 8 + j] = k == 0 ? hfma2_lo(m2[o + j], rr[o / 4], acc[8 * k + 8 + j]) : hfma2_hi(m2[o + j], rr[o / 4 + k / 2], acc[8 * k + 8 + j]);
            };
            TR(0, 0, t);
            uint64_t om, op;
#pragma unroll
            for (int j = 0; j < 8; j++) asm volatile("" : "=r"(ts[j]), "=r"(m1[8 + j]), "=r"(m2[8 + j]), "=r"(v[0][8 + j]), "=r"(v[1][8 + j]), "=r"(v[2][8 + j]));
            asm volatile("" : "=l"(om));
            if (t >= 0) {
            TC(0);
            if (t < Tm) asm volatile("bar.sync %0, 256;" ::"r"(3 + (warp >> 2)) : "memory");
            wg_fence();
            wgmma_rs2<W2_OFF + 8192, 8192, 0>(p1, p2, h, d0);
            wgmma_rs2<W2_OFF + 10240, 8192, 1>(p1, p2, h + 4, d0);
            wgmma_rs2<W2_OFF + 12288, 8192, 1>(p1, p2, h + 8, d0);
            wgmma_rs2<W2_OFF + 14336, 8192, 1>(p1, p2, h + 12, d0);
            wgmma_rs2<WR_OFF + 2048, 2048, 0>(w1, w2, rf, d0);
            wg_commit();
            TC(1);
            mbar_waitc(bar_side, t & 1);
            TC(2);
#pragma unroll
            for (int k = 0; k < 4; k++) lds2_if(srow + 1024 * k, (srow ^ 64) + 1024 * k, acc + 8 * k, fl & ST_START);
            wg_wait<N128 ? 0 : 1>();
            fence_regs(p1); fence_regs(w1);
            TC(3);
            products(m1, p1, w1);
#pragma unroll
            for (int k = 0; k < 3; k++) { lds128(vrow + 1024 + 1024 * k, v[k]); lds128((vrow ^ 64) + 1024 + 1024 * k, v[k] + 4); }
            if (!N128) wg_wait<0>();
            fence_regs(p2); fence_regs(w2);
            products(m2, p2, w2);
            asm("mad.wide.u32 %0, %1, 512, %2;" : "=l"(om) : "r"(fl >> 16), "l"(outq));
#pragma unroll
            for (int k = 0; k < 3; k++) { lds128(vrow + 9216 + 1024 * k, v[k] + 8); lds128((vrow ^ 64) + 9216 + 1024 * k, v[k] + 12); }
#pragma unroll
            for (int j = 0; j < 8; j++) asm volatile("" : "=r"(ts[j]));
            lds2_if(srow, srow ^ 64, ts, fl & ST_MID);
#pragma unroll
            for (int k = 0; k < 3; k++) { vterm(k, 0); rterm(k, 0); stg2_if(om + 128 + 128 * k, acc + 8 + 8 * k, fl & ST_MID); }
            TC(4);
            if (t + (warp >> 2) < Tm) asm volatile("bar.arrive %0, 256;" ::"r"(4 - (warp >> 2)) : "memory");
            }
            t++;
            wg_fence();
            wgmma_group<0>(p3, w3, h, rf, d0);
            wg_commit();
            if (T > 1000000) asm volatile("nanosleep.u32 0;");
#pragma unroll
            for (int k = 1; k < 4; k++) lds2_if(srow + 1024 * k, (srow ^ 64) + 1024 * k, acc + 8 * k, fl & ST_MID);
            uint32_t lo;
            asm volatile("ld.shared.u16 %0, [%1];" : "=r"(lo) : "r"(lent) : "memory");
            __syncwarp();
            if (lane == 0 && t > 0) mbar_arrive(bar_empty);
            if (t > 0) TC(5);
            mbar_waitc(bar_full + 8 * (t & 1), (t >> 1) & 1);
            if (t > 0) TC(6);
            wg_fence();
            wgmma_ss_k64(y, d0 + ((RING_OFF >> 4) + (warp >> 2) * 4096 + (t & 1) * 256 + ((uint64_t)(512 - 64) << 32)), d0);
            wg_commit();
            if (T > 1000000) asm volatile("nanosleep.u32 0;");
            asm("mad.wide.u32 %0, %1, 512, %2;" : "=l"(op) : "r"(fl & 511), "l"(outq));
            vrow ^= 4096;
            more = t < T;
#pragma unroll
            for (int k = 0; k < 3; k++) vterm(k, 8);
#define BBS if (T > 1000000) asm volatile("nanosleep.u32 0;")
            auto silu = [&](int i0, int i1) {
#pragma unroll
                for (int i = i0; i < i1; i++)
                    h[i] = pack2(fmaf(y[2 * i], tanh_fast(y[2 * i]), y[2 * i]), fmaf(y[2 * i + 1], tanh_fast(y[2 * i + 1]), y[2 * i + 1]));
            };
#pragma unroll
            for (int k = 0; k < 3; k++) rterm(k, 8);
            const uint32_t fo = fl;
            asm volatile("ld.shared.v2.u32 {%0,%1}, [%4];\nld.shared.v2.u32 {%2,%3}, [%4 + 512];" : "=r"(rr[0]), "=r"(rr[1]), "=r"(rr[2]), "=r"(rr[3]) : "r"(ent) : "memory");
            asm volatile("ld.shared.u32 %0, [%1];" : "=r"(fl) : "r"(fent) : "memory");
            stg2_if(op + 128, acc + 8, fo & ST_CLOSE);
            BBS;
            if (t > 0) TC(7);
            wg_wait<0>();
            fence_regs(p3); fence_regs(w3); fence_regs(y);
            if (t > 0) TC(8);
            ldsm4(lutq + lo, rf);
            products(m1, p3, w3);
            silu(0, SPREAD == 1 ? 6 : 4);
            stg2_if(op + 256, acc + 16, fo & ST_CLOSE);
            BBS;
#pragma unroll
            for (int j = 0; j < 8; j++) acc[j] = hadd2(acc[j], m1[j]);
            stg2_if(om, acc, fo & ST_MID);
#pragma unroll
            for (int j = 0; j < 8; j++) acc[j] = hadd2(fo & ST_MID ? ts[j] : acc[j], m1[8 + j]);
            silu(SPREAD == 1 ? 6 : 4, SPREAD == 1 ? 11 : 10);
            stg2_if(op + 384, acc + 24, fo & ST_CLOSE);
            BBS;
            silu(SPREAD == 1 ? 11 : 10, SPREAD == 1 ? 16 : 14);
            if (SPREAD == 2) BBS;
            stg2_if(op, acc, fo & ST_CLOSE);
            silu(SPREAD == 1 ? 16 : 14, 16);
            ent += 1024; fent += 256; lent += 1024;
        }
        TSX(15, 0);
        TSX(16, 128);
    } else {
        asm volatile("setmaxnreg.dec.sync.aligned.u32 %0;" ::"n"(256 - REG_C));
        const int lane = fresh_lane();
        const int w = warp - 8, s = lane >> 3, c = lane & 7, nzero = misc[36] & 0xFFFF;
        uint32_t sdst = sb + RING_OFF + w * 16384 + s * 128 + ((c ^ s) << 4);
        const uint32_t sw = s * 128 + ((c ^ ((s & 1) << 2)) << 4);
        uint32_t vdst = sb + RING_OFF + w * 16384 + sw;
        const uint32_t odst = sb + SIDE_OFF + w * 4096 + sw;
        uint32_t ent = sb + ND_OFF + (w * 8 + s) * 4;
        const char* svl = reinterpret_cast<const char*>(p.sv) + c * 16;
        const char* own = svl + (size_t)nbase * 512;
        if (LAG || LAG0) __nanosleep((warp & 4 ? LAG1 : LAG0) + LAG * max(min(LAGT - (int)(misc[2] + misc[3]), LAGM), 0));
#pragma unroll 1
        for (int t = 1; t <= T; t++) {
            const uint32_t e = sb + SRC_OFF + t * 256 + (w * 8 + s) * 2;
            const uint32_t s0 = lds16(e), s1 = lds16(e + 8), s2 = lds16(e + 128), s3 = lds16(e + 136);
            const uint32_t f0 = lds32(ent), f1 = lds32(ent + 16);
            ent += 256;
            sdst ^= 4096; vdst ^= 4096;
            TR(5, 256, t);
            mbar_wait(bar_empty, t & 1);
            TR(6, 256, t);
            gather_row_if(odst, own + (f0 & 511) * 512, f0 & (ST_START | ST_MID));
            gather_row_if(odst + 512, own + (f1 & 511) * 512, f1 & (ST_START | ST_MID));
            if (!ONEB) cp_async_arrive(bar_side);
            gather_s(sdst, svl, s0);
            gather_s((sdst ^ 64) + 512, svl, s1);
            gather_s(sdst + 8192, svl, s2);
            gather_s((sdst ^ 64) + 8704, svl, s3);
            cp_async_arrive(ONEB ? bar_side : bar_full + 8 * (t & 1));
            if (t < T) {
                if (PACE) __nanosleep(PACE);
                gather_v(vdst, svl, s0);
                if (PACE) __nanosleep(PACE);
                gather_v(vdst + 512, svl, s1);
                if (PACE) __nanosleep(PACE);
                gather_v(vdst + 8192, svl, s2);
                if (PACE) __nanosleep(PACE);
                gather_v(vdst + 8704, svl, s3);
            }
            TR(7, 256, t);
        }
        TSX(17, 256);
        const int z0 = ZW1 ? (w & 3) + ((w >> 2) == (misc[2] > misc[3]) ? 0 : 48) : w, zs = ZW1 ? 4 : 8;
#pragma unroll 1
        for (int z = z0 + zs * lane, ph = 0; z - zs * lane < nzero; z += 96, ph ^= 1) {
            const bool on = lane < 12 && z < nzero;
            const uint32_t row = sb + RING_OFF + w * 16384 + (max(T, 1) & 1) * 4096 + 1024 + (lane + (lane < 6 ? 0 : 10)) * 512;
            const size_t o = (size_t)(nbase + lds16(sb + ZL_OFF + 2 * min(z, 511))) * 256;
            const uint32_t n = __popc(__ballot_sync(0xffffffffu, on));
            if (lane == 0) mbar_expect_tx(bar_full + 24, n * 512);
            if (on) bulk_g2s(row, p.sv + o, 512, bar_full + 24);
            mbar_wait(bar_full + 24, ph);
            if (on) asm volatile("{\n.reg .b64 pol;\ncreatepolicy.fractional.L2::evict_first.b64 pol, 1.0;\n"
                                 "cp.async.bulk.global.shared::cta.bulk_group.L2::cache_hint [%0], [%1], 512, pol;\n"
                                 "cp.async.bulk.commit_group;\ncp.async.bulk.wait_group.read 0;\n}\n" ::"l"(p.out + o), "r"(row) : "memory");
            __syncwarp();
        }
        mbar_wait(bar_tab + 8, 0);
        TSX(11, 256);
    }
}

}

extern "C" void kernel_launch(void* const* d_in, const int* in_sizes, int n_in, void* d_out, int out_size) {
    static int s_G = 0;
    static void* s_scratch = nullptr;
    static void* s_encode = nullptr;
    const int N = in_sizes[0] / 256, E = in_sizes[2];
    if (s_G == 0) {
        cudaFuncSetAttribute(painn_kernel<0, 0, 0>, cudaFuncAttributeMaxDynamicSharedMemorySize, SMEM_BYTES);
        cudaFuncSetAttribute(painn_kernel<50000, 800000, 132>, cudaFuncAttributeMaxDynamicSharedMemorySize, SMEM_BYTES);
        int dev = 0, sms = 0, occ = 0;
        cudaGetDevice(&dev);
        cudaDeviceGetAttribute(&sms, cudaDevAttrMultiProcessorCount, dev);
        cudaOccupancyMaxActiveBlocksPerMultiprocessor(&occ, painn_kernel<0, 0, 0>, THREADS, SMEM_BYTES);
        cudaGetSymbolAddress(&s_scratch, g_scratch);
        cudaDriverEntryPointQueryResult qr;
        cudaGetDriverEntryPoint("cuTensorMapEncodeTiled", &s_encode, cudaEnableDefault, &qr);
        s_G = occ >= 1 ? (sms < MAXG ? sms : MAXG) : 0;
    }
    if (s_G == 0 || N > TABLE_MAXN || N > s_G * (MAXNPC - 1) || (s_G - 1) * ((N + s_G - 1) / s_G) >= N || E > MAXE || E < 4 * MAXG * MAXG) return;
    Params p;
    {
        typedef CUresult (*Encode)(CUtensorMap*, CUtensorMapDataType, cuuint32_t, void*, const cuuint64_t*, const cuuint64_t*, const cuuint32_t*,
                                   const cuuint32_t*, CUtensorMapInterleave, CUtensorMapSwizzle, CUtensorMapL2promotion, CUtensorMapFloatOOBfill);
        const cuuint64_t dims[2] = {64, (cuuint64_t)N * 4}, strides[1] = {128};
        const cuuint32_t box[2] = {8, 32}, es[2] = {1, 1};
        ((Encode)s_encode)(&p.tm, CU_TENSOR_MAP_DATA_TYPE_BFLOAT16, 2, d_in[0], dims, strides, box, es, CU_TENSOR_MAP_INTERLEAVE_NONE,
                           CU_TENSOR_MAP_SWIZZLE_NONE, CU_TENSOR_MAP_L2_PROMOTION_L2_128B, CU_TENSOR_MAP_FLOAT_OOB_FILL_NONE);
    }
    p.g = (Scratch*)s_scratch;
    p.sv = (const __nv_bfloat16*)d_in[0];
    p.pos = (const __nv_bfloat16*)d_in[1];
    p.src = (const int*)d_in[2];
    p.dst = (const int*)d_in[3];
    p.freqs = (const __nv_bfloat16*)d_in[4];
    p.w1 = (const __nv_bfloat16*)d_in[5];
    p.w2 = (const __nv_bfloat16*)d_in[6];
    p.wr = (const __nv_bfloat16*)d_in[7];
    p.out = (__nv_bfloat16*)d_out;
    p.desc0 = (uint64_t)(SB >> 4) | ((uint64_t)1 << 16) | ((uint64_t)64 << 32) | ((uint64_t)1 << 62);
    p.N = N; p.E = E; p.G = s_G;
    p.NPC = (N + s_G - 1) / s_G;
    p.magic = (uint32_t)(((1ull << 32) + p.NPC - 1) / p.NPC);
    p.gpc = ((E >> 2) + s_G - 1) / s_G;
    p.odd_edges = (E & 3) != 0 || p.gpc > 3 * THREADS;
    if (N == 50000 && E == 800000 && s_G == 132) painn_kernel<50000, 800000, 132><<<s_G, THREADS, SMEM_BYTES, cudaStreamPerThread>>>(p);
    else painn_kernel<0, 0, 0><<<s_G, THREADS, SMEM_BYTES, cudaStreamPerThread>>>(p);
}
```

```cpp
#include <cuda_runtime.h>
#include <cuda_bf16.h>
#include <cuda.h>
#include <stdint.h>

namespace {

constexpr int REG_C = 224;
#define PDELAY 200
#define WA 6
#define WC 3
#define WP 0
#define WE 3
#define GROLL 0
#define RESV 0
#define SPREAD 1
#define PACE 0
#define LATES 0
#define EARLYR 2
#define ARRE 0
#define WAITV 0
#define STAG 0
#define ONEB 0
#define LAG 400
#define ZW1 1
#define LAG0 0
#define LAGT 16
#define LAGM 3
#define P0 80
#define ED1 0
#define ED2 0
#define CLR 0
#define TSPLIT 8
#define TROT 0
#define DUMMY 0
#define N128 1
#define NRES 4
#define STAG2 0
#define PP 3
#define P1W 200
#define LAG1 700
#define LASTS 0
#define ZPF 0
#define STP ".cs"
#define ZP "evict_first"
#define EP ".cs"
#define WX 0
#define WH 0
#define WH0 0
#define WHE 0
#define PEEL 1
#define SKIP1 1
constexpr int THREADS = 512;
constexpr int MAXG = 136;
constexpr int ROUNDS = 11;
constexpr int LUTS = 286, LUTN = 318;
constexpr int MAXNPC = 480;
constexpr int MAXE = 1 << 20;

constexpr int W2_OFF = 8192;
constexpr int WR_OFF = 32768;
constexpr int WIMG = 38912;
constexpr int ZL_OFF = WIMG;
constexpr int RING_OFF = 39936;
constexpr int SIDE_OFF = RING_OFF + 16 * 8192;
constexpr int RR_OFF = SIDE_OFF + 32768;
constexpr int ND_OFF = RR_OFF + ROUNDS * 1024;
constexpr int SRC_OFF = ND_OFF + ROUNDS * 256;
constexpr int LUT_OFF = SRC_OFF + ROUNDS * 256;
constexpr int SINK_OFF = LUT_OFF + 320 * 32;
constexpr int BAR_OFF = SINK_OFF + 512;
constexpr int MISC_OFF = BAR_OFF + 8 * 46;
constexpr int SMEM_BYTES = MISC_OFF + 192 + MAXG;
#define PITCH 144
constexpr int TABLE_MAXN = 50176;
constexpr int STAGE_OFF = TABLE_MAXN * 4;
constexpr int SCNT_OFF = STAGE_OFF + MAXG * PITCH;
constexpr int OVL_OFF = MISC_OFF + 192;
constexpr int OPOS_OFF = LUT_OFF + 1024;
constexpr int NCNT_OFF = SIDE_OFF;
constexpr int NPOS_OFF = NCNT_OFF + 2048;
constexpr int YL_OFF = NPOS_OFF + 4096;
constexpr int TL_OFF = YL_OFF + 1024;
constexpr int SLOT_OFF = TL_OFF + 1024;
constexpr int SIZE_OFF = SLOT_OFF + 1280;
static_assert(SCNT_OFF + 4 * (MAXG + 32) <= OPOS_OFF && OPOS_OFF + 4096 <= LUT_OFF + LUTS * 32, "smem map");
static_assert(2 * (480 - 3 * MAXG) >= MAXG, "chunk map");
static_assert(SMEM_BYTES <= 232448 && MISC_OFF % 16 == 0 && BAR_OFF % 8 == 0 && (RING_OFF + 1024) % 8192 == 0 && SINK_OFF % 128 == 0, "smem map");

constexpr uint32_t PAY_INVALID = 0x3FFFFFFu;
constexpr uint32_t PAY_MARK = 0x3FFFDFFu;
constexpr uint32_t ST_START = 512, ST_CLOSE = 1024, ST_MID = 2048;
constexpr float QINVP = 9.0f / 510.0f;
constexpr uint32_t QTHRESH = 2126;

struct Scratch {
    unsigned sync[32];
    uint4 table[TABLE_MAXN / 4];
    uint4 wimg[WIMG / 16 + LUTS * 2];
    uint2 pos8[TABLE_MAXN];
    uint4 xbuf[MAXG * MAXG * 8 + 3 * THREADS];
    int ovfcnt[MAXG];
    int2 ovf[MAXE + 8 * MAXG + 8];
};
__device__ __align__(128) Scratch g_scratch;

struct Params {
    CUtensorMap tm;
    const __nv_bfloat16* pos;
    Scratch* g;
    const int* src;
    const int* dst;
    int N, NPC, E, gpc;
    const __nv_bfloat16* w2;
    const __nv_bfloat16* wr;
    const __nv_bfloat16* w1;
    const __nv_bfloat16* freqs;
    const __nv_bfloat16* sv;
    __nv_bfloat16* out;
    uint64_t desc0;
    int G;
    uint32_t magic;
    int odd_edges;
};
constexpr uint32_t SB = 1024;

#define TSX(i, thr)
#define TR(k, thr, t)
#define TC(k)
#define TS0(i) TSX(i, 0)

__device__ __forceinline__ uint32_t smem_u32(const void* p) { return (uint32_t)__cvta_generic_to_shared(p); }
__device__ __forceinline__ void mbar_init(uint32_t bar, uint32_t cnt) {
    asm volatile("mbarrier.init.shared::cta.b64 [%0], %1;" ::"r"(bar), "r"(cnt) : "memory");
}
__device__ __forceinline__ void mbar_arrive(uint32_t bar) {
    asm volatile("mbarrier.arrive.shared::cta.b64 _, [%0];" ::"r"(bar) : "memory");
}
__device__ __forceinline__ void mbar_expect_tx(uint32_t bar, uint32_t bytes) {
    asm volatile("mbarrier.arrive.expect_tx.shared::cta.b64 _, [%0], %1;" ::"r"(bar), "r"(bytes) : "memory");
}
__device__ __forceinline__ void mbar_wait(uint32_t bar, uint32_t parity) {
    asm volatile("{\n.reg .pred p;\n.reg .u32 c;\nmbarrier.try_wait.parity.shared::cta.b64 p, [%0], %1;\n@p bra DONE;\nmov.u32 c, 0;\n"
                 "AGAIN:\nmbarrier.try_wait.parity.shared::cta.b64 p, [%0], %1, 2000;\n@p bra DONE;\nadd.u32 c, c, 1;\n"
                 "setp.lt.u32 p, c, 0x100000;\n@p bra AGAIN;\ntrap;\nDONE:\n}\n" ::"r"(bar), "r"(parity) : "memory");
}
__device__ __forceinline__ void mbar_waitc(uint32_t bar, uint32_t parity) {
    mbar_wait(bar, parity);
}
__device__ __forceinline__ bool elect() {
    uint32_t r;
    asm volatile("{\n.reg .pred p;\nelect.sync _|p, 0xffffffff;\nselp.u32 %0, 1, 0, p;\n}\n" : "=r"(r));
    return r;
}
__device__ __forceinline__ uint32_t pin(uint32_t x) {
    uint32_t r;
    asm volatile("shfl.sync.bfly.b32 %0, %1, 0, 31, -1;" : "=r"(r) : "r"(x));
    return r;
}
__device__ __forceinline__ void bulk_g2s(uint32_t dst, const void* src, uint32_t bytes, uint32_t bar) {
    asm volatile("cp.async.bulk.shared::cluster.global.mbarrier::complete_tx::bytes [%0], [%1], %2, [%3];"
                 ::"r"(dst), "l"(src), "r"(bytes), "r"(bar) : "memory");
}
__device__ __forceinline__ void ldsm4(uint32_t addr, uint32_t* r) {
    asm volatile("ldmatrix.sync.aligned.m8n8.x4.shared.b16 {%0,%1,%2,%3}, [%4];"
                 : "=r"(r[0]), "=r"(r[1]), "=r"(r[2]), "=r"(r[3]) : "r"(addr) : "memory");
}
__device__ __forceinline__ uint32_t pack2(float lo, float hi) {
    uint32_t r;
    asm("cvt.rn.bf16x2.f32 %0, %1, %2;" : "=r"(r) : "f"(hi), "f"(lo));
    return r;
}
__device__ __forceinline__ float bf_lo(uint32_t w) { return __uint_as_float(w << 16); }
__device__ __forceinline__ float bf_hi(uint32_t w) { return __uint_as_float(w & 0xFFFF0000u); }
__device__ __forceinline__ float rbf16(float x) { return __uint_as_float(pack2(0.f, x)); }
__device__ __forceinline__ uint32_t hmul2(uint32_t a, uint32_t b) {
    uint32_t r;
    asm("mul.rn.bf16x2 %0, %1, %2;" : "=r"(r) : "r"(a), "r"(b));
    return r;
}
__device__ __forceinline__ uint32_t hfma2(uint32_t a, uint32_t b, uint32_t c) {
    uint32_t r;
    asm("fma.rn.bf16x2 %0, %1, %2, %3;" : "=r"(r) : "r"(a), "r"(b), "r"(c));
    return r;
}
__device__ __forceinline__ uint32_t hfma2_lo(uint32_t a, uint32_t b, uint32_t c) {
    uint32_t r;
    asm("{\n.reg .b16 l, h;\n.reg .b32 t;\nmov.b32 {l, h}, %2;\nmov.b32 t, {l, l};\nfma.rn.bf16x2 %0, %1, t, %3;\n}\n" : "=r"(r) : "r"(a), "r"(b), "r"(c));
    return r;
}
__device__ __forceinline__ uint32_t hfma2_hi(uint32_t a, uint32_t b, uint32_t c) {
    uint32_t r;
    asm("{\n.reg .b16 l, h;\n.reg .b32 t;\nmov.b32 {l, h}, %2;\nmov.b32 t, {h, h};\nfma.rn.bf16x2 %0, %1, t, %3;\n}\n" : "=r"(r) : "r"(a), "r"(b), "r"(c));
    return r;
}
__device__ __forceinline__ uint32_t hadd2(uint32_t a, uint32_t b) {
    uint32_t r;
    asm("add.rn.bf16x2 %0, %1, %2;" : "=r"(r) : "r"(a), "r"(b));
    return r;
}
__device__ __forceinline__ uint32_t hsub2(uint32_t a, uint32_t b) {
    uint32_t r;
    asm("sub.rn.bf16x2 %0, %1, %2;" : "=r"(r) : "r"(a), "r"(b));
    return r;
}
__device__ __forceinline__ void cp_async_arrive(uint32_t bar) {
    asm volatile("cp.async.mbarrier.arrive.noinc.shared::cta.b64 [%0];" ::"r"(bar) : "memory");
}
__device__ __forceinline__ float tanh_fast(float x) {
    float r;
    asm("tanh.approx.f32 %0, %1;" : "=f"(r) : "f"(x));
    return r;
}
__device__ __forceinline__ void wg_fence() { asm volatile("wgmma.fence.sync.aligned;" ::: "memory"); }
__device__ __forceinline__ void wg_commit() { asm volatile("wgmma.commit_group.sync.aligned;" ::: "memory"); }
template <int N>
__device__ __forceinline__ void wg_wait() { asm volatile("wgmma.wait_group.sync.aligned %0;" ::"n"(N) : "memory"); }

#define WG_REGS "{%0,%1,%2,%3,%4,%5,%6,%7,%8,%9,%10,%11,%12,%13,%14,%15,%16,%17,%18,%19,%20,%21,%22,%23,%24,%25,%26,%27,%28,%29,%30,%31}"
#define WG_OPS(c) c(d[0]), c(d[1]), c(d[2]), c(d[3]), c(d[4]), c(d[5]), c(d[6]), c(d[7]), c(d[8]), c(d[9]), c(d[10]), \
    c(d[11]), c(d[12]), c(d[13]), c(d[14]), c(d[15]), c(d[16]), c(d[17]), c(d[18]), c(d[19]), c(d[20]), c(d[21]),     \
    c(d[22]), c(d[23]), c(d[24]), c(d[25]), c(d[26]), c(d[27]), c(d[28]), c(d[29]), c(d[30]), c(d[31])
#define WG_OPSE(c) c(e[0]), c(e[1]), c(e[2]), c(e[3]), c(e[4]), c(e[5]), c(e[6]), c(e[7]), c(e[8]), c(e[9]), c(e[10]), c(e[11]), c(e[12]), c(e[13]), c(e[14]), c(e[15]), c(e[16]), c(e[17]), c(e[18]), c(e[19]), c(e[20]), c(e[21]), c(e[22]), c(e[23]), c(e[24]), c(e[25]), c(e[26]), c(e[27]), c(e[28]), c(e[29]), c(e[30]), c(e[31])
template <int OFF, int ACC, int IDX>
__device__ __forceinline__ void wgmma_rs(float* d, const uint32_t* a, uint64_t d0) {
    if (!ACC) {
#pragma unroll
        for (int i = 0; i < 32; i++) d[i] = 0.f;
    }
    if (IDX < (N128 ? NRES : 9))
        asm volatile("wgmma.mma_async.sync.aligned.m64n64k16.f32.bf16.bf16 " WG_REGS ", {%32,%33,%34,%35}, %36, %37, 1, 1, 1;"
                     : WG_OPS("+f") : "r"(a[0]), "r"(a[1]), "r"(a[2]), "r"(a[3]), "l"(d0 + (OFF >> 4)), "n"(ACC));
    else
        asm volatile("{\n.reg .b64 dd;\nmov.b64 dd, {%36, 0x40000040};\nwgmma.mma_async.sync.aligned.m64n64k16.f32.bf16.bf16 " WG_REGS
                     ", {%32,%33,%34,%35}, dd, %37, 1, 1, 1;\n}\n"
                     : WG_OPS("+f") : "r"(a[0]), "r"(a[1]), "r"(a[2]), "r"(a[3]), "n"(((SB + OFF) >> 4) | (1u << 16)), "n"(ACC));
}
template <int OFF, int LBO, int ACC>
__device__ __forceinline__ void wgmma_rs2(float* d, float* e, const uint32_t* a, uint64_t d0) {
    if (!ACC) {
#pragma unroll
        for (int i = 0; i < 32; i++) d[i] = e[i] = 0.f;
    }
    asm volatile("wgmma.mma_async.sync.aligned.m64n128k16.f32.bf16.bf16 {%0,%1,%2,%3,%4,%5,%6,%7,%8,%9,%10,%11,%12,%13,%14,%15,%16,%17,%18,%19,%20,%21,%22,%23,%24,%25,%26,%27,%28,%29,%30,%31,%32,%33,%34,%35,%36,%37,%38,%39,%40,%41,%42,%43,%44,%45,%46,%47,%48,%49,%50,%51,%52,%53,%54,%55,%56,%57,%58,%59,%60,%61,%62,%63}, {%64,%65,%66,%67}, %68, %69, 1, 1, 1;"
                 : WG_OPS("+f"), WG_OPSE("+f") : "r"(a[0]), "r"(a[1]), "r"(a[2]), "r"(a[3]), "l"(d0 + (OFF >> 4) + ((LBO / 16 - 1) << 16)), "n"(ACC));
}
template <int G>
__device__ __forceinline__ void wgmma_group(float* P, float* W, const uint32_t* h, const uint32_t* rf, uint64_t d0) {
    wgmma_rs<W2_OFF + 8192 * G, 0, 5 * G>(P, h, d0);
    wgmma_rs<W2_OFF + 8192 * G + 2048, 1, 5 * G + 1>(P, h + 4, d0);
    wgmma_rs<W2_OFF + 8192 * G + 4096, 1, 5 * G + 2>(P, h + 8, d0);
    wgmma_rs<W2_OFF + 8192 * G + 6144, 1, 5 * G + 3>(P, h + 12, d0);
    wgmma_rs<WR_OFF + 2048 * G, 0, 5 * G + 4>(W, rf, d0);
}
__device__ __forceinline__ void wgmma_ss_k64(float* d, uint64_t da, uint64_t db) {
#pragma unroll
    for (int i = 0; i < 32; i++) d[i] = 0.f;
    asm volatile("wgmma.mma_async.sync.aligned.m64n64k16.f32.bf16.bf16 " WG_REGS ", %32, %33, 0, 1, 1, 0, 1;" : WG_OPS("+f") : "l"(da), "l"(db));
#pragma unroll
    for (int k = 1; k < 4; k++)
        asm volatile("wgmma.mma_async.sync.aligned.m64n64k16.f32.bf16.bf16 " WG_REGS ", %32, %33, 1, 1, 1, 0, 1;"
                     : WG_OPS("+f") : "l"(da + 2 * k), "l"(db + 128 * k));
}
__device__ __forceinline__ void fence_regs(float* d) { asm volatile("" : WG_OPS("+f")::"memory"); }
__device__ __forceinline__ uint32_t qaxis(float x) {
    const float u = fmaf(x, QINVP, 0.25f);
    const float f = u - ((u + 12582912.f) - 12582912.f);
    return __float_as_uint(fmaf(fabsf(f), 510.f, 12582912.f));
}
__device__ __forceinline__ uint32_t qcode(float x, float y, float z, uint32_t tx) {
    return __byte_perm(__byte_perm(qaxis(x), qaxis(y), 0x3340), qaxis(z), 0x3410) ^ tx;
}
__device__ __forceinline__ bool near_test(uint32_t ca, uint32_t cb, uint32_t tag24) {
    const uint32_t D = __vabsdiffu4(ca, cb);
    return __dp4a(D, D, 0u) <= QTHRESH || ((ca ^ tag24) | (cb ^ tag24)) >= 0x1000000u;
}
constexpr float QMAX = 23.9375f;
__device__ __forceinline__ float square(uint32_t rxy, uint32_t rz) {
    const uint32_t qxy = hmul2(rxy, rxy), qz = hmul2(rz, rz);
    return bf_lo(qxy) + bf_hi(qxy) + bf_lo(qz);
}

__device__ __forceinline__ uint32_t lds32(uint32_t addr) {
    uint32_t r;
    asm volatile("ld.shared.u32 %0, [%1];" : "=r"(r) : "r"(addr) : "memory");
    return r;
}
__device__ __forceinline__ void sts32_if(uint32_t addr, uint32_t v, bool c) {
    asm volatile("{\n.reg .pred p;\nsetp.ne.u32 p, %2, 0;\n@p st.shared.u32 [%0], %1;\n}\n" ::"r"(addr), "r"(v), "r"((uint32_t)c) : "memory");
}
__device__ __forceinline__ uint32_t sel(bool c, uint32_t a, uint32_t b) {
    uint32_t r;
    asm("{\n.reg .pred p;\nsetp.ne.u32 p, %3, 0;\nselp.b32 %0, %1, %2, p;\n}\n" : "=r"(r) : "r"(a), "r"(b), "r"((uint32_t)c));
    return r;
}
__device__ __forceinline__ uint32_t lds16(uint32_t addr) {
    uint32_t r;
    asm volatile("ld.shared.u16 %0, [%1];" : "=r"(r) : "r"(addr) : "memory");
    return r;
}
__device__ __forceinline__ void sts16_if(uint32_t addr, uint32_t v, bool c) {
    asm volatile("{\n.reg .pred p;\nsetp.ne.u32 p, %2, 0;\n@p st.shared.u16 [%0], %1;\n}\n" ::"r"(addr), "h"((unsigned short)v), "r"((uint32_t)c) : "memory");
}
__device__ __forceinline__ void sts64_if(uint32_t addr, uint32_t x, uint32_t y, bool c) {
    asm volatile("{\n.reg .pred p;\nsetp.ne.u32 p, %3, 0;\n@p st.shared.v2.u32 [%0], {%1, %2};\n}\n" ::"r"(addr), "r"(x), "r"(y), "r"((uint32_t)c) : "memory");
}
__device__ __forceinline__ uint32_t atoms_add(uint32_t addr, uint32_t v) {
    uint32_t r;
    asm volatile("atom.shared.add.u32 %0, [%1], %2;" : "=r"(r) : "r"(addr), "r"(v) : "memory");
    return r;
}
__device__ __forceinline__ void stg128_if(void* ptr, uint4 v, bool c) {
    asm volatile("{\n.reg .pred p;\nsetp.ne.u32 p, %5, 0;\n@p st.relaxed.gpu.global.v4.u32 [%0], {%1,%2,%3,%4};\n}\n"
                 ::"l"(ptr), "r"(v.x), "r"(v.y), "r"(v.z), "r"(v.w), "r"((uint32_t)c) : "memory");
}
__device__ __forceinline__ void lds128(uint32_t addr, uint32_t* r) {
    asm volatile("ld.shared.v4.u32 {%0,%1,%2,%3}, [%4];" : "=r"(r[0]), "=r"(r[1]), "=r"(r[2]), "=r"(r[3]) : "r"(addr) : "memory");
}
__device__ __forceinline__ void stg2_if(uint64_t ptr, const uint32_t* r, uint32_t c) {
    asm volatile("{\n.reg .pred p;\nsetp.ne.u32 p, %9, 0;\n@p st.global" STP ".v4.u32 [%8], {%0,%1,%2,%3};\n"
                 "@p st.global" STP ".v4.u32 [%8 + 64], {%4,%5,%6,%7};\n}\n"
                 ::"r"(r[0]), "r"(r[1]), "r"(r[2]), "r"(r[3]), "r"(r[4]), "r"(r[5]), "r"(r[6]), "r"(r[7]), "l"(ptr), "r"(c) : "memory");
}
__device__ __forceinline__ void gather_s(uint32_t dst, const char* base, uint32_t src) {
    asm volatile("{\n.reg .pred p;\nsetp.eq.u32 p, %2, 0xFFFF;\ncp.async.cg.shared.global [%0], [%1], 16, p;\n}\n"
                 ::"r"(dst), "l"(base + (size_t)src * 512), "r"(src) : "memory");
}
__device__ __forceinline__ void gather_v(uint32_t dst, const char* base, uint32_t src) {
    asm volatile("{\n.reg .pred p;\nsetp.eq.u32 p, %2, 0xFFFF;\n"
                 "cp.async.cg.shared.global [%0 + 1024], [%1 + 128], 16, p;\ncp.async.cg.shared.global [%0 + 2048], [%1 + 256], 16, p;\n"
                 "cp.async.cg.shared.global [%0 + 3072], [%1 + 384], 16, p;\n}\n" ::"r"(dst), "l"(base + (size_t)src * 512), "r"(src) : "memory");
}
__device__ __forceinline__ void gather_row_if(uint32_t dst, const char* src, uint32_t c) {
    asm volatile("{\n.reg .pred p;\nsetp.ne.u32 p, %2, 0;\n@p cp.async.cg.shared.global [%0], [%1], 16;\n"
                 "@p cp.async.cg.shared.global [%0 + 1024], [%1 + 128], 16;\n@p cp.async.cg.shared.global [%0 + 2048], [%1 + 256], 16;\n"
                 "@p cp.async.cg.shared.global [%0 + 3072], [%1 + 384], 16;\n}\n" ::"r"(dst), "l"(src), "r"(c) : "memory");
}
__device__ __forceinline__ void lds2_if(uint32_t a0, uint32_t a1, uint32_t* r, uint32_t c) {
    asm volatile("{\n.reg .pred p;\nsetp.ne.u32 p, %10, 0;\n@p ld.shared.v4.u32 {%0,%1,%2,%3}, [%8];\n@p ld.shared.v4.u32 {%4,%5,%6,%7}, [%9];\n}\n"
                 : "+r"(r[0]), "+r"(r[1]), "+r"(r[2]), "+r"(r[3]), "+r"(r[4]), "+r"(r[5]), "+r"(r[6]), "+r"(r[7])
                 : "r"(a0), "r"(a1), "r"(c) : "memory");
}
__device__ __forceinline__ int fresh_lane() {
    int l;
    asm volatile("mov.u32 %0, %%laneid;" : "=r"(l));
    return l;
}

__device__ __forceinline__ void cold_edges(unsigned char* smem, const Params& p, int lo, int hi, uint32_t tag) {
#pragma unroll 1
    for (int e = lo + threadIdx.x; e < hi; e += THREADS) {
        const int s = p.src[e], d = p.dst[e];
        if (near_test(reinterpret_cast<const uint32_t*>(smem)[s], reinterpret_cast<const uint32_t*>(smem)[d], tag << 24)) {
            const uint32_t own = __umulhi((uint32_t)d, p.magic);
            const uint32_t slot4 = atomicAdd(reinterpret_cast<uint32_t*>(smem + SCNT_OFF) + own, 4u);
            uint32_t* line = reinterpret_cast<uint32_t*>(smem + STAGE_OFF) + own * (PITCH / 4);
            if (slot4 < 124) {
                line[slot4 >> 2] = ((uint32_t)s << 15) + ((uint32_t)(d - own * p.NPC) << 6) + tag;
            } else {
                uint32_t o = atomicAdd(reinterpret_cast<uint32_t*>(smem + MISC_OFF) + 16, 1u);
                p.g->ovf[(size_t)blockIdx.x * (4 * p.gpc + 4) + o] = make_int2(s, d);
                line[31] = (PAY_MARK << 6) | tag;
            }
        }
    }
}
__device__ __forceinline__ void cold_filter(unsigned char* smem, const Params& p, int e0, int e1, uint32_t tag, int redo) {
    if (redo) {
        if (threadIdx.x < MAXG) reinterpret_cast<uint32_t*>(smem + SCNT_OFF)[threadIdx.x] = 0;
        __syncthreads();
    }
    cold_edges(smem, p, redo ? 4 * e0 : 4 * (e0 + 3 * THREADS), 4 * e1, tag);
    if (blockIdx.x == 0) cold_edges(smem, p, p.E & ~3, p.E, tag);
    __syncthreads();
    if (threadIdx.x == 0) p.g->ovfcnt[blockIdx.x] = reinterpret_cast<uint32_t*>(smem + MISC_OFF)[16];
    __threadfence();
    __syncthreads();
}
__device__ __forceinline__ float distance(float q) {
    float d;
    asm("sqrt.approx.ftz.f32 %0, %1;" : "=f"(d) : "f"(rbf16(rbf16(q) + 1e-8f)));
    return rbf16(d);
}
__device__ __forceinline__ float fcut(float d) {
    return d < 5.0f ? 0.5f * rbf16(rbf16(__cosf(rbf16(rbf16(3.14159265358979f * d) * 0.2f))) + 1.0f) : 0.f;
}
__device__ __forceinline__ uint4 basis8(float d, uint4 f) {
    const float sc = __fdividef(fcut(d), d);
    const uint32_t dd = __byte_perm(__float_as_uint(d), 0, 0x3232);
    uint32_t x[4] = {hmul2(f.x, dd), hmul2(f.y, dd), hmul2(f.z, dd), hmul2(f.w, dd)};
#pragma unroll
    for (int i = 0; i < 4; i++) x[i] = pack2(__sinf(bf_lo(x[i])) * sc, __sinf(bf_hi(x[i])) * sc);
    return make_uint4(x[0], x[1], x[2], x[3]);
}
__device__ __forceinline__ void cold_nodes(unsigned char* smem, const Params& p, int nn, uint32_t tag) {
    float* acc = reinterpret_cast<float*>(smem + RING_OFF);
    const int nbase = blockIdx.x * p.NPC, lane = threadIdx.x & 31;
    const uint32_t* sv = reinterpret_cast<const uint32_t*>(p.sv);
    const volatile uint32_t* xin = reinterpret_cast<const uint32_t*>(p.g->xbuf) + blockIdx.x * p.G * 32;
#pragma unroll 1
    for (int i = threadIdx.x; i < p.G * 32; i += THREADS) {
        if (xin[(i & ~31) + 15] < (PAY_MARK << 6)) {
            uint32_t w;
            int it = 0;
            do {
                w = xin[i];
                if (++it > (1 << 22)) __trap();
            } while ((w ^ tag) & 63u);
            if ((w >> 6) == PAY_MARK) smem[OVL_OFF + atomicAdd(reinterpret_cast<uint32_t*>(smem + MISC_OFF) + 17, 1u)] = (unsigned char)(i >> 5);
        }
    }
    __threadfence();
    __syncthreads();
    const int nmark = reinterpret_cast<uint32_t*>(smem + MISC_OFF)[17];
#pragma unroll 1
    for (int c0 = 0; c0 < nn; c0 += 128) {
        __syncthreads();
#pragma unroll 1
        for (int i = threadIdx.x; i < 128 * 256; i += THREADS) acc[i] = 0.f;
        __syncthreads();
#pragma unroll 1
        for (int m = -1; m < nmark; m++) {
            const int pr = m < 0 ? 0 : smem[OVL_OFF + m];
            const int cnt = m < 0 ? p.G * 32 : __ldcg(&p.g->ovfcnt[pr]);
#pragma unroll 1
            for (int i = threadIdx.x; i - lane < cnt; i += THREADS) {
                int2 e = make_int2(0, -1);
                if (i < cnt) {
                    if (m < 0) {
                        const uint32_t w = xin[i];
                        if (((w ^ tag) & 63u) == 0) e = make_int2(w >> 15, (w >> 6) & 511u);
                    } else {
                        e = __ldcg(p.g->ovf + (size_t)pr * (4 * p.gpc + 4) + i);
                        e.y -= nbase;
                    }
                }
                uint32_t rxy = 0, rz = 0;
                bool in = e.y >= c0 && e.y < min(c0 + 128, nn);
                if (in) {
                    const uint2 ps = __ldcg(p.g->pos8 + e.x), pd = __ldcg(p.g->pos8 + nbase + e.y);
                    rxy = hsub2(ps.x, pd.x);
                    rz = hsub2(ps.y, pd.y);
                    in = square(rxy, rz) < QMAX;
                }
#pragma unroll 1
                for (uint32_t todo = __ballot_sync(0xffffffffu, in); todo; todo &= todo - 1) {
                    const int l = __ffs(todo) - 1;
                    const uint32_t* row = sv + (size_t)__shfl_sync(0xffffffffu, e.x, l) * 128 + lane;
                    float* o = acc + (__shfl_sync(0xffffffffu, e.y, l) - c0) * 256 + 2 * lane;
                    const uint32_t xy = __shfl_sync(0xffffffffu, rxy, l), z = __shfl_sync(0xffffffffu, rz, l);
                    const float d = distance(square(xy, z)), fc = fcut(d);
                    uint32_t x = __ldg(row);
                    float y0 = 0.f, y1 = 0.f, m2[6];
#pragma unroll 4
                    for (int k = 0; k < 64; k++) {
                        const uint32_t u = __shfl_sync(0xffffffffu, x, k >> 1), w = __ldg(reinterpret_cast<const uint32_t*>(p.w1) + k * 32 + lane);
                        const float a = k & 1 ? bf_hi(u) : bf_lo(u);
                        y0 = fmaf(a, bf_lo(w), y0);
                        y1 = fmaf(a, bf_hi(w), y1);
                    }
                    y0 = rbf16(y0); y1 = rbf16(y1);
                    x = pack2(y0 / (1.f + __expf(-y0)), y1 / (1.f + __expf(-y1)));
                    const float rb = rbf16(rbf16(__sinf(rbf16(d * __bfloat162float(p.freqs[lane & 15])))) / d);
#pragma unroll
                    for (int g = 0; g < 3; g++) {
                        float p0 = 0.f, p1 = 0.f, w0 = 0.f, w1 = 0.f;
#pragma unroll 4
                        for (int k = 0; k < 64; k++) {
                            const uint32_t u = __shfl_sync(0xffffffffu, x, k >> 1), w = __ldg(reinterpret_cast<const uint32_t*>(p.w2) + k * 96 + g * 32 + lane);
                            const float a = k & 1 ? bf_hi(u) : bf_lo(u);
                            p0 = fmaf(a, bf_lo(w), p0);
                            p1 = fmaf(a, bf_hi(w), p1);
                        }
#pragma unroll 4
                        for (int k = 0; k < 16; k++) {
                            const uint32_t w = __ldg(reinterpret_cast<const uint32_t*>(p.wr) + k * 96 + g * 32 + lane);
                            const float a = __shfl_sync(0xffffffffu, rb, k);
                            w0 = fmaf(a, bf_lo(w), w0);
                            w1 = fmaf(a, bf_hi(w), w1);
                        }
                        m2[2 * g] = rbf16(rbf16(p0) * rbf16(rbf16(w0) * fc));
                        m2[2 * g + 1] = rbf16(rbf16(p1) * rbf16(rbf16(w1) * fc));
                    }
                    atomicAdd(o, m2[0]);
                    atomicAdd(o + 1, m2[1]);
#pragma unroll
                    for (int k = 1; k < 4; k++) {
                        const uint32_t v = __ldg(row + 32 * k);
                        const float rh = rbf16((k == 1 ? bf_lo(xy) : k == 2 ? bf_hi(xy) : bf_lo(z)) / d);
                        atomicAdd(o + 64 * k, fmaf(m2[2], bf_lo(v), m2[4] * rh));
                        atomicAdd(o + 64 * k + 1, fmaf(m2[3], bf_hi(v), m2[5] * rh));
                    }
                }
            }
        }
        __syncthreads();
#pragma unroll 1
        for (int i = threadIdx.x; i < min(128, nn - c0) * 128; i += THREADS) {
            const uint32_t v = __ldg(sv + (size_t)(nbase + c0) * 128 + i);
            reinterpret_cast<uint32_t*>(p.out)[(size_t)(nbase + c0) * 128 + i] = pack2(bf_lo(v) + rbf16(acc[2 * i]), bf_hi(v) + rbf16(acc[2 * i + 1]));
        }
    }
}

template <int CN, int CE, int CG>
__global__ void __launch_bounds__(THREADS, 1) painn_kernel(const __grid_constant__ Params p) {
    extern __shared__ __align__(1024) unsigned char smem_dyn[];
    unsigned char* const smem = static_cast<unsigned char*>(__cvta_shared_to_generic(SB));
    constexpr uint32_t sb = SB;
    const int tid = threadIdx.x, lane = tid & 31;
    const int warp = __shfl_sync(0xffffffffu, tid >> 5, 0);
    constexpr int CNPC = CG ? (CN + CG - 1) / CG : 1, CGPC = CG ? (CE / 4 + CG - 1) / CG : 1;
    const int b = blockIdx.x, G = CG ? CG : p.G, NPC = CG ? CNPC : p.NPC, N = CG ? CN : p.N, gpc = CG ? CGPC : p.gpc;
    const uint32_t magic = CG ? (uint32_t)(((1ull << 32) + CNPC - 1) / CNPC) : p.magic;
    const bool odd_edges = CG ? (CE & 3) != 0 || CGPC > 3 * THREADS : p.odd_edges;
    const int nbase = b * NPC, nn = min(NPC, N - nbase);
    const int e0 = b * gpc, e1 = min((CG ? CE : p.E) >> 2, e0 + gpc);

    uint4* stage4 = reinterpret_cast<uint4*>(smem + STAGE_OFF);
    uint32_t* ncnt = reinterpret_cast<uint32_t*>(smem + NCNT_OFF);
    uint32_t* misc = reinterpret_cast<uint32_t*>(smem + MISC_OFF);
    const uint32_t bar_full = sb + BAR_OFF + (warp & 7) * 40, bar_empty = bar_full + 16, bar_side = bar_full + 32, bar_tab = sb + BAR_OFF + 336;

    auto warm = [&](int first, int n, int pause) {
#pragma unroll 1
        for (int i = first; i < first + n; i++) {
            if (elect())
                asm volatile("cp.async.bulk.tensor.2d.shared::cluster.global.mbarrier::complete_tx::bytes [%0], [%1, {0, %3}], [%2];"
                             ::"r"(sb + SINK_OFF), "l"(&p.tm), "r"(bar_tab + 8), "r"(nbase * 4 + i * 32) : "memory");
            if (pause) { const uint32_t t0 = clock(); while (clock() - t0 < (uint32_t)pause) {} }
        }
    };
    TS0(0);
    int4 es[3], ed[3];
    auto load_edges = [&](int i) {
        const int g = min(e0 + tid + i * THREADS, e1 - 1);
        asm volatile("ld.global" EP ".v4.u32 {%0,%1,%2,%3}, [%8];\nld.global" EP ".v4.u32 {%4,%5,%6,%7}, [%9];"
                     : "=r"(es[i].x), "=r"(es[i].y), "=r"(es[i].z), "=r"(es[i].w), "=r"(ed[i].x), "=r"(ed[i].y), "=r"(ed[i].z), "=r"(ed[i].w)
                     : "l"(reinterpret_cast<const int4*>(p.src) + g), "l"(reinterpret_cast<const int4*>(p.dst) + g) : "memory");
    };
    unsigned epoch;
    const uint32_t tbytes = ((N + 3) >> 2) * 16;
    {
        uint32_t pxy, pz;
        asm volatile("ld.global.nc.u32 %0, [%3];\nld.global.nc.u32 %1, [%3 + 4];\nld.global.ca.u32 %2, [%4];"
                     : "=r"(pxy), "=r"(pz), "=r"(epoch)
                     : "l"(reinterpret_cast<const uint32_t*>(p.pos) + ((nbase + min(tid, nn - 1)) * 3 >> 1)), "l"(p.g->sync) : "memory");
        const uint32_t sh = ((nbase + tid) & 1) << 4;
        pxy = __funnelshift_r(pxy, pz, sh);
        pz >>= sh;
        if (tid < nn) {
            reinterpret_cast<uint32_t*>(p.g->table)[nbase + tid] = qcode(bf_lo(pxy), bf_hi(pxy), bf_lo(pz), ((epoch & 31u) ^ 0x6Bu) << 24);
            p.g->pos8[nbase + tid] = make_uint2(pxy, pz);
        }
        reinterpret_cast<uint2*>(smem + OPOS_OFF)[tid] = make_uint2(pxy, pz);
        if (pxy == 0xFFFFFFFFu && pz == 0xFFFFFFFFu && epoch == 0xFFFFFFFFu) asm volatile("nanosleep.u32 0;");
        load_edges(0);
    }
    __syncthreads();
    const uint32_t tag = (epoch & 31u) | 32u;
    if (warp == 15) {
        if (elect()) {
            asm volatile("red.relaxed.gpu.global.add.u32 [%0], 1;" ::"l"(p.g->sync + 1) : "memory");
            asm volatile("prefetch.tensormap [%0];" ::"l"(&p.tm) : "memory");
            mbar_init(bar_tab, 1);
            mbar_init(bar_tab + 8, 1);
                        mbar_expect_tx(bar_tab, tbytes);
            mbar_expect_tx(bar_tab + 8, (WA + WC + WE + WX) * 512);
        }
        TSX(1, 511);
        const unsigned want = (epoch + 1) * G;
        unsigned c;
        int it = smem_u32(smem_dyn) == SB ? 0 : 1 << 22;
        do {
            asm volatile("ld.relaxed.gpu.global.u32 %0, [%1];" : "=r"(c) : "l"(p.g->sync + 1) : "memory");
            if (++it > (1 << 22)) __trap();
        } while (c != want);
        __syncwarp();
        if (lane < TSPLIT) {
            const uint32_t part = (tbytes / TSPLIT) & ~127u, i = (lane + (TROT ? b : 0)) % TSPLIT;
            bulk_g2s(sb + i * part, reinterpret_cast<const char*>(p.g->table) + i * part, i == TSPLIT - 1 ? tbytes - i * part : part, bar_tab);
        }
        TSX(2, 511);
    }
    if (warp == 14) {
#pragma unroll 1
        for (int c = b * 32 + lane; c < WIMG / 16 + LUTS * 2; c += G * 32) {
            const int row = c >> 3, j = (c ^ row) & 7;
            uint4 v;
            if (c < 512) {
                const uint32_t half = 0x3F003F00u;
                v = __ldg(reinterpret_cast<const uint4*>(p.w1) + row * 8 + j);
                v = make_uint4(hmul2(v.x, half), hmul2(v.y, half), hmul2(v.z, half), hmul2(v.w, half));
            } else if (c >= WIMG / 16) {
                v = basis8(__uint_as_float((0x409D - ((c - WIMG / 16) >> 1)) << 16), __ldg(reinterpret_cast<const uint4*>(p.freqs) + (c & 1)));
            } else {
                const uint32_t* q = (c < 2048 ? reinterpret_cast<const uint32_t*>(p.w2) + (row & 63) * 96 + ((row >> 6) - 1) * 32
                                              : reinterpret_cast<const uint32_t*>(p.wr) + (row & 15) * 96 + ((row >> 4) - 16) * 32) + (j & 4) * 4 + (j & 3);
                v = make_uint4(__ldg(q), __ldg(q + 4), __ldg(q + 8), __ldg(q + 12));
            }
            p.g->wimg[c] = v;
        }
    }
    if (warp < 8 && elect()) {
        mbar_init(bar_full, 32); mbar_init(bar_full + 8, 32);
        mbar_init(bar_empty, 1);
        mbar_init(bar_side, 32);
        mbar_init(bar_full + 24, 1);
    }
    if (tid < MAXG) reinterpret_cast<uint32_t*>(smem + SCNT_OFF)[tid] = 0;
    if (tid < 48) misc[tid] = 0;
    {
        const uint32_t inv = (PAY_INVALID << 6) | tag;
        stage4[tid] = stage4[tid + THREADS] = make_uint4(inv, inv, inv, inv);
        if (tid < MAXG * (PITCH / 16) - 2 * THREADS) stage4[tid + 2 * THREADS] = make_uint4(inv, inv, inv, inv);
    }
    __syncthreads();
    {
    uint4* const xout = p.g->xbuf + ((tid >> 3) * G + b) * 8 + (tid & 7);
#pragma unroll
    for (int i = 0; i < 3; i++) stg128_if(xout + i * G * THREADS, make_uint4(0, 0, 0, 0), tid + i * THREADS < G * 8);
    }
    if (ED1) __nanosleep(ED1);
    load_edges(1);
    if (ED2 > 0) __nanosleep(ED2);
    if (ED2 >= 0) load_edges(2);
    if (tid == THREADS - 1) asm volatile("fence.acq_rel.gpu;" ::: "memory");
    mbar_wait(bar_tab, 0);
    TS0(3);
    if (ED2 < 0) load_edges(2);
    if (warp == 15) {
        warm(0, WA, 0);
        if (WH && WHE && elect()) asm volatile("cp.async.bulk.prefetch.L2.global [%0], %1;" ::"l"(p.sv + (size_t)(nbase + WH0) * 256), "r"(max(min(WH, nn - WH0), 1) * 512) : "memory");
    }

#pragma unroll 1
    for (int i = 0, g = e0 + tid; i < 3; i++, g += THREADS) {
        const int s[4] = {es[0].x, es[0].y, es[0].z, es[0].w}, d[4] = {ed[0].x, ed[0].y, ed[0].z, ed[0].w};
        uint32_t ca[4], cb[4], own[4], sl[4];
        bool c[4];
#pragma unroll
        for (int j = 0; j < 4; j++) { ca[j] = lds32(sb + 4 * s[j]); cb[j] = lds32(sb + 4 * d[j]); }
#pragma unroll
        for (int j = 0; j < 4; j++) {
            c[j] = near_test(ca[j], cb[j], tag << 24) && g < e1;
            own[j] = __umulhi((uint32_t)d[j], magic);
            sl[j] = atomicAdd(reinterpret_cast<uint32_t*>(smem + SCNT_OFF) + (c[j] ? own[j] : MAXG + lane), 4u);
        }
#pragma unroll
        for (int j = 0; j < 4; j++)
            sts32_if(sb + STAGE_OFF + own[j] * PITCH + sl[j], own[j] * (uint32_t)(-64 * NPC) + (((uint32_t)s[j] << 15) + (((uint32_t)d[j] << 6) + tag)),
                     c[j] && sl[j] < 124);
        es[0] = es[1]; es[1] = es[2];
        ed[0] = ed[1]; ed[1] = ed[2];
    }
    __syncthreads();
    {
        const int redo = __syncthreads_or(tid < MAXG && reinterpret_cast<uint32_t*>(smem + SCNT_OFF)[tid] > 124);
        if (__builtin_expect(redo || odd_edges, 0)) cold_filter(smem, p, e0, e1, tag, redo);
    }
    TS0(4);
#pragma unroll
    for (int i = 0; i < 2; i++) {
        const int r = min((tid >> 2) + i * (THREADS / 4), G), c = r * (PITCH / 16) + (tid & 3);
        uint4* const x = p.g->xbuf + (r * G + b) * 8 + (tid & 3);
        stg128_if(x, stage4[c], r < G);
        if (__builtin_expect(reinterpret_cast<uint32_t*>(smem + SCNT_OFF)[r] >= 64 && r < G, 0)) stg128_if(x + 4, stage4[c + 4], true);
    }
    ncnt[tid] = 0;
    if (tid < 480) reinterpret_cast<uint32_t*>(smem + SLOT_OFF)[tid] = tid < 32 ? tid * 0x100010 + 0x80000 : tid < 320 ? ~0u : 0u;
    if (tid == 511) reinterpret_cast<uint2*>(smem + NPOS_OFF)[511] = make_uint2(sb + SLOT_OFF + 1278, 0);
    __syncthreads();
    reinterpret_cast<uint4*>(smem + RR_OFF)[tid] = make_uint4(0, 0, 0, 0);
    if (tid < ROUNDS * 80 - THREADS) reinterpret_cast<uint4*>(smem + RR_OFF)[tid + THREADS] = make_uint4(0, 0, 0, 0);
    if (tid < ROUNDS * 32) reinterpret_cast<uint2*>(smem + SRC_OFF)[tid] = make_uint2(~0u, ~0u);
    __nanosleep(PDELAY);
    TS0(5);

    uint32_t rxy[4], gz[4], src[4], rk[4], dn[4];
    const uint32_t sink = sb + NCNT_OFF + 4 * (480 + lane);
    if (warp < 15) {
        uint32_t ew[3][4], bad[2];
        const int u = tid - 3 * G;
        const uint4* const xin = p.g->xbuf + b * G * 8;
        const uint4* cp = xin + (u < 0 ? tid + tid / 3 * 5 : u * 8 + 3);
        bad[0] = u < G;
        bad[1] = u >= 0 && u + 480 - 3 * G < G;
#pragma unroll
        for (int i = 0; i < 3; i++) ew[i][0] = ew[i][1] = ew[i][2] = ew[i][3] = (PAY_INVALID << 6) | tag;
        int it = 0;
#pragma unroll 1
        do {
#pragma unroll
            for (int i = 0; i < 2; i++)
                asm volatile("{\n.reg .pred p;\nsetp.ne.u32 p, %5, 0;\n@p ld.relaxed.gpu.global.v4.u32 {%0,%1,%2,%3}, [%4];\n}\n"
                             : "+r"(ew[i][0]), "+r"(ew[i][1]), "+r"(ew[i][2]), "+r"(ew[i][3]) : "l"(cp + i * (480 - 3 * G) * 8), "r"(bad[i]) : "memory");
#pragma unroll
            for (int i = 0; i < 2; i++) bad[i] = ((ew[i][0] ^ tag) | (ew[i][1] ^ tag) | (ew[i][2] ^ tag) | (ew[i][3] ^ tag)) & 63u;
            if (++it > (1 << 22)) __trap();
        } while (__any_sync(0xffffffffu, bad[0] | bad[1]));
        if (warp >= (3 * G) >> 5) {
            const uint32_t f0 = __ballot_sync(0xffffffffu, u >= 0 && ew[0][3] < (PAY_MARK << 6)), f1 = __ballot_sync(0xffffffffu, ew[1][3] < (PAY_MARK << 6));
            if (__builtin_expect(f0 | f1, 0)) {
                uint64_t f = (uint64_t)f1 << 32 | f0;
#pragma unroll 1
                for (int k = 7 - (lane >> 2); k; k--) f &= f - 1;
                if (f) {
                    const int l = __ffsll(f) - 1;
                    do {
                        asm volatile("ld.relaxed.gpu.global.v4.u32 {%0,%1,%2,%3}, [%4];" : "=r"(ew[2][0]), "=r"(ew[2][1]), "=r"(ew[2][2]), "=r"(ew[2][3])
                                     : "l"(xin + (u - lane + l + (l >> 5) * (448 - 3 * G)) * 8 + 4 + (lane & 3)) : "memory");
                        if (++it > (1 << 22)) __trap();
                    } while (((ew[2][0] ^ tag) | (ew[2][1] ^ tag) | (ew[2][2] ^ tag) | (ew[2][3] ^ tag)) & 63u);
                    if ((ew[2][3] >> 6) == PAY_MARK || lane == 0) misc[0] = 1;
                }
                __syncwarp();
            }
#pragma unroll 1
            for (int i = 0; i < 2; i++) {
                if (ew[0][0] >= (PAY_MARK << 6)) {
#pragma unroll
                    for (int j = 0; j < 4; j++) { ew[0][j] = ew[1][j]; ew[1][j] = ~0u; }
                }
                uint32_t from = __ballot_sync(0xffffffffu, ew[1][0] < (PAY_MARK << 6)), to = __ballot_sync(0xffffffffu, ew[0][0] >= (PAY_MARK << 6));
#pragma unroll 1
                for (; from; from &= from - 1, to &= to - 1) {
                    if (!to) misc[0] = 1;
#pragma unroll
                    for (int j = 0; j < 4; j++) {
                        const uint32_t x = __shfl_sync(0xffffffffu, ew[1][j], __ffs(from) - 1);
                        if (lane == __ffs(to) - 1) ew[0][j] = x;
                    }
                }
#pragma unroll
                for (int j = 0; j < 4; j++) ew[1][j] = ew[2][j];
            }
        }
        {
            uint2 ps[4], pd[4];
#pragma unroll
            for (int j = 0; j < 4; j++) {
                dn[j] = (ew[0][j] >> 3) & 4088u;
                src[j] = ew[0][j] >> 15;
                ps[j] = __ldcg(p.g->pos8 + (dn[j] == 4088u ? nbase : src[j]));
            }
#pragma unroll
            for (int j = 0; j < 4; j++) pd[j] = *reinterpret_cast<const uint2*>(smem + OPOS_OFF + dn[j]);
            if (WC) asm volatile("bar.arrive 1, 512;" ::: "memory");
            float q[4];
#pragma unroll
            for (int j = 0; j < 4; j++) {
                rxy[j] = hsub2(ps[j].x, pd[j].x);
                gz[j] = hsub2(ps[j].y, pd[j].y);
                q[j] = square(rxy[j], gz[j]);
                const bool in = q[j] < QMAX && dn[j] != 4088u;
                rk[j] = atoms_add(in ? sb + NCNT_OFF + (dn[j] >> 1) : sink, 512u);
                if (!in) dn[j] = 4088u;
            }
            uint32_t row[4], n = 0;
            bool single[4];
#pragma unroll
            for (int j = 0; j < 4; j++) {
                q[j] = distance(q[j]);
                row[j] = 0x409D - (__float_as_uint(q[j]) >> 16);
                single[j] = row[j] >= LUTS && dn[j] != 4088u;
                n += single[j];
            }
            n = atoms_add(n ? sb + MISC_OFF + 4 : sink, n) + LUTS;
#pragma unroll
            for (int j = 0; j < 4; j++) {
                float id;
                asm("rcp.approx.ftz.f32 %0, %1;" : "=f"(id) : "f"(q[j]));
                sts32_if(sb + LUT_OFF + min(n, LUTN - 1) * 32, __float_as_uint(q[j]), single[j]);
                if (single[j]) row[j] = n++;
                rxy[j] = pack2(bf_lo(rxy[j]) * id, bf_hi(rxy[j]) * id);
                gz[j] = pack2(0.f, bf_lo(gz[j]) * id) + row[j] * 32;
            }
        }
    } else {
        const uint4 fq = __ldg(reinterpret_cast<const uint4*>(p.freqs) + (lane & 1));
        rxy[0] = fq.x; rxy[1] = fq.y; rxy[2] = fq.z; rxy[3] = fq.w;
        warm(WA + WC + WE, WX, WP);
        if (WH && !WHE && elect()) asm volatile("cp.async.bulk.prefetch.L2.global [%0], %1;" ::"l"(p.sv + (size_t)(nbase + WH0) * 256), "r"(max(min(WH, nn - WH0), 1) * 512) : "memory");
        if (WC) asm volatile("bar.sync 1, 512;" ::: "memory");
        warm(WA, WC, 0);
    }
    __syncthreads();
    TS0(6);

    const uint32_t lt = (1u << lane) - 1;
    uint32_t place = ~0u, mid = 0, last = 0, steps = 0, c = 0;
    if (warp < 15) {
        if (tid < nn) c = ncnt[tid] >> 9;
        steps = min((c + 1) >> 1, 15u);
        const uint32_t bin = sel(tid >= nn, 9, (uint32_t)(0x11223354678ull >> (4 * min(c, 11u))) & 15), sh = (bin & 1) * 16;
        const bool odd = c > 3 && (c & 1);
        const uint32_t peers = __match_any_sync(0xffffffffu, bin), om = __ballot_sync(0xffffffffu, odd);
        uint32_t x = atoms_add(lane == 0 ? sb + MISC_OFF + 4 * 37 : sink, __popc(om));
        uint32_t r = atoms_add((peers & lt) == 0 ? sb + MISC_OFF + 4 * 32 + 2 * (bin & 14) : sink, __popc(peers) << sh);
        x = __shfl_sync(0xffffffffu, x, 0) + __popc(om & lt);
        r = ((__shfl_sync(0xffffffffu, r, __ffs(peers) - 1) >> sh) & 0xFFFFu) + __popc(peers & lt);
        sts16_if(sb + sel(bin == 8, ZL_OFF, sel(bin == 7, YL_OFF, TL_OFF)) + 2 * r, tid, (0x190 >> bin) & 1);
        const uint64_t ones = 0x0001010101010101ull >> (56 - 8 * min(bin, 7u));
        asm volatile("bar.sync 2, 480;" ::: "memory");
        uint32_t h[4];
        lds128(sb + MISC_OFF + 4 * 32, h);
        const int nodd = misc[37], n1 = h[3] >> 16, n3 = h[2] & 0xFFFF, left = max(min(nodd + n3 - n1, n3), 0), half = left >> 1;
        const bool twin = bin == 4 && (int)r < 2 * half;
        x = sel(bin == 4, nodd + r - left, sel(odd, x, 1023));
        const bool pair = twin ? !(r & 1) : (int)x >= (bin == 4 ? nodd : 0) && (int)x < n1;
        const uint32_t y = lds16(sel(twin, sb + TL_OFF + 2 + 2 * r, sb + YL_OFF + 2 * (x & 511)));
        const uint32_t base = __dp2a_lo(h[0], (uint32_t)ones, __dp2a_hi(h[1], (uint32_t)ones, 0u)) +
                              __dp2a_lo(h[2], (uint32_t)(ones >> 32), __dp2a_hi(h[3], (uint32_t)(ones >> 32), 0u));
        r -= sel(bin == 7, nodd + n3, 0);
        const bool unit = (bin < 8 && (int)r >= 0 && (pair || !twin));
        place = sel(unit, base + sel(twin, r >> 1, r - sel(bin < 4, 0, half)), ~0u);
        sts32_if(sb + MISC_OFF + 16, base - half + max(n1 - nodd - n3, 0), bin >= 7);
        steps += twin;
        last = sel(twin, y, tid) | sel(steps > 1, ST_CLOSE, ST_CLOSE | ST_START);
        mid = sel(pair, y | sel(twin, ST_MID, ST_MID | ST_CLOSE) | (tid << 16), last);
        c = sel(pair, c, 2 * steps - 1);
        const uint32_t sa = sb + SLOT_OFF + sel(steps < ROUNDS, 2 * place, 1278);
        sts64_if(sb + NPOS_OFF + 8 * tid, sa, 0, unit);
        sts64_if(sb + NPOS_OFF + 8 * y, sa, c << 9, pair);
        asm volatile("{\n.reg .pred p;\nsetp.ne.u32 p, %2, 0;\n@p st.shared.u8 [%0], %1;\n}\n" ::"r"(sb + SIZE_OFF + place), "r"(steps), "r"((uint32_t)unit) : "memory");
    } else {
        if (elect()) {
            if (b == 0) p.g->sync[0] = epoch + 1;
            asm volatile("fence.proxy.async.global;" ::: "memory");
            mbar_expect_tx(bar_tab, WIMG + LUTS * 32);
            bulk_g2s(sb, p.g->wimg, WIMG, bar_tab);
            bulk_g2s(sb + LUT_OFF, p.g->wimg + WIMG / 16, LUTS * 32, bar_tab);
        }
        warm(WA + WC, WE, 0);
#pragma unroll 1
        for (uint32_t i = lane; i - lane < 2 * min(misc[1], LUTN - LUTS); i += 32) {
            const uint32_t d = lds32(sb + LUT_OFF + (LUTS + (i >> 1)) * 32);
            __syncwarp();
            reinterpret_cast<uint4*>(smem + LUT_OFF)[2 * LUTS + i] = basis8(__uint_as_float(d), make_uint4(rxy[0], rxy[1], rxy[2], rxy[3]));
        }
        TSX(12, 511);
    }
    __syncthreads();
    TS0(7);
    uint32_t st[4];
    if (warp == 15) {
        uint32_t until0 = lds16(sb + SIZE_OFF + 2 * lane), until1 = until0 >> 8, next = 64, s0, s1;
        const uint32_t nsched = misc[4];
        until0 &= 255;
        uint32_t t = __reduce_min_sync(0xffffffffu, min(until0, until1));
        bool go = true;
#pragma unroll 1
        while (go) {
            go = t < ROUNDS && next < nsched;
            const bool n0 = until0 == t, n1 = until1 == t;
            const uint32_t i = next + __popc(__ballot_sync(0xffffffffu, n0) & lt) + __popc(__ballot_sync(0xffffffffu, n1) & lt), j = i + n0;
            next += __reduce_add_sync(0xffffffffu, n0 + n1);
            asm volatile("{\n.reg .pred p, q;\nsetp.ne.u32 p, %4, 0;\nsetp.ne.u32 q, %5, 0;\nmov.u32 %0, 0;\nmov.u32 %1, 0;\n@p ld.shared.u8 %0, [%2];\n@q ld.shared.u8 %1, [%3];\n}\n"
                         : "=&r"(s0), "=&r"(s1) : "r"(sb + SIZE_OFF + i), "r"(sb + SIZE_OFF + j), "r"((uint32_t)n0), "r"((uint32_t)n1) : "memory");
            sts16_if(sb + SLOT_OFF + 2 * i, 1024 * t + 16 * lane, n0);
            sts16_if(sb + SLOT_OFF + 2 * j, 1024 * t + 16 * lane + 8, n1);
            until0 += s0;
            until1 += s1;
            t++;
        }
        until0 = __reduce_max_sync(lane < 16 ? 0xFFFFu : 0xFFFF0000u, max(until0, until1));
        if ((lane & 15) == 0) misc[2 + (lane >> 4)] = until0;
        __syncthreads();
        lds128(sb + MISC_OFF, st);
    } else {
#pragma unroll
        for (int j = 0; j < 4; j++) {
            const uint2 np = *reinterpret_cast<const uint2*>(smem + NPOS_OFF + dn[j]);
            dn[j] = np.x;
            rk[j] += np.y;
        }
#pragma unroll 1
        for (int pass = 0; pass < 2; pass++) {
            uint32_t e[4];
#pragma unroll
            for (int j = 0; j < 4; j++) e[j] = lds16(dn[j]);
            const uint32_t x = lds16(sb + SLOT_OFF + 2 * min(place, 639u));
#pragma unroll
            for (int j = 0; j < 4; j++) {
                sts16_if(sb + SRC_OFF + ((rk[j] + e[j]) >> 2), src[j], e[j] != 0xFFFFu);
                sts64_if(sb + RR_OFF + rk[j] + e[j], rxy[j], gz[j], e[j] != 0xFFFFu);
                if (e[j] != 0xFFFFu) dn[j] = sb + SLOT_OFF + 1278;
            }
            if (pass) {
                const uint32_t nd = sb + ND_OFF + ((x >> 2) & 0xFF00) + ((x >> 1) & 0xFC);
                sts32_if(nd, tid | ST_START, x != 0xFFFFu);
                sts32_if(nd + steps * 256 - 256, last, x != 0xFFFFu && steps < ROUNDS);
                sts32_if(nd + c * 128 - 128, mid, x != 0xFFFFu && steps < ROUNDS);
                break;
            }
            asm volatile("bar.sync 2, 480;" ::: "memory");
            if (warp < 8) {
                const int s = lane >> 3, c = lane & 7;
                const uint32_t dst = sb + RING_OFF + warp * 16384 + s * 128, y = sb + SRC_OFF + (warp * 8 + s) * 2;
                const uint32_t sdst = dst + ((c ^ s) << 4), vdst = dst + ((c ^ ((s & 1) << 2)) << 4);
                const uint32_t s0 = lds16(y), s1 = lds16(y + 8), s2 = lds16(y + 128), s3 = lds16(y + 136);
                const char* svl = reinterpret_cast<const char*>(p.sv) + c * 16;
                gather_s(sdst, svl, s0);
                gather_s((sdst ^ 64) + 512, svl, s1);
                gather_s(sdst + 8192, svl, s2);
                gather_s((sdst ^ 64) + 8704, svl, s3);
                cp_async_arrive(bar_full);
                TS0(10);
                if (P0) __nanosleep(warp & 4 ? P1W : P0);
                gather_v(vdst, svl, s0);
                if (P0) __nanosleep(P0);
                gather_v(vdst + 512, svl, s1);
                if (P0) __nanosleep(P0);
                gather_v(vdst + 8192, svl, s2);
                if (P0) __nanosleep(P0);
                gather_v(vdst + 8704, svl, s3);
                asm volatile("cp.async.mbarrier.arrive.shared::cta.b64 [%0];" ::"r"(bar_side) : "memory");
            }
            __syncthreads();
            TS0(8);
            lds128(sb + MISC_OFF, st);
        }
    }
    __syncthreads();
    if (__builtin_expect(max(st[2], st[3]) >= ROUNDS || st[1] > LUTN - LUTS || st[0], 0)) {
        asm volatile("cp.async.wait_all;" ::: "memory");
        mbar_wait(bar_tab, 1);
        mbar_wait(bar_tab + 8, 0);
        cold_nodes(smem, p, nn, tag);
        return;
    }
    TS0(9);
    const int T = __shfl_sync(0xffffffffu, warp & 4 ? st[3] : st[2], 0);

    if (warp < 8) {
        asm volatile("setmaxnreg.inc.sync.aligned.u32 %0;" ::"n"(REG_C));
        const int lane = fresh_lane();
        const int g = lane >> 2, q = lane & 3;
        const uint64_t d0 = (uint64_t)__shfl_sync(0xffffffffu, pin((uint32_t)(p.desc0 >> 32)), 0) << 32 | __shfl_sync(0xffffffffu, pin((uint32_t)p.desc0), 0);
        const uint32_t swz = g * 128 + ((q ^ ((g & 1) << 2)) << 4);
        const uint32_t srow = pin(sb + SIDE_OFF + warp * 4096 + swz);
        uint32_t vrow = pin(sb + RING_OFF + warp * 16384 + swz + 4096);
        uint32_t ent = pin(sb + RR_OFF + (warp * 8 + g) * 8), fent = pin(sb + ND_OFF + (warp * 8 + g) * 4);
        uint32_t lent = pin(sb + RR_OFF + (warp * 8 + (lane & 7)) * 8 + 4 + (lane & 8) * 64);
        const uint32_t lutq = pin(sb + LUT_OFF + (lane >> 4) * 16);
        uint64_t outq;
        {
            const uint64_t a = reinterpret_cast<uint64_t>(p.out) + (size_t)nbase * 512 + q * 16;
            const uint32_t lo = pin((uint32_t)a), hi = pin((uint32_t)(a >> 32));
            asm volatile("mov.b64 %0, {%1, %2};" : "=l"(outq) : "r"(lo), "r"(hi));
        }
        uint32_t acc[32], rf[4], h[16], rr[4], fl = 0;
#pragma unroll
        for (int i = 0; i < 32; i++) asm volatile("" : "=r"(acc[i]));
#pragma unroll
        for (int i = 0; i < 16; i++) asm volatile("" : "=r"(h[i]));
#pragma unroll
        for (int i = 0; i < 4; i++) asm volatile("" : "=r"(rf[i]), "=r"(rr[i]));
        int t = -1;
        TSX(18, 0);
        mbar_wait(bar_tab, 1);
        if (warp & 4) __nanosleep(st[2] > st[3] ? STAG : STAG2);
        TSX(14, 0);
        const int Tm = __shfl_sync(0xffffffffu, min(st[2], st[3]), 0);
        if (warp >= 4 && Tm > 0) asm volatile("bar.arrive 3, 256;" ::: "memory");
        bool more = T < 0x7FFFFFFF;
#pragma unroll 1
        while (more) {
            float y[32], p1[32], w1[32], p2[32], w2[32], p3[32], w3[32];
            uint32_t m1[16], m2[16], v[3][16], ts[8];
            auto products = [](uint32_t* m, const float* P, const float* W) {
#pragma unroll
                for (int j = 0; j < 8; j++) {
                    m[j] = pack2(P[4 * j] * W[4 * j], P[4 * j + 1] * W[4 * j + 1]);
                    m[8 + j] = pack2(P[4 * j + 2] * W[4 * j + 2], P[4 * j + 3] * W[4 * j + 3]);
                }
            };
            auto vterm = [&](int k, int o) {
#pragma unroll
                for (int j = 0; j < 8; j++) acc[8 * k + 8 + j] = hfma2(m1[o + j], v[k][o + j], acc[8 * k + 8 + j]);
            };
            auto rterm = [&](int k, int o) {
#pragma unroll
                for (int j = 0; j < 8; j++)
                    acc[8 * k + 8 + j] = k == 0 ? hfma2_lo(m2[o + j], rr[o / 4], acc[8 * k + 8 + j]) : hfma2_hi(m2[o + j], rr[o / 4 + k / 2], acc[8 * k + 8 + j]);
            };
            TR(0, 0, t);
            uint64_t om, op;
#pragma unroll
            for (int j = 0; j < 8; j++) asm volatile("" : "=r"(ts[j]), "=r"(m1[8 + j]), "=r"(m2[8 + j]), "=r"(v[0][8 + j]), "=r"(v[1][8 + j]), "=r"(v[2][8 + j]));
            asm volatile("" : "=l"(om));
            if (t >= 0) {
            TC(0);
            if (t < Tm) asm volatile("bar.sync %0, 256;" ::"r"(3 + (warp >> 2)) : "memory");
            wg_fence();
            wgmma_rs2<W2_OFF + 8192, 8192, 0>(p1, p2, h, d0);
            wgmma_rs2<W2_OFF + 10240, 8192, 1>(p1, p2, h + 4, d0);
            wgmma_rs2<W2_OFF + 12288, 8192, 1>(p1, p2, h + 8, d0);
            wgmma_rs2<W2_OFF + 14336, 8192, 1>(p1, p2, h + 12, d0);
            wgmma_rs2<WR_OFF + 2048, 2048, 0>(w1, w2, rf, d0);
            wg_commit();
            TC(1);
            mbar_waitc(bar_side, t & 1);
            TC(2);
#pragma unroll
            for (int k = 0; k < 4; k++) lds2_if(srow + 1024 * k, (srow ^ 64) + 1024 * k, acc + 8 * k, fl & ST_START);
            wg_wait<N128 ? 0 : 1>();
            fence_regs(p1); fence_regs(w1);
            TC(3);
            products(m1, p1, w1);
#pragma unroll
            for (int k = 0; k < 3; k++) { lds128(vrow + 1024 + 1024 * k, v[k]); lds128((vrow ^ 64) + 1024 + 1024 * k, v[k] + 4); }
            if (!N128) wg_wait<0>();
            fence_regs(p2); fence_regs(w2);
            products(m2, p2, w2);
            asm("mad.wide.u32 %0, %1, 512, %2;" : "=l"(om) : "r"(fl >> 16), "l"(outq));
#pragma unroll
            for (int k = 0; k < 3; k++) { lds128(vrow + 9216 + 1024 * k, v[k] + 8); lds128((vrow ^ 64) + 9216 + 1024 * k, v[k] + 12); }
#pragma unroll
            for (int j = 0; j < 8; j++) asm volatile("" : "=r"(ts[j]));
            lds2_if(srow, srow ^ 64, ts, fl & ST_MID);
#pragma unroll
            for (int k = 0; k < 3; k++) { vterm(k, 0); rterm(k, 0); stg2_if(om + 128 + 128 * k, acc + 8 + 8 * k, fl & ST_MID); }
            TC(4);
            if (t + (warp >> 2) < Tm) asm volatile("bar.arrive %0, 256;" ::"r"(4 - (warp >> 2)) : "memory");
            }
            t++;
            wg_fence();
            wgmma_group<0>(p3, w3, h, rf, d0);
            wg_commit();
            if (T > 1000000) asm volatile("nanosleep.u32 0;");
#pragma unroll
            for (int k = 1; k < 4; k++) lds2_if(srow + 1024 * k, (srow ^ 64) + 1024 * k, acc + 8 * k, fl & ST_MID);
            uint32_t lo;
            asm volatile("ld.shared.u16 %0, [%1];" : "=r"(lo) : "r"(lent) : "memory");
            __syncwarp();
            if (lane == 0 && t > 0) mbar_arrive(bar_empty);
            if (t > 0) TC(5);
            if (t >= T) {
                asm("mad.wide.u32 %0, %1, 512, %2;" : "=l"(op) : "r"(fl & 511), "l"(outq));
#pragma unroll
                for (int k = 0; k < 3; k++) { vterm(k, 8); rterm(k, 8); stg2_if(op + 128 + 128 * k, acc + 8 + 8 * k, fl & ST_CLOSE); }
                wg_wait<0>();
                fence_regs(p3); fence_regs(w3);
                products(m1, p3, w3);
#pragma unroll
                for (int j = 0; j < 8; j++) acc[j] = hadd2(acc[j], m1[j]);
                stg2_if(om, acc, fl & ST_MID);
#pragma unroll
                for (int j = 0; j < 8; j++) acc[j] = hadd2(fl & ST_MID ? ts[j] : acc[j], m1[8 + j]);
                stg2_if(op, acc, fl & ST_CLOSE);
                asm volatile("cp.async.wait_all;" ::: "memory");
                break;
            }
            mbar_waitc(bar_full + 8 * (t & 1), (t >> 1) & 1);
            if (t > 0) TC(6);
            wg_fence();
            wgmma_ss_k64(y, d0 + ((RING_OFF >> 4) + (warp >> 2) * 4096 + (t & 1) * 256 + ((uint64_t)(512 - 64) << 32)), d0);
            wg_commit();
            if (T > 1000000) asm volatile("nanosleep.u32 0;");
            asm("mad.wide.u32 %0, %1, 512, %2;" : "=l"(op) : "r"(fl & 511), "l"(outq));
            vrow ^= 4096;
            if (!PEEL) more = t < T;
#pragma unroll
            for (int k = 0; k < 3; k++) vterm(k, 8);
#define BBS if (T > 1000000) asm volatile("nanosleep.u32 0;")
            auto silu = [&](int i0, int i1) {
#pragma unroll
                for (int i = i0; i < i1; i++)
                    h[i] = pack2(fmaf(y[2 * i], tanh_fast(y[2 * i]), y[2 * i]), fmaf(y[2 * i + 1], tanh_fast(y[2 * i + 1]), y[2 * i + 1]));
            };
#pragma unroll
            for (int k = 0; k < 3; k++) rterm(k, 8);
            const uint32_t fo = fl;
            asm volatile("ld.shared.v2.u32 {%0,%1}, [%4];\nld.shared.v2.u32 {%2,%3}, [%4 + 512];" : "=r"(rr[0]), "=r"(rr[1]), "=r"(rr[2]), "=r"(rr[3]) : "r"(ent) : "memory");
            asm volatile("ld.shared.u32 %0, [%1];" : "=r"(fl) : "r"(fent) : "memory");
            stg2_if(op + 128, acc + 8, fo & ST_CLOSE);
            BBS;
            if (t > 0) TC(7);
            wg_wait<0>();
            fence_regs(p3); fence_regs(w3); fence_regs(y);
            if (t > 0) TC(8);
            ldsm4(lutq + lo, rf);
            products(m1, p3, w3);
            silu(0, SPREAD == 1 ? 6 : 4);
            stg2_if(op + 256, acc + 16, fo & ST_CLOSE);
            BBS;
#pragma unroll
            for (int j = 0; j < 8; j++) acc[j] = hadd2(acc[j], m1[j]);
            stg2_if(om, acc, fo & ST_MID);
#pragma unroll
            for (int j = 0; j < 8; j++) acc[j] = hadd2(fo & ST_MID ? ts[j] : acc[j], m1[8 + j]);
            silu(SPREAD == 1 ? 6 : 4, SPREAD == 1 ? 11 : 10);
            stg2_if(op + 384, acc + 24, fo & ST_CLOSE);
            BBS;
            silu(SPREAD == 1 ? 11 : 10, SPREAD == 1 ? 16 : 14);
            if (SPREAD == 2) BBS;
            stg2_if(op, acc, fo & ST_CLOSE);
            silu(SPREAD == 1 ? 16 : 14, 16);
            ent += 1024; fent += 256; lent += 1024;
        }
        TSX(15, 0);
        TSX(16, 128);
    } else {
        asm volatile("setmaxnreg.dec.sync.aligned.u32 %0;" ::"n"(256 - REG_C));
        const int lane = fresh_lane();
        const int w = warp - 8, s = lane >> 3, c = lane & 7, nzero = misc[36] & 0xFFFF;
        uint32_t sdst = sb + RING_OFF + w * 16384 + s * 128 + ((c ^ s) << 4);
        const uint32_t sw = s * 128 + ((c ^ ((s & 1) << 2)) << 4);
        uint32_t vdst = sb + RING_OFF + w * 16384 + sw;
        const uint32_t odst = sb + SIDE_OFF + w * 4096 + sw;
        uint32_t ent = sb + ND_OFF + (w * 8 + s) * 4;
        const char* svl = reinterpret_cast<const char*>(p.sv) + c * 16;
        const char* own = svl + (size_t)nbase * 512;
        if (LAG || LAG0) __nanosleep((warp & 4 ? LAG1 : LAG0) + LAG * max(min(LAGT - (int)(misc[2] + misc[3]), LAGM), 0));
#pragma unroll 1
        for (int t = 1; t <= T; t++) {
            const uint32_t e = sb + SRC_OFF + t * 256 + (w * 8 + s) * 2;
            const uint32_t s0 = lds16(e), s1 = lds16(e + 8), s2 = lds16(e + 128), s3 = lds16(e + 136);
            const uint32_t f0 = lds32(ent), f1 = lds32(ent + 16);
            ent += 256;
            sdst ^= 4096; vdst ^= 4096;
            TR(5, 256, t);
            mbar_wait(bar_empty, t & 1);
            TR(6, 256, t);
            gather_row_if(odst, own + (f0 & 511) * 512, f0 & (ST_START | ST_MID));
            gather_row_if(odst + 512, own + (f1 & 511) * 512, f1 & (ST_START | ST_MID));
            if (!ONEB) cp_async_arrive(bar_side);
            if (PEEL && t == T) break;
            gather_s(sdst, svl, s0);
            gather_s((sdst ^ 64) + 512, svl, s1);
            gather_s(sdst + 8192, svl, s2);
            gather_s((sdst ^ 64) + 8704, svl, s3);
            cp_async_arrive(ONEB ? bar_side : bar_full + 8 * (t & 1));
            if (t < T) {
                if (PACE) __nanosleep(PACE);
                gather_v(vdst, svl, s0);
                if (PACE) __nanosleep(PACE);
                gather_v(vdst + 512, svl, s1);
                if (PACE) __nanosleep(PACE);
                gather_v(vdst + 8192, svl, s2);
                if (PACE) __nanosleep(PACE);
                gather_v(vdst + 8704, svl, s3);
            }
            TR(7, 256, t);
        }
        TSX(17, 256);
        TSX(20, 384);
        const int z0 = ZW1 ? (w & 3) + ((w >> 2) == (misc[2] > misc[3]) ? 0 : 48) : w, zs = ZW1 ? 4 : 8;
#pragma unroll 1
        for (int z = z0 + zs * lane, ph = 0; z - zs * lane < nzero; z += 96, ph ^= 1) {
            const bool on = lane < 12 && z < nzero;
            const uint32_t row = sb + RING_OFF + w * 16384 + (max(T, 1) & 1) * 4096 + 1024 + (lane + (lane < 6 ? 0 : 10)) * 512;
            const size_t o = (size_t)(nbase + lds16(sb + ZL_OFF + 2 * min(z, 511))) * 256;
            const uint32_t n = __popc(__ballot_sync(0xffffffffu, on));
            if (lane == 0) mbar_expect_tx(bar_full + 24, n * 512);
            if (on) bulk_g2s(row, p.sv + o, 512, bar_full + 24);
            TSX(21, 256);
            mbar_wait(bar_full + 24, ph);
            TSX(22, 256);
            if (on) asm volatile("{\n.reg .b64 pol;\ncreatepolicy.fractional.L2::" ZP ".b64 pol, 1.0;\n"
                                 "cp.async.bulk.global.shared::cta.bulk_group.L2::cache_hint [%0], [%1], 512, pol;\n"
                                 "cp.async.bulk.commit_group;\ncp.async.bulk.wait_group.read 0;\n}\n" ::"l"(p.out + o), "r"(row) : "memory");
            __syncwarp();
        }
        mbar_wait(bar_tab + 8, 0);
        TSX(11, 256);
        TSX(19, 384);
    }
}

}

extern "C" void kernel_launch(void* const* d_in, const int* in_sizes, int n_in, void* d_out, int out_size) {
    static int s_G = 0;
    static void* s_scratch = nullptr;
    static void* s_encode = nullptr;
    const int N = in_sizes[0] / 256, E = in_sizes[2];
    if (s_G == 0) {
        cudaFuncSetAttribute(painn_kernel<0, 0, 0>, cudaFuncAttributeMaxDynamicSharedMemorySize, SMEM_BYTES);
        cudaFuncSetAttribute(painn_kernel<50000, 800000, 132>, cudaFuncAttributeMaxDynamicSharedMemorySize, SMEM_BYTES);
        int dev = 0, sms = 0, occ = 0;
        cudaGetDevice(&dev);
        cudaDeviceGetAttribute(&sms, cudaDevAttrMultiProcessorCount, dev);
        cudaOccupancyMaxActiveBlocksPerMultiprocessor(&occ, painn_kernel<0, 0, 0>, THREADS, SMEM_BYTES);
        cudaGetSymbolAddress(&s_scratch, g_scratch);
        cudaDriverEntryPointQueryResult qr;
        cudaGetDriverEntryPoint("cuTensorMapEncodeTiled", &s_encode, cudaEnableDefault, &qr);
        s_G = occ >= 1 ? (sms < MAXG ? sms : MAXG) : 0;
    }
    if (s_G == 0 || N > TABLE_MAXN || N > s_G * (MAXNPC - 1) || (s_G - 1) * ((N + s_G - 1) / s_G) >= N || E > MAXE || E < 4 * MAXG * MAXG) return;
    Params p;
    {
        typedef CUresult (*Encode)(CUtensorMap*, CUtensorMapDataType, cuuint32_t, void*, const cuuint64_t*, const cuuint64_t*, const cuuint32_t*,
                                   const cuuint32_t*, CUtensorMapInterleave, CUtensorMapSwizzle, CUtensorMapL2promotion, CUtensorMapFloatOOBfill);
        const cuuint64_t dims[2] = {64, (cuuint64_t)N * 4}, strides[1] = {128};
        const cuuint32_t box[2] = {8, 32}, es[2] = {1, 1};
        ((Encode)s_encode)(&p.tm, CU_TENSOR_MAP_DATA_TYPE_BFLOAT16, 2, d_in[0], dims, strides, box, es, CU_TENSOR_MAP_INTERLEAVE_NONE,
                           CU_TENSOR_MAP_SWIZZLE_NONE, CU_TENSOR_MAP_L2_PROMOTION_L2_128B, CU_TENSOR_MAP_FLOAT_OOB_FILL_NONE);
    }
    p.g = (Scratch*)s_scratch;
    p.sv = (const __nv_bfloat16*)d_in[0];
    p.pos = (const __nv_bfloat16*)d_in[1];
    p.src = (const int*)d_in[2];
    p.dst = (const int*)d_in[3];
    p.freqs = (const __nv_bfloat16*)d_in[4];
    p.w1 = (const __nv_bfloat16*)d_in[5];
    p.w2 = (const __nv_bfloat16*)d_in[6];
    p.wr = (const __nv_bfloat16*)d_in[7];
    p.out = (__nv_bfloat16*)d_out;
    p.desc0 = (uint64_t)(SB >> 4) | ((uint64_t)1 << 16) | ((uint64_t)64 << 32) | ((uint64_t)1 << 62);
    p.N = N; p.E = E; p.G = s_G;
    p.NPC = (N + s_G - 1) / s_G;
    p.magic = (uint32_t)(((1ull << 32) + p.NPC - 1) / p.NPC);
    p.gpc = ((E >> 2) + s_G - 1) / s_G;
    p.odd_edges = (E & 3) != 0 || p.gpc > 3 * THREADS;
    if (N == 50000 && E == 800000 && s_G == 132) painn_kernel<50000, 800000, 132><<<s_G, THREADS, SMEM_BYTES, cudaStreamPerThread>>>(p);
    else painn_kernel<0, 0, 0><<<s_G, THREADS, SMEM_BYTES, cudaStreamPerThread>>>(p);
}
```

```cpp
#include <cuda_runtime.h>
#include <cuda_bf16.h>
#include <cuda.h>
#include <stdint.h>

namespace {

constexpr int REG_C = 224;
constexpr int PDELAY = 200;
constexpr int WA = 6, WC = 3, WE = 3;
constexpr int P0 = 80, P1W = 200;
constexpr int LAG = 400, LAG1 = 700;
constexpr int THREADS = 512;
constexpr int MAXG = 136;
constexpr int ROUNDS = 11;
constexpr int LUTS = 286, LUTN = 318;
constexpr int MAXNPC = 480;
constexpr int MAXE = 1 << 20;

constexpr int W2_OFF = 8192;
constexpr int WR_OFF = 32768;
constexpr int WIMG = 38912;
constexpr int ZL_OFF = WIMG;
constexpr int RING_OFF = 39936;
constexpr int SIDE_OFF = RING_OFF + 16 * 8192;
constexpr int RR_OFF = SIDE_OFF + 32768;
constexpr int ND_OFF = RR_OFF + ROUNDS * 1024;
constexpr int SRC_OFF = ND_OFF + ROUNDS * 256;
constexpr int LUT_OFF = SRC_OFF + ROUNDS * 256;
constexpr int SINK_OFF = LUT_OFF + 320 * 32;
constexpr int BAR_OFF = SINK_OFF + 512;
constexpr int MISC_OFF = BAR_OFF + 8 * 46;
constexpr int SMEM_BYTES = MISC_OFF + 192 + MAXG;
constexpr int PITCH = 144;
constexpr int TABLE_MAXN = 50176;
constexpr int STAGE_OFF = TABLE_MAXN * 4;
constexpr int SCNT_OFF = STAGE_OFF + MAXG * PITCH;
constexpr int OVL_OFF = MISC_OFF + 192;
constexpr int OPOS_OFF = LUT_OFF + 1024;
constexpr int NCNT_OFF = SIDE_OFF;
constexpr int NPOS_OFF = NCNT_OFF + 2048;
constexpr int YL_OFF = NPOS_OFF + 4096;
constexpr int TL_OFF = YL_OFF + 1024;
constexpr int SLOT_OFF = TL_OFF + 1024;
constexpr int SIZE_OFF = SLOT_OFF + 1280;
static_assert(SCNT_OFF + 4 * (MAXG + 32) <= OPOS_OFF && OPOS_OFF + 4096 <= LUT_OFF + LUTS * 32, "smem map");
static_assert(2 * (480 - 3 * MAXG) >= MAXG, "chunk map");
static_assert(SMEM_BYTES <= 232448 && MISC_OFF % 16 == 0 && BAR_OFF % 8 == 0 && (RING_OFF + 1024) % 8192 == 0 && SINK_OFF % 128 == 0, "smem map");

constexpr uint32_t PAY_INVALID = 0x3FFFFFFu;
constexpr uint32_t PAY_MARK = 0x3FFFDFFu;
constexpr uint32_t ST_START = 512, ST_CLOSE = 1024, ST_MID = 2048;
constexpr float QINVP = 9.0f / 510.0f;
constexpr uint32_t QTHRESH = 2126;

struct Scratch {
    unsigned sync[32];
    uint4 table[TABLE_MAXN / 4];
    uint4 wimg[WIMG / 16 + LUTS * 2];
    uint2 pos8[TABLE_MAXN];
    uint4 xbuf[MAXG * MAXG * 8 + 3 * THREADS];
    int ovfcnt[MAXG];
    int2 ovf[MAXE + 8 * MAXG + 8];
};
__device__ __align__(128) Scratch g_scratch;

struct Params {
    CUtensorMap tm;
    const __nv_bfloat16* pos;
    Scratch* g;
    const int* src;
    const int* dst;
    int N, NPC, E, gpc;
    const __nv_bfloat16* w2;
    const __nv_bfloat16* wr;
    const __nv_bfloat16* w1;
    const __nv_bfloat16* freqs;
    const __nv_bfloat16* sv;
    __nv_bfloat16* out;
    uint64_t desc0;
    int G;
    uint32_t magic;
    int odd_edges;
};
constexpr uint32_t SB = 1024;

#define TSX(i, thr)
#define TR(k, thr, t)
#define TC(k)
#define TS0(i) TSX(i, 0)

__device__ __forceinline__ uint32_t smem_u32(const void* p) { return (uint32_t)__cvta_generic_to_shared(p); }
__device__ __forceinline__ void mbar_init(uint32_t bar, uint32_t cnt) {
    asm volatile("mbarrier.init.shared::cta.b64 [%0], %1;" ::"r"(bar), "r"(cnt) : "memory");
}
__device__ __forceinline__ void mbar_arrive(uint32_t bar) {
    asm volatile("mbarrier.arrive.shared::cta.b64 _, [%0];" ::"r"(bar) : "memory");
}
__device__ __forceinline__ void mbar_expect_tx(uint32_t bar, uint32_t bytes) {
    asm volatile("mbarrier.arrive.expect_tx.shared::cta.b64 _, [%0], %1;" ::"r"(bar), "r"(bytes) : "memory");
}
__device__ __forceinline__ void mbar_wait(uint32_t bar, uint32_t parity) {
    asm volatile("{\n.reg .pred p;\n.reg .u32 c;\nmbarrier.try_wait.parity.shared::cta.b64 p, [%0], %1;\n@p bra DONE;\nmov.u32 c, 0;\n"
                 "AGAIN:\nmbarrier.try_wait.parity.shared::cta.b64 p, [%0], %1, 2000;\n@p bra DONE;\nadd.u32 c, c, 1;\n"
                 "setp.lt.u32 p, c, 0x100000;\n@p bra AGAIN;\ntrap;\nDONE:\n}\n" ::"r"(bar), "r"(parity) : "memory");
}
__device__ __forceinline__ bool elect() {
    uint32_t r;
    asm volatile("{\n.reg .pred p;\nelect.sync _|p, 0xffffffff;\nselp.u32 %0, 1, 0, p;\n}\n" : "=r"(r));
    return r;
}
__device__ __forceinline__ uint32_t pin(uint32_t x) {
    uint32_t r;
    asm volatile("shfl.sync.bfly.b32 %0, %1, 0, 31, -1;" : "=r"(r) : "r"(x));
    return r;
}
__device__ __forceinline__ void bulk_g2s(uint32_t dst, const void* src, uint32_t bytes, uint32_t bar) {
    asm volatile("cp.async.bulk.shared::cluster.global.mbarrier::complete_tx::bytes [%0], [%1], %2, [%3];"
                 ::"r"(dst), "l"(src), "r"(bytes), "r"(bar) : "memory");
}
__device__ __forceinline__ void ldsm4(uint32_t addr, uint32_t* r) {
    asm volatile("ldmatrix.sync.aligned.m8n8.x4.shared.b16 {%0,%1,%2,%3}, [%4];"
                 : "=r"(r[0]), "=r"(r[1]), "=r"(r[2]), "=r"(r[3]) : "r"(addr) : "memory");
}
__device__ __forceinline__ uint32_t pack2(float lo, float hi) {
    uint32_t r;
    asm("cvt.rn.bf16x2.f32 %0, %1, %2;" : "=r"(r) : "f"(hi), "f"(lo));
    return r;
}
__device__ __forceinline__ float bf_lo(uint32_t w) { return __uint_as_float(w << 16); }
__device__ __forceinline__ float bf_hi(uint32_t w) { return __uint_as_float(w & 0xFFFF0000u); }
__device__ __forceinline__ float rbf16(float x) { return __uint_as_float(pack2(0.f, x)); }
__device__ __forceinline__ uint32_t hmul2(uint32_t a, uint32_t b) {
    uint32_t r;
    asm("mul.rn.bf16x2 %0, %1, %2;" : "=r"(r) : "r"(a), "r"(b));
    return r;
}
__device__ __forceinline__ uint32_t hfma2(uint32_t a, uint32_t b, uint32_t c) {
    uint32_t r;
    asm("fma.rn.bf16x2 %0, %1, %2, %3;" : "=r"(r) : "r"(a), "r"(b), "r"(c));
    return r;
}
__device__ __forceinline__ uint32_t hfma2_lo(uint32_t a, uint32_t b, uint32_t c) {
    uint32_t r;
    asm("{\n.reg .b16 l, h;\n.reg .b32 t;\nmov.b32 {l, h}, %2;\nmov.b32 t, {l, l};\nfma.rn.bf16x2 %0, %1, t, %3;\n}\n" : "=r"(r) : "r"(a), "r"(b), "r"(c));
    return r;
}
__device__ __forceinline__ uint32_t hfma2_hi(uint32_t a, uint32_t b, uint32_t c) {
    uint32_t r;
    asm("{\n.reg .b16 l, h;\n.reg .b32 t;\nmov.b32 {l, h}, %2;\nmov.b32 t, {h, h};\nfma.rn.bf16x2 %0, %1, t, %3;\n}\n" : "=r"(r) : "r"(a), "r"(b), "r"(c));
    return r;
}
__device__ __forceinline__ uint32_t hadd2(uint32_t a, uint32_t b) {
    uint32_t r;
    asm("add.rn.bf16x2 %0, %1, %2;" : "=r"(r) : "r"(a), "r"(b));
    return r;
}
__device__ __forceinline__ uint32_t hsub2(uint32_t a, uint32_t b) {
    uint32_t r;
    asm("sub.rn.bf16x2 %0, %1, %2;" : "=r"(r) : "r"(a), "r"(b));
    return r;
}
__device__ __forceinline__ void cp_async_arrive(uint32_t bar) {
    asm volatile("cp.async.mbarrier.arrive.noinc.shared::cta.b64 [%0];" ::"r"(bar) : "memory");
}
__device__ __forceinline__ float tanh_fast(float x) {
    float r;
    asm("tanh.approx.f32 %0, %1;" : "=f"(r) : "f"(x));
    return r;
}
__device__ __forceinline__ void wg_fence() { asm volatile("wgmma.fence.sync.aligned;" ::: "memory"); }
__device__ __forceinline__ void wg_commit() { asm volatile("wgmma.commit_group.sync.aligned;" ::: "memory"); }
template <int N>
__device__ __forceinline__ void wg_wait() { asm volatile("wgmma.wait_group.sync.aligned %0;" ::"n"(N) : "memory"); }

#define WG_REGS "{%0,%1,%2,%3,%4,%5,%6,%7,%8,%9,%10,%11,%12,%13,%14,%15,%16,%17,%18,%19,%20,%21,%22,%23,%24,%25,%26,%27,%28,%29,%30,%31}"
#define WG_OPS(c) c(d[0]), c(d[1]), c(d[2]), c(d[3]), c(d[4]), c(d[5]), c(d[6]), c(d[7]), c(d[8]), c(d[9]), c(d[10]), \
    c(d[11]), c(d[12]), c(d[13]), c(d[14]), c(d[15]), c(d[16]), c(d[17]), c(d[18]), c(d[19]), c(d[20]), c(d[21]),     \
    c(d[22]), c(d[23]), c(d[24]), c(d[25]), c(d[26]), c(d[27]), c(d[28]), c(d[29]), c(d[30]), c(d[31])
#define WG_OPSE(c) c(e[0]), c(e[1]), c(e[2]), c(e[3]), c(e[4]), c(e[5]), c(e[6]), c(e[7]), c(e[8]), c(e[9]), c(e[10]), c(e[11]), c(e[12]), c(e[13]), c(e[14]), c(e[15]), c(e[16]), c(e[17]), c(e[18]), c(e[19]), c(e[20]), c(e[21]), c(e[22]), c(e[23]), c(e[24]), c(e[25]), c(e[26]), c(e[27]), c(e[28]), c(e[29]), c(e[30]), c(e[31])
template <int OFF, int ACC, int IDX>
__device__ __forceinline__ void wgmma_rs(float* d, const uint32_t* a, uint64_t d0) {
    if (!ACC) {
#pragma unroll
        for (int i = 0; i < 32; i++) d[i] = 0.f;
    }
    if (IDX < 4)
        asm volatile("wgmma.mma_async.sync.aligned.m64n64k16.f32.bf16.bf16 " WG_REGS ", {%32,%33,%34,%35}, %36, %37, 1, 1, 1;"
                     : WG_OPS("+f") : "r"(a[0]), "r"(a[1]), "r"(a[2]), "r"(a[3]), "l"(d0 + (OFF >> 4)), "n"(ACC));
    else
        asm volatile("{\n.reg .b64 dd;\nmov.b64 dd, {%36, 0x40000040};\nwgmma.mma_async.sync.aligned.m64n64k16.f32.bf16.bf16 " WG_REGS
                     ", {%32,%33,%34,%35}, dd, %37, 1, 1, 1;\n}\n"
                     : WG_OPS("+f") : "r"(a[0]), "r"(a[1]), "r"(a[2]), "r"(a[3]), "n"(((SB + OFF) >> 4) | (1u << 16)), "n"(ACC));
}
template <int OFF, int LBO, int ACC>
__device__ __forceinline__ void wgmma_rs2(float* d, float* e, const uint32_t* a, uint64_t d0) {
    if (!ACC) {
#pragma unroll
        for (int i = 0; i < 32; i++) d[i] = e[i] = 0.f;
    }
    asm volatile("wgmma.mma_async.sync.aligned.m64n128k16.f32.bf16.bf16 {%0,%1,%2,%3,%4,%5,%6,%7,%8,%9,%10,%11,%12,%13,%14,%15,%16,%17,%18,%19,%20,%21,%22,%23,%24,%25,%26,%27,%28,%29,%30,%31,%32,%33,%34,%35,%36,%37,%38,%39,%40,%41,%42,%43,%44,%45,%46,%47,%48,%49,%50,%51,%52,%53,%54,%55,%56,%57,%58,%59,%60,%61,%62,%63}, {%64,%65,%66,%67}, %68, %69, 1, 1, 1;"
                 : WG_OPS("+f"), WG_OPSE("+f") : "r"(a[0]), "r"(a[1]), "r"(a[2]), "r"(a[3]), "l"(d0 + (OFF >> 4) + ((LBO / 16 - 1) << 16)), "n"(ACC));
}
template <int G>
__device__ __forceinline__ void wgmma_group(float* P, float* W, const uint32_t* h, const uint32_t* rf, uint64_t d0) {
    wgmma_rs<W2_OFF + 8192 * G, 0, 5 * G>(P, h, d0);
    wgmma_rs<W2_OFF + 8192 * G + 2048, 1, 5 * G + 1>(P, h + 4, d0);
    wgmma_rs<W2_OFF + 8192 * G + 4096, 1, 5 * G + 2>(P, h + 8, d0);
    wgmma_rs<W2_OFF + 8192 * G + 6144, 1, 5 * G + 3>(P, h + 12, d0);
    wgmma_rs<WR_OFF + 2048 * G, 0, 5 * G + 4>(W, rf, d0);
}
__device__ __forceinline__ void wgmma_ss_k64(float* d, uint64_t da, uint64_t db) {
#pragma unroll
    for (int i = 0; i < 32; i++) d[i] = 0.f;
    asm volatile("wgmma.mma_async.sync.aligned.m64n64k16.f32.bf16.bf16 " WG_REGS ", %32, %33, 0, 1, 1, 0, 1;" : WG_OPS("+f") : "l"(da), "l"(db));
#pragma unroll
    for (int k = 1; k < 4; k++)
        asm volatile("wgmma.mma_async.sync.aligned.m64n64k16.f32.bf16.bf16 " WG_REGS ", %32, %33, 1, 1, 1, 0, 1;"
                     : WG_OPS("+f") : "l"(da + 2 * k), "l"(db + 128 * k));
}
__device__ __forceinline__ void fence_regs(float* d) { asm volatile("" : WG_OPS("+f")::"memory"); }
__device__ __forceinline__ uint32_t qaxis(float x) {
    const float u = fmaf(x, QINVP, 0.25f);
    const float f = u - ((u + 12582912.f) - 12582912.f);
    return __float_as_uint(fmaf(fabsf(f), 510.f, 12582912.f));
}
__device__ __forceinline__ uint32_t qcode(float x, float y, float z, uint32_t tx) {
    return __byte_perm(__byte_perm(qaxis(x), qaxis(y), 0x3340), qaxis(z), 0x3410) ^ tx;
}
__device__ __forceinline__ bool near_test(uint32_t ca, uint32_t cb, uint32_t tag24) {
    const uint32_t D = __vabsdiffu4(ca, cb);
    return __dp4a(D, D, 0u) <= QTHRESH || ((ca ^ tag24) | (cb ^ tag24)) >= 0x1000000u;
}
constexpr float QMAX = 23.9375f;
__device__ __forceinline__ float square(uint32_t rxy, uint32_t rz) {
    const uint32_t qxy = hmul2(rxy, rxy), qz = hmul2(rz, rz);
    return bf_lo(qxy) + bf_hi(qxy) + bf_lo(qz);
}

__device__ __forceinline__ uint32_t lds32(uint32_t addr) {
    uint32_t r;
    asm volatile("ld.shared.u32 %0, [%1];" : "=r"(r) : "r"(addr) : "memory");
    return r;
}
__device__ __forceinline__ void sts32_if(uint32_t addr, uint32_t v, bool c) {
    asm volatile("{\n.reg .pred p;\nsetp.ne.u32 p, %2, 0;\n@p st.shared.u32 [%0], %1;\n}\n" ::"r"(addr), "r"(v), "r"((uint32_t)c) : "memory");
}
__device__ __forceinline__ uint32_t sel(bool c, uint32_t a, uint32_t b) {
    uint32_t r;
    asm("{\n.reg .pred p;\nsetp.ne.u32 p, %3, 0;\nselp.b32 %0, %1, %2, p;\n}\n" : "=r"(r) : "r"(a), "r"(b), "r"((uint32_t)c));
    return r;
}
__device__ __forceinline__ uint32_t lds16(uint32_t addr) {
    uint32_t r;
    asm volatile("ld.shared.u16 %0, [%1];" : "=r"(r) : "r"(addr) : "memory");
    return r;
}
__device__ __forceinline__ void sts16_if(uint32_t addr, uint32_t v, bool c) {
    asm volatile("{\n.reg .pred p;\nsetp.ne.u32 p, %2, 0;\n@p st.shared.u16 [%0], %1;\n}\n" ::"r"(addr), "h"((unsigned short)v), "r"((uint32_t)c) : "memory");
}
__device__ __forceinline__ void sts64_if(uint32_t addr, uint32_t x, uint32_t y, bool c) {
    asm volatile("{\n.reg .pred p;\nsetp.ne.u32 p, %3, 0;\n@p st.shared.v2.u32 [%0], {%1, %2};\n}\n" ::"r"(addr), "r"(x), "r"(y), "r"((uint32_t)c) : "memory");
}
__device__ __forceinline__ uint32_t atoms_add(uint32_t addr, uint32_t v) {
    uint32_t r;
    asm volatile("atom.shared.add.u32 %0, [%1], %2;" : "=r"(r) : "r"(addr), "r"(v) : "memory");
    return r;
}
__device__ __forceinline__ void stg128_if(void* ptr, uint4 v, bool c) {
    asm volatile("{\n.reg .pred p;\nsetp.ne.u32 p, %5, 0;\n@p st.relaxed.gpu.global.v4.u32 [%0], {%1,%2,%3,%4};\n}\n"
                 ::"l"(ptr), "r"(v.x), "r"(v.y), "r"(v.z), "r"(v.w), "r"((uint32_t)c) : "memory");
}
__device__ __forceinline__ void lds128(uint32_t addr, uint32_t* r) {
    asm volatile("ld.shared.v4.u32 {%0,%1,%2,%3}, [%4];" : "=r"(r[0]), "=r"(r[1]), "=r"(r[2]), "=r"(r[3]) : "r"(addr) : "memory");
}
__device__ __forceinline__ void stg2_if(uint64_t ptr, const uint32_t* r, uint32_t c) {
    asm volatile("{\n.reg .pred p;\nsetp.ne.u32 p, %9, 0;\n@p st.global.cs.v4.u32 [%8], {%0,%1,%2,%3};\n"
                 "@p st.global.cs.v4.u32 [%8 + 64], {%4,%5,%6,%7};\n}\n"
                 ::"r"(r[0]), "r"(r[1]), "r"(r[2]), "r"(r[3]), "r"(r[4]), "r"(r[5]), "r"(r[6]), "r"(r[7]), "l"(ptr), "r"(c) : "memory");
}
__device__ __forceinline__ void gather_s(uint32_t dst, const char* base, uint32_t src) {
    asm volatile("{\n.reg .pred p;\nsetp.eq.u32 p, %2, 0xFFFF;\ncp.async.cg.shared.global [%0], [%1], 16, p;\n}\n"
                 ::"r"(dst), "l"(base + (size_t)src * 512), "r"(src) : "memory");
}
__device__ __forceinline__ void gather_v(uint32_t dst, const char* base, uint32_t src) {
    asm volatile("{\n.reg .pred p;\nsetp.eq.u32 p, %2, 0xFFFF;\n"
                 "cp.async.cg.shared.global [%0 + 1024], [%1 + 128], 16, p;\ncp.async.cg.shared.global [%0 + 2048], [%1 + 256], 16, p;\n"
                 "cp.async.cg.shared.global [%0 + 3072], [%1 + 384], 16, p;\n}\n" ::"r"(dst), "l"(base + (size_t)src * 512), "r"(src) : "memory");
}
__device__ __forceinline__ void gather_row_if(uint32_t dst, const char* src, uint32_t c) {
    asm volatile("{\n.reg .pred p;\nsetp.ne.u32 p, %2, 0;\n@p cp.async.cg.shared.global [%0], [%1], 16;\n"
                 "@p cp.async.cg.shared.global [%0 + 1024], [%1 + 128], 16;\n@p cp.async.cg.shared.global [%0 + 2048], [%1 + 256], 16;\n"
                 "@p cp.async.cg.shared.global [%0 + 3072], [%1 + 384], 16;\n}\n" ::"r"(dst), "l"(src), "r"(c) : "memory");
}
__device__ __forceinline__ void lds2_if(uint32_t a0, uint32_t a1, uint32_t* r, uint32_t c) {
    asm volatile("{\n.reg .pred p;\nsetp.ne.u32 p, %10, 0;\n@p ld.shared.v4.u32 {%0,%1,%2,%3}, [%8];\n@p ld.shared.v4.u32 {%4,%5,%6,%7}, [%9];\n}\n"
                 : "+r"(r[0]), "+r"(r[1]), "+r"(r[2]), "+r"(r[3]), "+r"(r[4]), "+r"(r[5]), "+r"(r[6]), "+r"(r[7])
                 : "r"(a0), "r"(a1), "r"(c) : "memory");
}
__device__ __forceinline__ int fresh_lane() {
    int l;
    asm volatile("mov.u32 %0, %%laneid;" : "=r"(l));
    return l;
}

__device__ __forceinline__ void cold_edges(unsigned char* smem, const Params& p, int lo, int hi, uint32_t tag) {
#pragma unroll 1
    for (int e = lo + threadIdx.x; e < hi; e += THREADS) {
        const int s = p.src[e], d = p.dst[e];
        if (near_test(reinterpret_cast<const uint32_t*>(smem)[s], reinterpret_cast<const uint32_t*>(smem)[d], tag << 24)) {
            const uint32_t own = __umulhi((uint32_t)d, p.magic);
            const uint32_t slot4 = atomicAdd(reinterpret_cast<uint32_t*>(smem + SCNT_OFF) + own, 4u);
            uint32_t* line = reinterpret_cast<uint32_t*>(smem + STAGE_OFF) + own * (PITCH / 4);
            if (slot4 < 124) {
                line[slot4 >> 2] = ((uint32_t)s << 15) + ((uint32_t)(d - own * p.NPC) << 6) + tag;
            } else {
                uint32_t o = atomicAdd(reinterpret_cast<uint32_t*>(smem + MISC_OFF) + 16, 1u);
                p.g->ovf[(size_t)blockIdx.x * (4 * p.gpc + 4) + o] = make_int2(s, d);
                line[31] = (PAY_MARK << 6) | tag;
            }
        }
    }
}
__device__ __forceinline__ void cold_filter(unsigned char* smem, const Params& p, int e0, int e1, uint32_t tag, int redo) {
    if (redo) {
        if (threadIdx.x < MAXG) reinterpret_cast<uint32_t*>(smem + SCNT_OFF)[threadIdx.x] = 0;
        __syncthreads();
    }
    cold_edges(smem, p, redo ? 4 * e0 : 4 * (e0 + 3 * THREADS), 4 * e1, tag);
    if (blockIdx.x == 0) cold_edges(smem, p, p.E & ~3, p.E, tag);
    __syncthreads();
    if (threadIdx.x == 0) p.g->ovfcnt[blockIdx.x] = reinterpret_cast<uint32_t*>(smem + MISC_OFF)[16];
    __threadfence();
    __syncthreads();
}
__device__ __forceinline__ float distance(float q) {
    float d;
    asm("sqrt.approx.ftz.f32 %0, %1;" : "=f"(d) : "f"(rbf16(rbf16(q) + 1e-8f)));
    return rbf16(d);
}
__device__ __forceinline__ float fcut(float d) {
    return d < 5.0f ? 0.5f * rbf16(rbf16(__cosf(rbf16(rbf16(3.14159265358979f * d) * 0.2f))) + 1.0f) : 0.f;
}
__device__ __forceinline__ uint4 basis8(float d, uint4 f) {
    const float sc = __fdividef(fcut(d), d);
    const uint32_t dd = __byte_perm(__float_as_uint(d), 0, 0x3232);
    uint32_t x[4] = {hmul2(f.x, dd), hmul2(f.y, dd), hmul2(f.z, dd), hmul2(f.w, dd)};
#pragma unroll
    for (int i = 0; i < 4; i++) x[i] = pack2(__sinf(bf_lo(x[i])) * sc, __sinf(bf_hi(x[i])) * sc);
    return make_uint4(x[0], x[1], x[2], x[3]);
}
__device__ __forceinline__ void cold_nodes(unsigned char* smem, const Params& p, int nn, uint32_t tag) {
    float* acc = reinterpret_cast<float*>(smem + RING_OFF);
    const int nbase = blockIdx.x * p.NPC, lane = threadIdx.x & 31;
    const uint32_t* sv = reinterpret_cast<const uint32_t*>(p.sv);
    const volatile uint32_t* xin = reinterpret_cast<const uint32_t*>(p.g->xbuf) + blockIdx.x * p.G * 32;
#pragma unroll 1
    for (int i = threadIdx.x; i < p.G * 32; i += THREADS) {
        if (xin[(i & ~31) + 15] < (PAY_MARK << 6)) {
            uint32_t w;
            int it = 0;
            do {
                w = xin[i];
                if (++it > (1 << 22)) __trap();
            } while ((w ^ tag) & 63u);
            if ((w >> 6) == PAY_MARK) smem[OVL_OFF + atomicAdd(reinterpret_cast<uint32_t*>(smem + MISC_OFF) + 17, 1u)] = (unsigned char)(i >> 5);
        }
    }
    __threadfence();
    __syncthreads();
    const int nmark = reinterpret_cast<uint32_t*>(smem + MISC_OFF)[17];
#pragma unroll 1
    for (int c0 = 0; c0 < nn; c0 += 128) {
        __syncthreads();
#pragma unroll 1
        for (int i = threadIdx.x; i < 128 * 256; i += THREADS) acc[i] = 0.f;
        __syncthreads();
#pragma unroll 1
        for (int m = -1; m < nmark; m++) {
            const int pr = m < 0 ? 0 : smem[OVL_OFF + m];
            const int cnt = m < 0 ? p.G * 32 : __ldcg(&p.g->ovfcnt[pr]);
#pragma unroll 1
            for (int i = threadIdx.x; i - lane < cnt; i += THREADS) {
                int2 e = make_int2(0, -1);
                if (i < cnt) {
                    if (m < 0) {
                        const uint32_t w = xin[i];
                        if (((w ^ tag) & 63u) == 0) e = make_int2(w >> 15, (w >> 6) & 511u);
                    } else {
                        e = __ldcg(p.g->ovf + (size_t)pr * (4 * p.gpc + 4) + i);
                        e.y -= nbase;
                    }
                }
                uint32_t rxy = 0, rz = 0;
                bool in = e.y >= c0 && e.y < min(c0 + 128, nn);
                if (in) {
                    const uint2 ps = __ldcg(p.g->pos8 + e.x), pd = __ldcg(p.g->pos8 + nbase + e.y);
                    rxy = hsub2(ps.x, pd.x);
                    rz = hsub2(ps.y, pd.y);
                    in = square(rxy, rz) < QMAX;
                }
#pragma unroll 1
                for (uint32_t todo = __ballot_sync(0xffffffffu, in); todo; todo &= todo - 1) {
                    const int l = __ffs(todo) - 1;
                    const uint32_t* row = sv + (size_t)__shfl_sync(0xffffffffu, e.x, l) * 128 + lane;
                    float* o = acc + (__shfl_sync(0xffffffffu, e.y, l) - c0) * 256 + 2 * lane;
                    const uint32_t xy = __shfl_sync(0xffffffffu, rxy, l), z = __shfl_sync(0xffffffffu, rz, l);
                    const float d = distance(square(xy, z)), fc = fcut(d);
                    uint32_t x = __ldg(row);
                    float y0 = 0.f, y1 = 0.f, m2[6];
#pragma unroll 4
                    for (int k = 0; k < 64; k++) {
                        const uint32_t u = __shfl_sync(0xffffffffu, x, k >> 1), w = __ldg(reinterpret_cast<const uint32_t*>(p.w1) + k * 32 + lane);
                        const float a = k & 1 ? bf_hi(u) : bf_lo(u);
                        y0 = fmaf(a, bf_lo(w), y0);
                        y1 = fmaf(a, bf_hi(w), y1);
                    }
                    y0 = rbf16(y0); y1 = rbf16(y1);
                    x = pack2(y0 / (1.f + __expf(-y0)), y1 / (1.f + __expf(-y1)));
                    const float rb = rbf16(rbf16(__sinf(rbf16(d * __bfloat162float(p.freqs[lane & 15])))) / d);
#pragma unroll
                    for (int g = 0; g < 3; g++) {
                        float p0 = 0.f, p1 = 0.f, w0 = 0.f, w1 = 0.f;
#pragma unroll 4
                        for (int k = 0; k < 64; k++) {
                            const uint32_t u = __shfl_sync(0xffffffffu, x, k >> 1), w = __ldg(reinterpret_cast<const uint32_t*>(p.w2) + k * 96 + g * 32 + lane);
                            const float a = k & 1 ? bf_hi(u) : bf_lo(u);
                            p0 = fmaf(a, bf_lo(w), p0);
                            p1 = fmaf(a, bf_hi(w), p1);
                        }
#pragma unroll 4
                        for (int k = 0; k < 16; k++) {
                            const uint32_t w = __ldg(reinterpret_cast<const uint32_t*>(p.wr) + k * 96 + g * 32 + lane);
                            const float a = __shfl_sync(0xffffffffu, rb, k);
                            w0 = fmaf(a, bf_lo(w), w0);
                            w1 = fmaf(a, bf_hi(w), w1);
                        }
                        m2[2 * g] = rbf16(rbf16(p0) * rbf16(rbf16(w0) * fc));
                        m2[2 * g + 1] = rbf16(rbf16(p1) * rbf16(rbf16(w1) * fc));
                    }
                    atomicAdd(o, m2[0]);
                    atomicAdd(o + 1, m2[1]);
#pragma unroll
                    for (int k = 1; k < 4; k++) {
                        const uint32_t v = __ldg(row + 32 * k);
                        const float rh = rbf16((k == 1 ? bf_lo(xy) : k == 2 ? bf_hi(xy) : bf_lo(z)) / d);
                        atomicAdd(o + 64 * k, fmaf(m2[2], bf_lo(v), m2[4] * rh));
                        atomicAdd(o + 64 * k + 1, fmaf(m2[3], bf_hi(v), m2[5] * rh));
                    }
                }
            }
        }
        __syncthreads();
#pragma unroll 1
        for (int i = threadIdx.x; i < min(128, nn - c0) * 128; i += THREADS) {
            const uint32_t v = __ldg(sv + (size_t)(nbase + c0) * 128 + i);
            reinterpret_cast<uint32_t*>(p.out)[(size_t)(nbase + c0) * 128 + i] = pack2(bf_lo(v) + rbf16(acc[2 * i]), bf_hi(v) + rbf16(acc[2 * i + 1]));
        }
    }
}

template <int CN, int CE, int CG>
__global__ void __launch_bounds__(THREADS, 1) painn_kernel(const __grid_constant__ Params p) {
    extern __shared__ __align__(1024) unsigned char smem_dyn[];
    unsigned char* const smem = static_cast<unsigned char*>(__cvta_shared_to_generic(SB));
    constexpr uint32_t sb = SB;
    const int tid = threadIdx.x, lane = tid & 31;
    const int warp = __shfl_sync(0xffffffffu, tid >> 5, 0);
    constexpr int CNPC = CG ? (CN + CG - 1) / CG : 1, CGPC = CG ? (CE / 4 + CG - 1) / CG : 1;
    const int b = blockIdx.x, G = CG ? CG : p.G, NPC = CG ? CNPC : p.NPC, N = CG ? CN : p.N, gpc = CG ? CGPC : p.gpc;
    const uint32_t magic = CG ? (uint32_t)(((1ull << 32) + CNPC - 1) / CNPC) : p.magic;
    const bool odd_edges = CG ? (CE & 3) != 0 || CGPC > 3 * THREADS : p.odd_edges;
    const int nbase = b * NPC, nn = min(NPC, N - nbase);
    const int e0 = b * gpc, e1 = min((CG ? CE : p.E) >> 2, e0 + gpc);

    uint4* stage4 = reinterpret_cast<uint4*>(smem + STAGE_OFF);
    uint32_t* ncnt = reinterpret_cast<uint32_t*>(smem + NCNT_OFF);
    uint32_t* misc = reinterpret_cast<uint32_t*>(smem + MISC_OFF);
    const uint32_t bar_full = sb + BAR_OFF + (warp & 7) * 40, bar_empty = bar_full + 16, bar_side = bar_full + 32, bar_tab = sb + BAR_OFF + 336;

    auto warm = [&](int first, int n) {
#pragma unroll 1
        for (int i = first; i < first + n; i++) {
            if (elect())
                asm volatile("cp.async.bulk.tensor.2d.shared::cluster.global.mbarrier::complete_tx::bytes [%0], [%1, {0, %3}], [%2];"
                             ::"r"(sb + SINK_OFF), "l"(&p.tm), "r"(bar_tab + 8), "r"(nbase * 4 + i * 32) : "memory");
        }
    };
    TS0(0);
    int4 es[3], ed[3];
    auto load_edges = [&](int i) {
        const int g = min(e0 + tid + i * THREADS, e1 - 1);
        asm volatile("ld.global.cs.v4.u32 {%0,%1,%2,%3}, [%8];\nld.global.cs.v4.u32 {%4,%5,%6,%7}, [%9];"
                     : "=r"(es[i].x), "=r"(es[i].y), "=r"(es[i].z), "=r"(es[i].w), "=r"(ed[i].x), "=r"(ed[i].y), "=r"(ed[i].z), "=r"(ed[i].w)
                     : "l"(reinterpret_cast<const int4*>(p.src) + g), "l"(reinterpret_cast<const int4*>(p.dst) + g) : "memory");
    };
    unsigned epoch;
    const uint32_t tbytes = ((N + 3) >> 2) * 16;
    {
        uint32_t pxy, pz;
        asm volatile("ld.global.nc.u32 %0, [%3];\nld.global.nc.u32 %1, [%3 + 4];\nld.global.ca.u32 %2, [%4];"
                     : "=r"(pxy), "=r"(pz), "=r"(epoch)
                     : "l"(reinterpret_cast<const uint32_t*>(p.pos) + ((nbase + min(tid, nn - 1)) * 3 >> 1)), "l"(p.g->sync) : "memory");
        const uint32_t sh = ((nbase + tid) & 1) << 4;
        pxy = __funnelshift_r(pxy, pz, sh);
        pz >>= sh;
        if (tid < nn) {
            reinterpret_cast<uint32_t*>(p.g->table)[nbase + tid] = qcode(bf_lo(pxy), bf_hi(pxy), bf_lo(pz), ((epoch & 31u) ^ 0x6Bu) << 24);
            p.g->pos8[nbase + tid] = make_uint2(pxy, pz);
        }
        reinterpret_cast<uint2*>(smem + OPOS_OFF)[tid] = make_uint2(pxy, pz);
        if (pxy == 0xFFFFFFFFu && pz == 0xFFFFFFFFu && epoch == 0xFFFFFFFFu) asm volatile("nanosleep.u32 0;");
        load_edges(0);
    }
    __syncthreads();
    const uint32_t tag = (epoch & 31u) | 32u;
    if (warp == 15) {
        if (elect()) {
            asm volatile("red.relaxed.gpu.global.add.u32 [%0], 1;" ::"l"(p.g->sync + 1) : "memory");
            asm volatile("prefetch.tensormap [%0];" ::"l"(&p.tm) : "memory");
            mbar_init(bar_tab, 1);
            mbar_init(bar_tab + 8, 1);
            mbar_expect_tx(bar_tab, tbytes);
            mbar_expect_tx(bar_tab + 8, (WA + WC + WE) * 512);
        }
        TSX(1, 511);
        const unsigned want = (epoch + 1) * G;
        unsigned c;
        int it = smem_u32(smem_dyn) == SB ? 0 : 1 << 22;
        do {
            asm volatile("ld.relaxed.gpu.global.u32 %0, [%1];" : "=r"(c) : "l"(p.g->sync + 1) : "memory");
            if (++it > (1 << 22)) __trap();
        } while (c != want);
        __syncwarp();
        if (lane < 8) {
            const uint32_t part = (tbytes / 8) & ~127u, i = lane;
            bulk_g2s(sb + i * part, reinterpret_cast<const char*>(p.g->table) + i * part, i == 7 ? tbytes - i * part : part, bar_tab);
        }
        TSX(2, 511);
    }
    if (warp == 14) {
#pragma unroll 1
        for (int c = b * 32 + lane; c < WIMG / 16 + LUTS * 2; c += G * 32) {
            const int row = c >> 3, j = (c ^ row) & 7;
            uint4 v;
            if (c < 512) {
                const uint32_t half = 0x3F003F00u;
                v = __ldg(reinterpret_cast<const uint4*>(p.w1) + row * 8 + j);
                v = make_uint4(hmul2(v.x, half), hmul2(v.y, half), hmul2(v.z, half), hmul2(v.w, half));
            } else if (c >= WIMG / 16) {
                v = basis8(__uint_as_float((0x409D - ((c - WIMG / 16) >> 1)) << 16), __ldg(reinterpret_cast<const uint4*>(p.freqs) + (c & 1)));
            } else {
                const uint32_t* q = (c < 2048 ? reinterpret_cast<const uint32_t*>(p.w2) + (row & 63) * 96 + ((row >> 6) - 1) * 32
                                              : reinterpret_cast<const uint32_t*>(p.wr) + (row & 15) * 96 + ((row >> 4) - 16) * 32) + (j & 4) * 4 + (j & 3);
                v = make_uint4(__ldg(q), __ldg(q + 4), __ldg(q + 8), __ldg(q + 12));
            }
            p.g->wimg[c] = v;
        }
    }
    if (warp < 8 && elect()) {
        mbar_init(bar_full, 32); mbar_init(bar_full + 8, 32);
        mbar_init(bar_empty, 1);
        mbar_init(bar_side, 32);
    }
    if (tid < MAXG) reinterpret_cast<uint32_t*>(smem + SCNT_OFF)[tid] = 0;
    if (tid < 48) misc[tid] = 0;
    {
        const uint32_t inv = (PAY_INVALID << 6) | tag;
        stage4[tid] = stage4[tid + THREADS] = make_uint4(inv, inv, inv, inv);
        if (tid < MAXG * (PITCH / 16) - 2 * THREADS) stage4[tid + 2 * THREADS] = make_uint4(inv, inv, inv, inv);
    }
    __syncthreads();
#pragma unroll
    for (int i = 0; i < 3; i++)
        stg128_if(p.g->xbuf + ((tid >> 3) * G + b) * 8 + (tid & 7) + i * G * THREADS, make_uint4(0, 0, 0, 0), tid + i * THREADS < G * 8);
    load_edges(1);
    load_edges(2);
    if (tid == THREADS - 1) asm volatile("fence.acq_rel.gpu;" ::: "memory");
    mbar_wait(bar_tab, 0);
    TS0(3);
    if (warp == 15) warm(0, WA);

    bool over = false;
#pragma unroll 1
    for (int i = 0, g = e0 + tid; i < 3; i++, g += THREADS) {
        const int s[4] = {es[0].x, es[0].y, es[0].z, es[0].w}, d[4] = {ed[0].x, ed[0].y, ed[0].z, ed[0].w};
        uint32_t ca[4], cb[4], own[4], sl[4];
        bool c[4];
#pragma unroll
        for (int j = 0; j < 4; j++) { ca[j] = lds32(sb + 4 * s[j]); cb[j] = lds32(sb + 4 * d[j]); }
#pragma unroll
        for (int j = 0; j < 4; j++) {
            c[j] = near_test(ca[j], cb[j], tag << 24) && g < e1;
            own[j] = __umulhi((uint32_t)d[j], magic);
            sl[j] = atomicAdd(reinterpret_cast<uint32_t*>(smem + SCNT_OFF) + (c[j] ? own[j] : MAXG + lane), 4u);
        }
#pragma unroll
        for (int j = 0; j < 4; j++)
            sts32_if(sb + STAGE_OFF + own[j] * PITCH + sl[j], own[j] * (uint32_t)(-64 * NPC) + (((uint32_t)s[j] << 15) + (((uint32_t)d[j] << 6) + tag)),
                     c[j] && sl[j] < 124);
#pragma unroll
        for (int j = 0; j < 4; j++) over |= c[j] && sl[j] >= 124;
        es[0] = es[1]; es[1] = es[2];
        ed[0] = ed[1]; ed[1] = ed[2];
    }
    {
        const int redo = __syncthreads_or(over);
        if (__builtin_expect(redo || odd_edges, 0)) cold_filter(smem, p, e0, e1, tag, redo);
    }
    TS0(4);
#pragma unroll 1
    for (int r = tid >> 2; r < G; r += THREADS / 4) {
        const int c = r * (PITCH / 16) + (tid & 3);
        uint4* const x = p.g->xbuf + (r * G + b) * 8 + (tid & 3);
        stg128_if(x, stage4[c], true);
        stg128_if(x + 4, stage4[c + 4], reinterpret_cast<uint32_t*>(smem + SCNT_OFF)[r] >= 64);
    }
    ncnt[tid] = 0;
    if (tid < 480) reinterpret_cast<uint32_t*>(smem + SLOT_OFF)[tid] = tid < 32 ? tid * 0x100010 + 0x80000 : tid < 320 ? ~0u : 0u;
    if (tid == 511) reinterpret_cast<uint2*>(smem + NPOS_OFF)[511] = make_uint2(sb + SLOT_OFF + 1278, 0);
    __syncthreads();
    reinterpret_cast<uint4*>(smem + RR_OFF)[tid] = make_uint4(0, 0, 0, 0);
    if (tid < ROUNDS * 80 - THREADS) reinterpret_cast<uint4*>(smem + RR_OFF)[tid + THREADS] = make_uint4(0, 0, 0, 0);
    if (tid < ROUNDS * 32) reinterpret_cast<uint2*>(smem + SRC_OFF)[tid] = make_uint2(~0u, ~0u);
    __nanosleep(PDELAY);
    TS0(5);

    uint32_t rxy[4], gz[4], src[4], rk[4], dn[4];
    const uint32_t sink = sb + NCNT_OFF + 4 * (480 + lane);
    if (warp < 15) {
        uint32_t ew[3][4], bad[2];
        const int u = tid - 3 * G;
        const uint4* const xin = p.g->xbuf + b * G * 8;
        const uint4* cp = xin + (u < 0 ? tid + tid / 3 * 5 : u * 8 + 3);
        bad[0] = u < G;
        bad[1] = u >= 0 && u + 480 - 3 * G < G;
#pragma unroll
        for (int i = 0; i < 3; i++) ew[i][0] = ew[i][1] = ew[i][2] = ew[i][3] = (PAY_INVALID << 6) | tag;
        int it = 0;
#pragma unroll 1
        do {
#pragma unroll
            for (int i = 0; i < 2; i++)
                asm volatile("{\n.reg .pred p;\nsetp.ne.u32 p, %5, 0;\n@p ld.relaxed.gpu.global.v4.u32 {%0,%1,%2,%3}, [%4];\n}\n"
                             : "+r"(ew[i][0]), "+r"(ew[i][1]), "+r"(ew[i][2]), "+r"(ew[i][3]) : "l"(cp + i * (480 - 3 * G) * 8), "r"(bad[i]) : "memory");
#pragma unroll
            for (int i = 0; i < 2; i++) bad[i] = ((ew[i][0] ^ tag) | (ew[i][1] ^ tag) | (ew[i][2] ^ tag) | (ew[i][3] ^ tag)) & 63u;
            if (++it > (1 << 22)) __trap();
        } while (__any_sync(0xffffffffu, bad[0] | bad[1]));
        if (warp >= (3 * G) >> 5) {
            const uint32_t f0 = __ballot_sync(0xffffffffu, u >= 0 && ew[0][3] < (PAY_MARK << 6)), f1 = __ballot_sync(0xffffffffu, ew[1][3] < (PAY_MARK << 6));
            if (__builtin_expect(f0 | f1, 0)) {
                uint64_t f = (uint64_t)f1 << 32 | f0;
#pragma unroll 1
                for (int k = 7 - (lane >> 2); k; k--) f &= f - 1;
                if (f) {
                    const int l = __ffsll(f) - 1;
                    do {
                        asm volatile("ld.relaxed.gpu.global.v4.u32 {%0,%1,%2,%3}, [%4];" : "=r"(ew[2][0]), "=r"(ew[2][1]), "=r"(ew[2][2]), "=r"(ew[2][3])
                                     : "l"(xin + (u - lane + l + (l >> 5) * (448 - 3 * G)) * 8 + 4 + (lane & 3)) : "memory");
                        if (++it > (1 << 22)) __trap();
                    } while (((ew[2][0] ^ tag) | (ew[2][1] ^ tag) | (ew[2][2] ^ tag) | (ew[2][3] ^ tag)) & 63u);
                    if ((ew[2][3] >> 6) == PAY_MARK || lane == 0) misc[0] = 1;
                }
                __syncwarp();
            }
#pragma unroll 1
            for (int i = 0; i < 2; i++) {
                if (ew[0][0] >= (PAY_MARK << 6)) {
#pragma unroll
                    for (int j = 0; j < 4; j++) { ew[0][j] = ew[1][j]; ew[1][j] = ~0u; }
                }
                uint32_t from = __ballot_sync(0xffffffffu, ew[1][0] < (PAY_MARK << 6)), to = __ballot_sync(0xffffffffu, ew[0][0] >= (PAY_MARK << 6));
#pragma unroll 1
                for (; from; from &= from - 1, to &= to - 1) {
                    if (!to) misc[0] = 1;
#pragma unroll
                    for (int j = 0; j < 4; j++) {
                        const uint32_t x = __shfl_sync(0xffffffffu, ew[1][j], __ffs(from) - 1);
                        if (lane == __ffs(to) - 1) ew[0][j] = x;
                    }
                }
#pragma unroll
                for (int j = 0; j < 4; j++) ew[1][j] = ew[2][j];
            }
        }
        {
            uint2 ps[4], pd[4];
#pragma unroll
            for (int j = 0; j < 4; j++) {
                dn[j] = (ew[0][j] >> 3) & 4088u;
                src[j] = ew[0][j] >> 15;
                ps[j] = __ldcg(p.g->pos8 + (dn[j] == 4088u ? nbase : src[j]));
            }
#pragma unroll
            for (int j = 0; j < 4; j++) pd[j] = *reinterpret_cast<const uint2*>(smem + OPOS_OFF + dn[j]);
            asm volatile("bar.arrive 1, 512;" ::: "memory");
            float q[4];
#pragma unroll
            for (int j = 0; j < 4; j++) {
                rxy[j] = hsub2(ps[j].x, pd[j].x);
                gz[j] = hsub2(ps[j].y, pd[j].y);
                q[j] = square(rxy[j], gz[j]);
                const bool in = q[j] < QMAX && dn[j] != 4088u;
                rk[j] = atoms_add(in ? sb + NCNT_OFF + (dn[j] >> 1) : sink, 512u);
                if (!in) dn[j] = 4088u;
            }
            uint32_t row[4], n = 0;
            bool single[4];
#pragma unroll
            for (int j = 0; j < 4; j++) {
                q[j] = distance(q[j]);
                row[j] = 0x409D - (__float_as_uint(q[j]) >> 16);
                single[j] = row[j] >= LUTS && dn[j] != 4088u;
                n += single[j];
            }
            n = atoms_add(n ? sb + MISC_OFF + 4 : sink, n) + LUTS;
#pragma unroll
            for (int j = 0; j < 4; j++) {
                float id;
                asm("rcp.approx.ftz.f32 %0, %1;" : "=f"(id) : "f"(q[j]));
                sts32_if(sb + LUT_OFF + min(n, LUTN - 1) * 32, __float_as_uint(q[j]), single[j]);
                if (single[j]) row[j] = n++;
                rxy[j] = pack2(bf_lo(rxy[j]) * id, bf_hi(rxy[j]) * id);
                gz[j] = pack2(0.f, bf_lo(gz[j]) * id) + row[j] * 32;
            }
        }
    } else {
        const uint4 fq = __ldg(reinterpret_cast<const uint4*>(p.freqs) + (lane & 1));
        rxy[0] = fq.x; rxy[1] = fq.y; rxy[2] = fq.z; rxy[3] = fq.w;
        asm volatile("bar.sync 1, 512;" ::: "memory");
        warm(WA, WC);
    }
    __syncthreads();
    TS0(6);

    const uint32_t lt = (1u << lane) - 1;
    uint32_t place = ~0u, mid = 0, last = 0, steps = 0, c = 0;
    if (warp < 15) {
        if (tid < nn) c = ncnt[tid] >> 9;
        steps = min((c + 1) >> 1, 15u);
        const uint32_t bin = sel(tid >= nn, 9, (uint32_t)(0x11223354678ull >> (4 * min(c, 11u))) & 15), sh = (bin & 1) * 16;
        const bool odd = c > 3 && (c & 1);
        const uint32_t peers = __match_any_sync(0xffffffffu, bin), om = __ballot_sync(0xffffffffu, odd);
        uint32_t x = atoms_add(lane == 0 ? sb + MISC_OFF + 4 * 37 : sink, __popc(om));
        uint32_t r = atoms_add((peers & lt) == 0 ? sb + MISC_OFF + 4 * 32 + 2 * (bin & 14) : sink, __popc(peers) << sh);
        x = __shfl_sync(0xffffffffu, x, 0) + __popc(om & lt);
        r = ((__shfl_sync(0xffffffffu, r, __ffs(peers) - 1) >> sh) & 0xFFFFu) + __popc(peers & lt);
        sts16_if(sb + sel(bin == 8, ZL_OFF, sel(bin == 7, YL_OFF, TL_OFF)) + 2 * r, tid, (0x190 >> bin) & 1);
        const uint64_t ones = 0x0001010101010101ull >> (56 - 8 * min(bin, 7u));
        asm volatile("bar.sync 2, 480;" ::: "memory");
        uint32_t h[4];
        lds128(sb + MISC_OFF + 4 * 32, h);
        const int nodd = misc[37], n1 = h[3] >> 16, n3 = h[2] & 0xFFFF, left = max(min(nodd + n3 - n1, n3), 0), half = left >> 1;
        const bool twin = bin == 4 && (int)r < 2 * half;
        x = sel(bin == 4, nodd + r - left, sel(odd, x, 1023));
        const bool pair = twin ? !(r & 1) : (int)x >= (bin == 4 ? nodd : 0) && (int)x < n1;
        const uint32_t y = lds16(sel(twin, sb + TL_OFF + 2 + 2 * r, sb + YL_OFF + 2 * (x & 511)));
        const uint32_t base = __dp2a_lo(h[0], (uint32_t)ones, __dp2a_hi(h[1], (uint32_t)ones, 0u)) +
                              __dp2a_lo(h[2], (uint32_t)(ones >> 32), __dp2a_hi(h[3], (uint32_t)(ones >> 32), 0u));
        r -= sel(bin == 7, nodd + n3, 0);
        const bool unit = (bin < 8 && (int)r >= 0 && (pair || !twin));
        place = sel(unit, base + sel(twin, r >> 1, r - sel(bin < 4, 0, half)), ~0u);
        sts32_if(sb + MISC_OFF + 16, base - half + max(n1 - nodd - n3, 0), bin >= 7);
        steps += twin;
        last = sel(twin, y, tid) | sel(steps > 1, ST_CLOSE, ST_CLOSE | ST_START);
        mid = sel(pair, y | sel(twin, ST_MID, ST_MID | ST_CLOSE) | (tid << 16), last);
        c = sel(pair, c, 2 * steps - 1);
        const uint32_t sa = sb + SLOT_OFF + sel(steps <= ROUNDS, 2 * place, 1278);
        sts64_if(sb + NPOS_OFF + 8 * tid, sa, 0, unit);
        sts64_if(sb + NPOS_OFF + 8 * y, sa, c << 9, pair);
        asm volatile("{\n.reg .pred p;\nsetp.ne.u32 p, %2, 0;\n@p st.shared.u8 [%0], %1;\n}\n" ::"r"(sb + SIZE_OFF + place), "r"(steps), "r"((uint32_t)unit) : "memory");
    } else {
        if (elect()) {
            if (b == 0) p.g->sync[0] = epoch + 1;
            asm volatile("fence.proxy.async.global;" ::: "memory");
            mbar_expect_tx(bar_tab, WIMG + LUTS * 32);
            bulk_g2s(sb, p.g->wimg, WIMG, bar_tab);
            bulk_g2s(sb + LUT_OFF, p.g->wimg + WIMG / 16, LUTS * 32, bar_tab);
        }
        warm(WA + WC, WE);
#pragma unroll 1
        for (uint32_t i = lane; i - lane < 2 * min(misc[1], LUTN - LUTS); i += 32) {
            const uint32_t d = lds32(sb + LUT_OFF + (LUTS + (i >> 1)) * 32);
            __syncwarp();
            reinterpret_cast<uint4*>(smem + LUT_OFF)[2 * LUTS + i] = basis8(__uint_as_float(d), make_uint4(rxy[0], rxy[1], rxy[2], rxy[3]));
        }
        TSX(12, 511);
    }
    __syncthreads();
    TS0(7);
    uint32_t st[4];
    if (warp == 15) {
        uint32_t until0 = lds16(sb + SIZE_OFF + 2 * lane), until1 = until0 >> 8, next = 64, s0, s1;
        const uint32_t nsched = misc[4];
        until0 &= 255;
        uint32_t t = __reduce_min_sync(0xffffffffu, min(until0, until1));
        bool go = true;
#pragma unroll 1
        while (go) {
            go = t < ROUNDS && next < nsched;
            const bool n0 = until0 == t, n1 = until1 == t;
            const uint32_t i = next + __popc(__ballot_sync(0xffffffffu, n0) & lt) + __popc(__ballot_sync(0xffffffffu, n1) & lt), j = i + n0;
            next += __reduce_add_sync(0xffffffffu, n0 + n1);
            asm volatile("{\n.reg .pred p, q;\nsetp.ne.u32 p, %4, 0;\nsetp.ne.u32 q, %5, 0;\nmov.u32 %0, 0;\nmov.u32 %1, 0;\n@p ld.shared.u8 %0, [%2];\n@q ld.shared.u8 %1, [%3];\n}\n"
                         : "=&r"(s0), "=&r"(s1) : "r"(sb + SIZE_OFF + i), "r"(sb + SIZE_OFF + j), "r"((uint32_t)n0), "r"((uint32_t)n1) : "memory");
            until0 += s0;
            until1 += s1;
            sts16_if(sb + SLOT_OFF + 2 * i, 1024 * t + 16 * lane, n0 && until0 <= ROUNDS);
            sts16_if(sb + SLOT_OFF + 2 * j, 1024 * t + 16 * lane + 8, n1 && until1 <= ROUNDS);
            t++;
        }
        until0 = __reduce_max_sync(lane < 16 ? 0xFFFFu : 0xFFFF0000u, max(until0, until1));
        if ((lane & 15) == 0) misc[2 + (lane >> 4)] = until0;
        __syncthreads();
        lds128(sb + MISC_OFF, st);
    } else {
#pragma unroll
        for (int j = 0; j < 4; j++) {
            const uint2 np = *reinterpret_cast<const uint2*>(smem + NPOS_OFF + dn[j]);
            dn[j] = np.x;
            rk[j] += np.y;
        }
#pragma unroll 1
        for (int pass = 0; pass < 2; pass++) {
            uint32_t e[4];
#pragma unroll
            for (int j = 0; j < 4; j++) e[j] = lds16(dn[j]);
            const uint32_t x = lds16(sb + SLOT_OFF + 2 * min(place, 639u));
#pragma unroll
            for (int j = 0; j < 4; j++) {
                sts16_if(sb + SRC_OFF + ((rk[j] + e[j]) >> 2), src[j], e[j] != 0xFFFFu);
                sts64_if(sb + RR_OFF + rk[j] + e[j], rxy[j], gz[j], e[j] != 0xFFFFu);
                if (e[j] != 0xFFFFu) dn[j] = sb + SLOT_OFF + 1278;
            }
            if (pass) {
                const uint32_t nd = sb + ND_OFF + ((x >> 2) & 0xFF00) + ((x >> 1) & 0xFC);
                sts32_if(nd, tid | ST_START, x != 0xFFFFu);
                sts32_if(nd + steps * 256 - 256, last, x != 0xFFFFu && steps <= ROUNDS);
                sts32_if(nd + c * 128 - 128, mid, x != 0xFFFFu && steps <= ROUNDS);
                break;
            }
            asm volatile("bar.sync 2, 480;" ::: "memory");
            if (warp < 8) {
                const int s = lane >> 3, c = lane & 7;
                const uint32_t dst = sb + RING_OFF + warp * 16384 + s * 128, y = sb + SRC_OFF + (warp * 8 + s) * 2;
                const uint32_t sdst = dst + ((c ^ s) << 4), vdst = dst + ((c ^ ((s & 1) << 2)) << 4);
                const uint32_t s0 = lds16(y), s1 = lds16(y + 8), s2 = lds16(y + 128), s3 = lds16(y + 136);
                const char* svl = reinterpret_cast<const char*>(p.sv) + c * 16;
                gather_s(sdst, svl, s0);
                gather_s((sdst ^ 64) + 512, svl, s1);
                gather_s(sdst + 8192, svl, s2);
                gather_s((sdst ^ 64) + 8704, svl, s3);
                cp_async_arrive(bar_full);
                TS0(10);
                __nanosleep(warp & 4 ? P1W : P0);
                gather_v(vdst, svl, s0);
                __nanosleep(P0);
                gather_v(vdst + 512, svl, s1);
                __nanosleep(P0);
                gather_v(vdst + 8192, svl, s2);
                __nanosleep(P0);
                gather_v(vdst + 8704, svl, s3);
                asm volatile("cp.async.mbarrier.arrive.shared::cta.b64 [%0];" ::"r"(bar_side) : "memory");
            }
            __syncthreads();
            TS0(8);
            lds128(sb + MISC_OFF, st);
        }
    }
    __syncthreads();
    if (__builtin_expect(max(st[2], st[3]) > ROUNDS || st[1] > LUTN - LUTS || st[0], 0)) {
        asm volatile("cp.async.wait_all;" ::: "memory");
        mbar_wait(bar_tab, 1);
        mbar_wait(bar_tab + 8, 0);
        cold_nodes(smem, p, nn, tag);
        return;
    }
    TS0(9);
    const int T = __shfl_sync(0xffffffffu, warp & 4 ? st[3] : st[2], 0);

    if (warp < 8) {
        asm volatile("setmaxnreg.inc.sync.aligned.u32 %0;" ::"n"(REG_C));
        const int lane = fresh_lane();
        const int g = lane >> 2, q = lane & 3;
        const uint64_t d0 = (uint64_t)__shfl_sync(0xffffffffu, pin((uint32_t)(p.desc0 >> 32)), 0) << 32 | __shfl_sync(0xffffffffu, pin((uint32_t)p.desc0), 0);
        const uint32_t swz = g * 128 + ((q ^ ((g & 1) << 2)) << 4);
        const uint32_t srow = pin(sb + SIDE_OFF + warp * 4096 + swz);
        uint32_t vrow = pin(sb + RING_OFF + warp * 16384 + swz + 4096);
        uint32_t ent = pin(sb + RR_OFF + (warp * 8 + g) * 8), fent = pin(sb + ND_OFF + (warp * 8 + g) * 4);
        uint32_t lent = pin(sb + RR_OFF + (warp * 8 + (lane & 7)) * 8 + 4 + (lane & 8) * 64);
        const uint32_t lutq = pin(sb + LUT_OFF + (lane >> 4) * 16);
        uint64_t outq;
        {
            const uint64_t a = reinterpret_cast<uint64_t>(p.out) + (size_t)nbase * 512 + q * 16;
            const uint32_t lo = pin((uint32_t)a), hi = pin((uint32_t)(a >> 32));
            asm volatile("mov.b64 %0, {%1, %2};" : "=l"(outq) : "r"(lo), "r"(hi));
        }
        uint32_t acc[32], rf[4], h[16], rr[4], fl = 0;
#pragma unroll
        for (int i = 0; i < 32; i++) asm volatile("" : "=r"(acc[i]));
#pragma unroll
        for (int i = 0; i < 16; i++) asm volatile("" : "=r"(h[i]));
#pragma unroll
        for (int i = 0; i < 4; i++) asm volatile("" : "=r"(rf[i]), "=r"(rr[i]));
        int t = -1;
        TSX(18, 0);
        mbar_wait(bar_tab, 1);
        TSX(14, 0);
        const int Tm = __shfl_sync(0xffffffffu, min(st[2], st[3]), 0);
        if (warp >= 4 && Tm > 0) asm volatile("bar.arrive 3, 256;" ::: "memory");
        bool more = T < 0x7FFFFFFF;
#pragma unroll 1
        while (more) {
            float y[32], p1[32], w1[32], p2[32], w2[32], p3[32], w3[32];
            uint32_t m1[16], m2[16], v[3][16], ts[8];
            auto products = [](uint32_t* m, const float* P, const float* W) {
#pragma unroll
                for (int j = 0; j < 8; j++) {
                    m[j] = pack2(P[4 * j] * W[4 * j], P[4 * j + 1] * W[4 * j + 1]);
                    m[8 + j] = pack2(P[4 * j + 2] * W[4 * j + 2], P[4 * j + 3] * W[4 * j + 3]);
                }
            };
            auto vterm = [&](int k, int o) {
#pragma unroll
                for (int j = 0; j < 8; j++) acc[8 * k + 8 + j] = hfma2(m1[o + j], v[k][o + j], acc[8 * k + 8 + j]);
            };
            auto rterm = [&](int k, int o) {
#pragma unroll
                for (int j = 0; j < 8; j++)
                    acc[8 * k + 8 + j] = k == 0 ? hfma2_lo(m2[o + j], rr[o / 4], acc[8 * k + 8 + j]) : hfma2_hi(m2[o + j], rr[o / 4 + k / 2], acc[8 * k + 8 + j]);
            };
            TR(0, 0, t);
            uint64_t om, op;
#pragma unroll
            for (int j = 0; j < 8; j++) asm volatile("" : "=r"(ts[j]), "=r"(m1[8 + j]), "=r"(m2[8 + j]), "=r"(v[0][8 + j]), "=r"(v[1][8 + j]), "=r"(v[2][8 + j]));
            asm volatile("" : "=l"(om));
            if (t >= 0) {
            TC(0);
            if (t < Tm) asm volatile("bar.sync %0, 256;" ::"r"(3 + (warp >> 2)) : "memory");
            wg_fence();
            wgmma_rs2<W2_OFF + 8192, 8192, 0>(p1, p2, h, d0);
            wgmma_rs2<W2_OFF + 10240, 8192, 1>(p1, p2, h + 4, d0);
            wgmma_rs2<W2_OFF + 12288, 8192, 1>(p1, p2, h + 8, d0);
            wgmma_rs2<W2_OFF + 14336, 8192, 1>(p1, p2, h + 12, d0);
            wgmma_rs2<WR_OFF + 2048, 2048, 0>(w1, w2, rf, d0);
            wg_commit();
            TC(1);
            mbar_wait(bar_side, t & 1);
            TC(2);
#pragma unroll
            for (int k = 0; k < 4; k++) lds2_if(srow + 1024 * k, (srow ^ 64) + 1024 * k, acc + 8 * k, fl & ST_START);
            wg_wait<0>();
            fence_regs(p1); fence_regs(w1);
            TC(3);
            products(m1, p1, w1);
#pragma unroll
            for (int k = 0; k < 3; k++) { lds128(vrow + 1024 + 1024 * k, v[k]); lds128((vrow ^ 64) + 1024 + 1024 * k, v[k] + 4); }
            fence_regs(p2); fence_regs(w2);
            products(m2, p2, w2);
            asm("mad.wide.u32 %0, %1, 512, %2;" : "=l"(om) : "r"(fl >> 16), "l"(outq));
#pragma unroll
            for (int k = 0; k < 3; k++) { lds128(vrow + 9216 + 1024 * k, v[k] + 8); lds128((vrow ^ 64) + 9216 + 1024 * k, v[k] + 12); }
#pragma unroll
            for (int j = 0; j < 8; j++) asm volatile("" : "=r"(ts[j]));
            lds2_if(srow, srow ^ 64, ts, fl & ST_MID);
#pragma unroll
            for (int k = 0; k < 3; k++) { vterm(k, 0); rterm(k, 0); stg2_if(om + 128 + 128 * k, acc + 8 + 8 * k, fl & ST_MID); }
            TC(4);
            if (t + (warp >> 2) < Tm) asm volatile("bar.arrive %0, 256;" ::"r"(4 - (warp >> 2)) : "memory");
            }
            t++;
            wg_fence();
            wgmma_group<0>(p3, w3, h, rf, d0);
            wg_commit();
            if (T > 1000000) asm volatile("nanosleep.u32 0;");
#pragma unroll
            for (int k = 1; k < 4; k++) lds2_if(srow + 1024 * k, (srow ^ 64) + 1024 * k, acc + 8 * k, fl & ST_MID);
            uint32_t lo;
            asm volatile("ld.shared.u16 %0, [%1];" : "=r"(lo) : "r"(lent) : "memory");
            __syncwarp();
            if (lane == 0 && t > 0) mbar_arrive(bar_empty);
            if (t > 0) TC(5);
            if (t >= T) {
                asm("mad.wide.u32 %0, %1, 512, %2;" : "=l"(op) : "r"(fl & 511), "l"(outq));
#pragma unroll
                for (int k = 0; k < 3; k++) { vterm(k, 8); rterm(k, 8); stg2_if(op + 128 + 128 * k, acc + 8 + 8 * k, fl & ST_CLOSE); }
                wg_wait<0>();
                fence_regs(p3); fence_regs(w3);
                products(m1, p3, w3);
#pragma unroll
                for (int j = 0; j < 8; j++) acc[j] = hadd2(acc[j], m1[j]);
                stg2_if(om, acc, fl & ST_MID);
#pragma unroll
                for (int j = 0; j < 8; j++) acc[j] = hadd2(fl & ST_MID ? ts[j] : acc[j], m1[8 + j]);
                stg2_if(op, acc, fl & ST_CLOSE);
                asm volatile("cp.async.wait_all;" ::: "memory");
                break;
            }
            mbar_wait(bar_full + 8 * (t & 1), (t >> 1) & 1);
            if (t > 0) TC(6);
            wg_fence();
            wgmma_ss_k64(y, d0 + ((RING_OFF >> 4) + (warp >> 2) * 4096 + (t & 1) * 256 + ((uint64_t)(512 - 64) << 32)), d0);
            wg_commit();
            if (T > 1000000) asm volatile("nanosleep.u32 0;");
            asm("mad.wide.u32 %0, %1, 512, %2;" : "=l"(op) : "r"(fl & 511), "l"(outq));
            vrow ^= 4096;
#pragma unroll
            for (int k = 0; k < 3; k++) vterm(k, 8);
#define BBS if (T > 1000000) asm volatile("nanosleep.u32 0;")
            auto silu = [&](int i0, int i1) {
#pragma unroll
                for (int i = i0; i < i1; i++)
                    h[i] = pack2(fmaf(y[2 * i], tanh_fast(y[2 * i]), y[2 * i]), fmaf(y[2 * i + 1], tanh_fast(y[2 * i + 1]), y[2 * i + 1]));
            };
#pragma unroll
            for (int k = 0; k < 3; k++) rterm(k, 8);
            const uint32_t fo = fl;
            asm volatile("ld.shared.v2.u32 {%0,%1}, [%4];\nld.shared.v2.u32 {%2,%3}, [%4 + 512];" : "=r"(rr[0]), "=r"(rr[1]), "=r"(rr[2]), "=r"(rr[3]) : "r"(ent) : "memory");
            asm volatile("ld.shared.u32 %0, [%1];" : "=r"(fl) : "r"(fent) : "memory");
            stg2_if(op + 128, acc + 8, fo & ST_CLOSE);
            BBS;
            if (t > 0) TC(7);
            wg_wait<0>();
            fence_regs(p3); fence_regs(w3); fence_regs(y);
            if (t > 0) TC(8);
            ldsm4(lutq + lo, rf);
            products(m1, p3, w3);
            silu(0, 6);
            stg2_if(op + 256, acc + 16, fo & ST_CLOSE);
            BBS;
#pragma unroll
            for (int j = 0; j < 8; j++) acc[j] = hadd2(acc[j], m1[j]);
            stg2_if(om, acc, fo & ST_MID);
#pragma unroll
            for (int j = 0; j < 8; j++) acc[j] = hadd2(fo & ST_MID ? ts[j] : acc[j], m1[8 + j]);
            silu(6, 11);
            stg2_if(op + 384, acc + 24, fo & ST_CLOSE);
            BBS;
            silu(11, 16);
            stg2_if(op, acc, fo & ST_CLOSE);
            ent += 1024; fent += 256; lent += 1024;
        }
        TSX(15, 0);
        TSX(16, 128);
    } else {
        asm volatile("setmaxnreg.dec.sync.aligned.u32 %0;" ::"n"(256 - REG_C));
        const int lane = fresh_lane();
        const int w = warp - 8, s = lane >> 3, c = lane & 7, nzero = misc[36] & 0xFFFF;
        uint32_t sdst = sb + RING_OFF + w * 16384 + s * 128 + ((c ^ s) << 4);
        const uint32_t sw = s * 128 + ((c ^ ((s & 1) << 2)) << 4);
        uint32_t vdst = sb + RING_OFF + w * 16384 + sw;
        const uint32_t odst = sb + SIDE_OFF + w * 4096 + sw;
        uint32_t ent = sb + ND_OFF + (w * 8 + s) * 4;
        const char* svl = reinterpret_cast<const char*>(p.sv) + c * 16;
        const char* own = svl + (size_t)nbase * 512;
        __nanosleep((warp & 4 ? LAG1 : 0) + LAG * max(min(16 - (int)(misc[2] + misc[3]), 3), 0));
#pragma unroll 1
        for (int t = 1; t <= T; t++) {
            const uint32_t e = sb + SRC_OFF + t * 256 + (w * 8 + s) * 2;
            const uint32_t s0 = lds16(e), s1 = lds16(e + 8), s2 = lds16(e + 128), s3 = lds16(e + 136);
            const uint32_t f0 = lds32(ent), f1 = lds32(ent + 16);
            ent += 256;
            sdst ^= 4096; vdst ^= 4096;
            TR(5, 256, t);
            mbar_wait(bar_empty, t & 1);
            TR(6, 256, t);
            gather_row_if(odst, own + (f0 & 511) * 512, f0 & (ST_START | ST_MID));
            gather_row_if(odst + 512, own + (f1 & 511) * 512, f1 & (ST_START | ST_MID));
            cp_async_arrive(bar_side);
            if (t == T) break;
            gather_s(sdst, svl, s0);
            gather_s((sdst ^ 64) + 512, svl, s1);
            gather_s(sdst + 8192, svl, s2);
            gather_s((sdst ^ 64) + 8704, svl, s3);
            cp_async_arrive(bar_full + 8 * (t & 1));
            gather_v(vdst, svl, s0);
            gather_v(vdst + 512, svl, s1);
            gather_v(vdst + 8192, svl, s2);
            gather_v(vdst + 8704, svl, s3);
            TR(7, 256, t);
        }
        TSX(17, 256);
        TSX(20, 384);
        const uint32_t rb = sb + RING_OFF + w * 16384 + (max(T, 1) & 1) * 4096 + s * 512 + c * 16;
#pragma unroll 1
        for (int z = (w & 3) + ((w >> 2) == (misc[2] > misc[3]) ? 0 : 48); z < nzero; z += 96) {
            const int n = (nzero - z + 3) >> 2;
            uint32_t zn[3];
#pragma unroll
            for (int i = 0; i < 3; i++) zn[i] = lds16(sb + ZL_OFF + 2 * min(z + 16 * i + 4 * s, 511));
#pragma unroll
            for (int i = 0; i < 3; i++)
                asm volatile("{\n.reg .pred p;\nsetp.lt.s32 p, %2, %3;\n@p cp.async.cg.shared.global [%0], [%1], 16;\n@p cp.async.cg.shared.global [%0 + 128], [%1 + 128], 16;\n"
                             "@p cp.async.cg.shared.global [%0 + 256], [%1 + 256], 16;\n@p cp.async.cg.shared.global [%0 + 384], [%1 + 384], 16;\n}\n"
                             ::"r"(rb + (i & 1) * 2048 + (i >> 1) * 8192), "l"(own + zn[i] * 512), "r"(4 * i + s), "r"(n) : "memory");
            TSX(21, 256);
            asm volatile("cp.async.wait_all;" ::: "memory");
            TSX(22, 256);
#pragma unroll
            for (int i = 0; i < 3; i++) {
                if (4 * i < n) {
                    char* dst = reinterpret_cast<char*>(p.out) + (size_t)(nbase + zn[i]) * 512 + c * 16;
#pragma unroll
                    for (int k = 0; k < 4; k += 2) {
                        uint32_t x[8];
                        lds128(rb + (i & 1) * 2048 + (i >> 1) * 8192 + k * 128, x);
                        lds128(rb + (i & 1) * 2048 + (i >> 1) * 8192 + k * 128 + 128, x + 4);
                        if (4 * i + s < n) {
                            __stcs(reinterpret_cast<uint4*>(dst + k * 128), make_uint4(x[0], x[1], x[2], x[3]));
                            __stcs(reinterpret_cast<uint4*>(dst + k * 128 + 128), make_uint4(x[4], x[5], x[6], x[7]));
                        }
                    }
                }
            }
        }
        mbar_wait(bar_tab + 8, 0);
        TSX(11, 256);
        TSX(19, 384);
    }
}

}

extern "C" void kernel_launch(void* const* d_in, const int* in_sizes, int n_in, void* d_out, int out_size) {
    static int s_G = 0;
    static void* s_scratch = nullptr;
    static void* s_encode = nullptr;
    const int N = in_sizes[0] / 256, E = in_sizes[2];
    if (s_G == 0) {
        cudaFuncSetAttribute(painn_kernel<0, 0, 0>, cudaFuncAttributeMaxDynamicSharedMemorySize, SMEM_BYTES);
        cudaFuncSetAttribute(painn_kernel<50000, 800000, 132>, cudaFuncAttributeMaxDynamicSharedMemorySize, SMEM_BYTES);
        int dev = 0, sms = 0, occ = 0;
        cudaGetDevice(&dev);
        cudaDeviceGetAttribute(&sms, cudaDevAttrMultiProcessorCount, dev);
        cudaOccupancyMaxActiveBlocksPerMultiprocessor(&occ, painn_kernel<0, 0, 0>, THREADS, SMEM_BYTES);
        cudaGetSymbolAddress(&s_scratch, g_scratch);
        cudaDriverEntryPointQueryResult qr;
        cudaGetDriverEntryPoint("cuTensorMapEncodeTiled", &s_encode, cudaEnableDefault, &qr);
        s_G = occ >= 1 ? (sms < MAXG ? sms : MAXG) : 0;
    }
    if (s_G == 0 || N > TABLE_MAXN || N > s_G * (MAXNPC - 1) || (s_G - 1) * ((N + s_G - 1) / s_G) >= N || E > MAXE || E < 4 * MAXG * MAXG) return;
    Params p;
    {
        typedef CUresult (*Encode)(CUtensorMap*, CUtensorMapDataType, cuuint32_t, void*, const cuuint64_t*, const cuuint64_t*, const cuuint32_t*,
                                   const cuuint32_t*, CUtensorMapInterleave, CUtensorMapSwizzle, CUtensorMapL2promotion, CUtensorMapFloatOOBfill);
        const cuuint64_t dims[2] = {64, (cuuint64_t)N * 4}, strides[1] = {128};
        const cuuint32_t box[2] = {8, 32}, es[2] = {1, 1};
        ((Encode)s_encode)(&p.tm, CU_TENSOR_MAP_DATA_TYPE_BFLOAT16, 2, d_in[0], dims, strides, box, es, CU_TENSOR_MAP_INTERLEAVE_NONE,
                           CU_TENSOR_MAP_SWIZZLE_NONE, CU_TENSOR_MAP_L2_PROMOTION_L2_128B, CU_TENSOR_MAP_FLOAT_OOB_FILL_NONE);
    }
    p.g = (Scratch*)s_scratch;
    p.sv = (const __nv_bfloat16*)d_in[0];
    p.pos = (const __nv_bfloat16*)d_in[1];
    p.src = (const int*)d_in[2];
    p.dst = (const int*)d_in[3];
    p.freqs = (const __nv_bfloat16*)d_in[4];
    p.w1 = (const __nv_bfloat16*)d_in[5];
    p.w2 = (const __nv_bfloat16*)d_in[6];
    p.wr = (const __nv_bfloat16*)d_in[7];
    p.out = (__nv_bfloat16*)d_out;
    p.desc0 = (uint64_t)(SB >> 4) | ((uint64_t)1 << 16) | ((uint64_t)64 << 32) | ((uint64_t)1 << 62);
    p.N = N; p.E = E; p.G = s_G;
    p.NPC = (N + s_G - 1) / s_G;
    p.magic = (uint32_t)(((1ull << 32) + p.NPC - 1) / p.NPC);
    p.gpc = ((E >> 2) + s_G - 1) / s_G;
    p.odd_edges = (E & 3) != 0 || p.gpc > 3 * THREADS;
    if (N == 50000 && E == 800000 && s_G == 132) painn_kernel<50000, 800000, 132><<<s_G, THREADS, SMEM_BYTES, cudaStreamPerThread>>>(p);
    else painn_kernel<0, 0, 0><<<s_G, THREADS, SMEM_BYTES, cudaStreamPerThread>>>(p);
}
```

```cpp
#include <cuda_runtime.h>
#include <cuda_bf16.h>
#include <cuda.h>
#include <stdint.h>

namespace {

constexpr int REG_C = 224;
constexpr int PDELAY = 120;
constexpr int WA = 7, WC = 3, WE = 3;
constexpr int P0 = 80, P1W = 200;
constexpr int LAG = 400, LAG1 = 700;
#define NP 8
#define NLEFT 4
#define CLR 1
constexpr int THREADS = 512;
constexpr int MAXG = 136;
constexpr int ROUNDS = 11;
constexpr int LUTS = 286, LUTN = 318;
constexpr int MAXNPC = 480;
constexpr int MAXE = 1 << 20;

constexpr int W2_OFF = 8192;
constexpr int WR_OFF = 32768;
constexpr int WIMG = 38912;
constexpr int ZL_OFF = WIMG;
constexpr int RING_OFF = 39936;
constexpr int SIDE_OFF = RING_OFF + 16 * 8192;
constexpr int RR_OFF = SIDE_OFF + 32768;
constexpr int ND_OFF = RR_OFF + ROUNDS * 1024;
constexpr int SRC_OFF = ND_OFF + ROUNDS * 256;
constexpr int LUT_OFF = SRC_OFF + ROUNDS * 256;
constexpr int SINK_OFF = LUT_OFF + 320 * 32;
constexpr int BAR_OFF = SINK_OFF + 512;
constexpr int MISC_OFF = BAR_OFF + 8 * 46;
constexpr int SMEM_BYTES = MISC_OFF + 192 + MAXG;
constexpr int PITCH = 144;
constexpr int TABLE_MAXN = 50176;
constexpr int STAGE_OFF = TABLE_MAXN * 4;
constexpr int SCNT_OFF = STAGE_OFF + MAXG * PITCH;
constexpr int OVL_OFF = MISC_OFF + 192;
constexpr int OPOS_OFF = LUT_OFF + 1024;
constexpr int NCNT_OFF = SIDE_OFF;
constexpr int NPOS_OFF = NCNT_OFF + 2048;
constexpr int YL_OFF = NPOS_OFF + 4096;
constexpr int TL_OFF = YL_OFF + 1024;
constexpr int SLOT_OFF = TL_OFF + 1024;
constexpr int SIZE_OFF = SLOT_OFF + 1280;
static_assert(SCNT_OFF + 4 * (MAXG + 32) <= OPOS_OFF && OPOS_OFF + 4096 <= LUT_OFF + LUTS * 32, "smem map");
static_assert(2 * (480 - 3 * MAXG) >= MAXG, "chunk map");
static_assert(SMEM_BYTES <= 232448 && MISC_OFF % 16 == 0 && BAR_OFF % 8 == 0 && (RING_OFF + 1024) % 8192 == 0 && SINK_OFF % 128 == 0, "smem map");

constexpr uint32_t PAY_INVALID = 0x3FFFFFFu;
constexpr uint32_t PAY_MARK = 0x3FFFDFFu;
constexpr uint32_t ST_START = 512, ST_CLOSE = 1024, ST_MID = 2048;
constexpr float QINVP = 9.0f / 510.0f;
constexpr uint32_t QTHRESH = 2126;

struct Scratch {
    unsigned sync[32];
    uint4 table[TABLE_MAXN / 4];
    uint4 wimg[WIMG / 16 + LUTS * 2];
    uint2 pos8[TABLE_MAXN];
    uint4 xbuf[MAXG * MAXG * 8 + 3 * THREADS];
    int ovfcnt[MAXG];
    int2 ovf[MAXE + 8 * MAXG + 8];
};
__device__ __align__(128) Scratch g_scratch;

struct Params {
    const __nv_bfloat16* pos;
    Scratch* g;
    const int* src;
    const int* dst;
    int N, NPC, E, gpc;
    const __nv_bfloat16* w2;
    const __nv_bfloat16* wr;
    const __nv_bfloat16* w1;
    const __nv_bfloat16* freqs;
    const __nv_bfloat16* sv;
    __nv_bfloat16* out;
    uint64_t desc0;
    int G;
    uint32_t magic;
    int odd_edges;
};
constexpr uint32_t SB = 1024;

#define TSX(i, thr)
#define TR(k, thr, t)
#define TC(k)
#define TS0(i) TSX(i, 0)

__device__ __forceinline__ uint32_t smem_u32(const void* p) { return (uint32_t)__cvta_generic_to_shared(p); }
__device__ __forceinline__ void mbar_init(uint32_t bar, uint32_t cnt) {
    asm volatile("mbarrier.init.shared::cta.b64 [%0], %1;" ::"r"(bar), "r"(cnt) : "memory");
}
__device__ __forceinline__ void mbar_arrive(uint32_t bar) {
    asm volatile("mbarrier.arrive.shared::cta.b64 _, [%0];" ::"r"(bar) : "memory");
}
__device__ __forceinline__ void mbar_expect_tx(uint32_t bar, uint32_t bytes) {
    asm volatile("mbarrier.arrive.expect_tx.shared::cta.b64 _, [%0], %1;" ::"r"(bar), "r"(bytes) : "memory");
}
__device__ __forceinline__ void mbar_wait(uint32_t bar, uint32_t parity) {
    asm volatile("{\n.reg .pred p;\n.reg .u32 c;\nmbarrier.try_wait.parity.shared::cta.b64 p, [%0], %1;\n@p bra DONE;\nmov.u32 c, 0;\n"
                 "AGAIN:\nmbarrier.try_wait.parity.shared::cta.b64 p, [%0], %1, 2000;\n@p bra DONE;\nadd.u32 c, c, 1;\n"
                 "setp.lt.u32 p, c, 0x100000;\n@p bra AGAIN;\ntrap;\nDONE:\n}\n" ::"r"(bar), "r"(parity) : "memory");
}
__device__ __forceinline__ bool elect() {
    uint32_t r;
    asm volatile("{\n.reg .pred p;\nelect.sync _|p, 0xffffffff;\nselp.u32 %0, 1, 0, p;\n}\n" : "=r"(r));
    return r;
}
__device__ __forceinline__ uint32_t pin(uint32_t x) {
    uint32_t r;
    asm volatile("shfl.sync.bfly.b32 %0, %1, 0, 31, -1;" : "=r"(r) : "r"(x));
    return r;
}
__device__ __forceinline__ void bulk_g2s(uint32_t dst, const void* src, uint32_t bytes, uint32_t bar) {
    asm volatile("cp.async.bulk.shared::cluster.global.mbarrier::complete_tx::bytes [%0], [%1], %2, [%3];"
                 ::"r"(dst), "l"(src), "r"(bytes), "r"(bar) : "memory");
}
__device__ __forceinline__ void ldsm4(uint32_t addr, uint32_t* r) {
    asm volatile("ldmatrix.sync.aligned.m8n8.x4.shared.b16 {%0,%1,%2,%3}, [%4];"
                 : "=r"(r[0]), "=r"(r[1]), "=r"(r[2]), "=r"(r[3]) : "r"(addr) : "memory");
}
__device__ __forceinline__ uint32_t pack2(float lo, float hi) {
    uint32_t r;
    asm("cvt.rn.bf16x2.f32 %0, %1, %2;" : "=r"(r) : "f"(hi), "f"(lo));
    return r;
}
__device__ __forceinline__ float bf_lo(uint32_t w) { return __uint_as_float(w << 16); }
__device__ __forceinline__ float bf_hi(uint32_t w) { return __uint_as_float(w & 0xFFFF0000u); }
__device__ __forceinline__ float rbf16(float x) { return __uint_as_float(pack2(0.f, x)); }
__device__ __forceinline__ uint32_t hmul2(uint32_t a, uint32_t b) {
    uint32_t r;
    asm("mul.rn.bf16x2 %0, %1, %2;" : "=r"(r) : "r"(a), "r"(b));
    return r;
}
__device__ __forceinline__ uint32_t hfma2(uint32_t a, uint32_t b, uint32_t c) {
    uint32_t r;
    asm("fma.rn.bf16x2 %0, %1, %2, %3;" : "=r"(r) : "r"(a), "r"(b), "r"(c));
    return r;
}
__device__ __forceinline__ uint32_t hfma2_lo(uint32_t a, uint32_t b, uint32_t c) {
    uint32_t r;
    asm("{\n.reg .b16 l, h;\n.reg .b32 t;\nmov.b32 {l, h}, %2;\nmov.b32 t, {l, l};\nfma.rn.bf16x2 %0, %1, t, %3;\n}\n" : "=r"(r) : "r"(a), "r"(b), "r"(c));
    return r;
}
__device__ __forceinline__ uint32_t hfma2_hi(uint32_t a, uint32_t b, uint32_t c) {
    uint32_t r;
    asm("{\n.reg .b16 l, h;\n.reg .b32 t;\nmov.b32 {l, h}, %2;\nmov.b32 t, {h, h};\nfma.rn.bf16x2 %0, %1, t, %3;\n}\n" : "=r"(r) : "r"(a), "r"(b), "r"(c));
    return r;
}
__device__ __forceinline__ uint32_t hadd2(uint32_t a, uint32_t b) {
    uint32_t r;
    asm("add.rn.bf16x2 %0, %1, %2;" : "=r"(r) : "r"(a), "r"(b));
    return r;
}
__device__ __forceinline__ uint32_t hsub2(uint32_t a, uint32_t b) {
    uint32_t r;
    asm("sub.rn.bf16x2 %0, %1, %2;" : "=r"(r) : "r"(a), "r"(b));
    return r;
}
__device__ __forceinline__ void cp_async_arrive(uint32_t bar) {
    asm volatile("cp.async.mbarrier.arrive.noinc.shared::cta.b64 [%0];" ::"r"(bar) : "memory");
}
__device__ __forceinline__ float tanh_fast(float x) {
    float r;
    asm("tanh.approx.f32 %0, %1;" : "=f"(r) : "f"(x));
    return r;
}
__device__ __forceinline__ void wg_fence() { asm volatile("wgmma.fence.sync.aligned;" ::: "memory"); }
__device__ __forceinline__ void wg_commit() { asm volatile("wgmma.commit_group.sync.aligned;" ::: "memory"); }
template <int N>
__device__ __forceinline__ void wg_wait() { asm volatile("wgmma.wait_group.sync.aligned %0;" ::"n"(N) : "memory"); }

#define WG_REGS "{%0,%1,%2,%3,%4,%5,%6,%7,%8,%9,%10,%11,%12,%13,%14,%15,%16,%17,%18,%19,%20,%21,%22,%23,%24,%25,%26,%27,%28,%29,%30,%31}"
#define WG_OPS(c) c(d[0]), c(d[1]), c(d[2]), c(d[3]), c(d[4]), c(d[5]), c(d[6]), c(d[7]), c(d[8]), c(d[9]), c(d[10]), \
    c(d[11]), c(d[12]), c(d[13]), c(d[14]), c(d[15]), c(d[16]), c(d[17]), c(d[18]), c(d[19]), c(d[20]), c(d[21]),     \
    c(d[22]), c(d[23]), c(d[24]), c(d[25]), c(d[26]), c(d[27]), c(d[28]), c(d[29]), c(d[30]), c(d[31])
#define WG_OPSE(c) c(e[0]), c(e[1]), c(e[2]), c(e[3]), c(e[4]), c(e[5]), c(e[6]), c(e[7]), c(e[8]), c(e[9]), c(e[10]), c(e[11]), c(e[12]), c(e[13]), c(e[14]), c(e[15]), c(e[16]), c(e[17]), c(e[18]), c(e[19]), c(e[20]), c(e[21]), c(e[22]), c(e[23]), c(e[24]), c(e[25]), c(e[26]), c(e[27]), c(e[28]), c(e[29]), c(e[30]), c(e[31])
template <int OFF, int ACC, int IDX>
__device__ __forceinline__ void wgmma_rs(float* d, const uint32_t* a, uint64_t d0) {
    if (!ACC) {
#pragma unroll
        for (int i = 0; i < 32; i++) d[i] = 0.f;
    }
    if (IDX < 4)
        asm volatile("wgmma.mma_async.sync.aligned.m64n64k16.f32.bf16.bf16 " WG_REGS ", {%32,%33,%34,%35}, %36, %37, 1, 1, 1;"
                     : WG_OPS("+f") : "r"(a[0]), "r"(a[1]), "r"(a[2]), "r"(a[3]), "l"(d0 + (OFF >> 4)), "n"(ACC));
    else
        asm volatile("{\n.reg .b64 dd;\nmov.b64 dd, {%36, 0x40000040};\nwgmma.mma_async.sync.aligned.m64n64k16.f32.bf16.bf16 " WG_REGS
                     ", {%32,%33,%34,%35}, dd, %37, 1, 1, 1;\n}\n"
                     : WG_OPS("+f") : "r"(a[0]), "r"(a[1]), "r"(a[2]), "r"(a[3]), "n"(((SB + OFF) >> 4) | (1u << 16)), "n"(ACC));
}
template <int OFF, int LBO, int ACC>
__device__ __forceinline__ void wgmma_rs2(float* d, float* e, const uint32_t* a, uint64_t d0) {
    if (!ACC) {
#pragma unroll
        for (int i = 0; i < 32; i++) d[i] = e[i] = 0.f;
    }
    asm volatile("wgmma.mma_async.sync.aligned.m64n128k16.f32.bf16.bf16 {%0,%1,%2,%3,%4,%5,%6,%7,%8,%9,%10,%11,%12,%13,%14,%15,%16,%17,%18,%19,%20,%21,%22,%23,%24,%25,%26,%27,%28,%29,%30,%31,%32,%33,%34,%35,%36,%37,%38,%39,%40,%41,%42,%43,%44,%45,%46,%47,%48,%49,%50,%51,%52,%53,%54,%55,%56,%57,%58,%59,%60,%61,%62,%63}, {%64,%65,%66,%67}, %68, %69, 1, 1, 1;"
                 : WG_OPS("+f"), WG_OPSE("+f") : "r"(a[0]), "r"(a[1]), "r"(a[2]), "r"(a[3]), "l"(d0 + (OFF >> 4) + ((LBO / 16 - 1) << 16)), "n"(ACC));
}
template <int G>
__device__ __forceinline__ void wgmma_group(float* P, float* W, const uint32_t* h, const uint32_t* rf, uint64_t d0) {
    wgmma_rs<W2_OFF + 8192 * G, 0, 5 * G>(P, h, d0);
    wgmma_rs<W2_OFF + 8192 * G + 2048, 1, 5 * G + 1>(P, h + 4, d0);
    wgmma_rs<W2_OFF + 8192 * G + 4096, 1, 5 * G + 2>(P, h + 8, d0);
    wgmma_rs<W2_OFF + 8192 * G + 6144, 1, 5 * G + 3>(P, h + 12, d0);
    wgmma_rs<WR_OFF + 2048 * G, 0, 5 * G + 4>(W, rf, d0);
}
__device__ __forceinline__ void wgmma_ss_k64(float* d, uint64_t da, uint64_t db) {
#pragma unroll
    for (int i = 0; i < 32; i++) d[i] = 0.f;
    asm volatile("wgmma.mma_async.sync.aligned.m64n64k16.f32.bf16.bf16 " WG_REGS ", %32, %33, 0, 1, 1, 0, 1;" : WG_OPS("+f") : "l"(da), "l"(db));
#pragma unroll
    for (int k = 1; k < 4; k++)
        asm volatile("wgmma.mma_async.sync.aligned.m64n64k16.f32.bf16.bf16 " WG_REGS ", %32, %33, 1, 1, 1, 0, 1;"
                     : WG_OPS("+f") : "l"(da + 2 * k), "l"(db + 128 * k));
}
__device__ __forceinline__ void fence_regs(float* d) { asm volatile("" : WG_OPS("+f")::"memory"); }
__device__ __forceinline__ uint32_t qaxis(float x) {
    const float u = fmaf(x, QINVP, 0.25f);
    const float f = u - ((u + 12582912.f) - 12582912.f);
    return __float_as_uint(fmaf(fabsf(f), 510.f, 12582912.f));
}
__device__ __forceinline__ uint32_t qcode(float x, float y, float z, uint32_t tx) {
    return __byte_perm(__byte_perm(qaxis(x), qaxis(y), 0x3340), qaxis(z), 0x3410) ^ tx;
}
__device__ __forceinline__ bool near_test(uint32_t ca, uint32_t cb, uint32_t tag24) {
    const uint32_t D = __vabsdiffu4(ca, cb);
    return __dp4a(D, D, 0u) <= QTHRESH || ((ca ^ tag24) | (cb ^ tag24)) >= 0x1000000u;
}
constexpr float QMAX = 23.9375f;
__device__ __forceinline__ float square(uint32_t rxy, uint32_t rz) {
    const uint32_t qxy = hmul2(rxy, rxy), qz = hmul2(rz, rz);
    return bf_lo(qxy) + bf_hi(qxy) + bf_lo(qz);
}

__device__ __forceinline__ uint32_t lds32(uint32_t addr) {
    uint32_t r;
    asm volatile("ld.shared.u32 %0, [%1];" : "=r"(r) : "r"(addr) : "memory");
    return r;
}
__device__ __forceinline__ void sts32_if(uint32_t addr, uint32_t v, bool c) {
    asm volatile("{\n.reg .pred p;\nsetp.ne.u32 p, %2, 0;\n@p st.shared.u32 [%0], %1;\n}\n" ::"r"(addr), "r"(v), "r"((uint32_t)c) : "memory");
}
__device__ __forceinline__ uint32_t sel(bool c, uint32_t a, uint32_t b) {
    uint32_t r;
    asm("{\n.reg .pred p;\nsetp.ne.u32 p, %3, 0;\nselp.b32 %0, %1, %2, p;\n}\n" : "=r"(r) : "r"(a), "r"(b), "r"((uint32_t)c));
    return r;
}
__device__ __forceinline__ uint32_t lds16(uint32_t addr) {
    uint32_t r;
    asm volatile("ld.shared.u16 %0, [%1];" : "=r"(r) : "r"(addr) : "memory");
    return r;
}
__device__ __forceinline__ void sts16_if(uint32_t addr, uint32_t v, bool c) {
    asm volatile("{\n.reg .pred p;\nsetp.ne.u32 p, %2, 0;\n@p st.shared.u16 [%0], %1;\n}\n" ::"r"(addr), "h"((unsigned short)v), "r"((uint32_t)c) : "memory");
}
__device__ __forceinline__ void sts64_if(uint32_t addr, uint32_t x, uint32_t y, bool c) {
    asm volatile("{\n.reg .pred p;\nsetp.ne.u32 p, %3, 0;\n@p st.shared.v2.u32 [%0], {%1, %2};\n}\n" ::"r"(addr), "r"(x), "r"(y), "r"((uint32_t)c) : "memory");
}
__device__ __forceinline__ uint32_t atoms_add(uint32_t addr, uint32_t v) {
    uint32_t r;
    asm volatile("atom.shared.add.u32 %0, [%1], %2;" : "=r"(r) : "r"(addr), "r"(v) : "memory");
    return r;
}
__device__ __forceinline__ void stg128_if(void* ptr, uint4 v, bool c) {
    asm volatile("{\n.reg .pred p;\nsetp.ne.u32 p, %5, 0;\n@p st.relaxed.gpu.global.v4.u32 [%0], {%1,%2,%3,%4};\n}\n"
                 ::"l"(ptr), "r"(v.x), "r"(v.y), "r"(v.z), "r"(v.w), "r"((uint32_t)c) : "memory");
}
__device__ __forceinline__ void lds128(uint32_t addr, uint32_t* r) {
    asm volatile("ld.shared.v4.u32 {%0,%1,%2,%3}, [%4];" : "=r"(r[0]), "=r"(r[1]), "=r"(r[2]), "=r"(r[3]) : "r"(addr) : "memory");
}
__device__ __forceinline__ void stg2_if(uint64_t ptr, const uint32_t* r, uint32_t c) {
    asm volatile("{\n.reg .pred p;\nsetp.ne.u32 p, %9, 0;\n@p st.global.cs.v4.u32 [%8], {%0,%1,%2,%3};\n"
                 "@p st.global.cs.v4.u32 [%8 + 64], {%4,%5,%6,%7};\n}\n"
                 ::"r"(r[0]), "r"(r[1]), "r"(r[2]), "r"(r[3]), "r"(r[4]), "r"(r[5]), "r"(r[6]), "r"(r[7]), "l"(ptr), "r"(c) : "memory");
}
__device__ __forceinline__ void gather_s(uint32_t dst, const char* base, uint32_t src) {
    asm volatile("{\n.reg .pred p;\nsetp.eq.u32 p, %2, 0xFFFF;\ncp.async.cg.shared.global [%0], [%1], 16, p;\n}\n"
                 ::"r"(dst), "l"(base + (size_t)src * 512), "r"(src) : "memory");
}
__device__ __forceinline__ void gather_v(uint32_t dst, const char* base, uint32_t src) {
    asm volatile("{\n.reg .pred p;\nsetp.eq.u32 p, %2, 0xFFFF;\n"
                 "cp.async.cg.shared.global [%0 + 1024], [%1 + 128], 16, p;\ncp.async.cg.shared.global [%0 + 2048], [%1 + 256], 16, p;\n"
                 "cp.async.cg.shared.global [%0 + 3072], [%1 + 384], 16, p;\n}\n" ::"r"(dst), "l"(base + (size_t)src * 512), "r"(src) : "memory");
}
__device__ __forceinline__ void gather_row_if(uint32_t dst, const char* src, uint32_t c) {
    asm volatile("{\n.reg .pred p;\nsetp.ne.u32 p, %2, 0;\n@p cp.async.cg.shared.global [%0], [%1], 16;\n"
                 "@p cp.async.cg.shared.global [%0 + 1024], [%1 + 128], 16;\n@p cp.async.cg.shared.global [%0 + 2048], [%1 + 256], 16;\n"
                 "@p cp.async.cg.shared.global [%0 + 3072], [%1 + 384], 16;\n}\n" ::"r"(dst), "l"(src), "r"(c) : "memory");
}
__device__ __forceinline__ void lds2_if(uint32_t a0, uint32_t a1, uint32_t* r, uint32_t c) {
    asm volatile("{\n.reg .pred p;\nsetp.ne.u32 p, %10, 0;\n@p ld.shared.v4.u32 {%0,%1,%2,%3}, [%8];\n@p ld.shared.v4.u32 {%4,%5,%6,%7}, [%9];\n}\n"
                 : "+r"(r[0]), "+r"(r[1]), "+r"(r[2]), "+r"(r[3]), "+r"(r[4]), "+r"(r[5]), "+r"(r[6]), "+r"(r[7])
                 : "r"(a0), "r"(a1), "r"(c) : "memory");
}
__device__ __forceinline__ int fresh_lane() {
    int l;
    asm volatile("mov.u32 %0, %%laneid;" : "=r"(l));
    return l;
}

__device__ __forceinline__ void cold_edges(unsigned char* smem, const Params& p, int lo, int hi, uint32_t tag) {
#pragma unroll 1
    for (int e = lo + threadIdx.x; e < hi; e += THREADS) {
        const int s = p.src[e], d = p.dst[e];
        if (near_test(reinterpret_cast<const uint32_t*>(smem)[s], reinterpret_cast<const uint32_t*>(smem)[d], tag << 24)) {
            const uint32_t own = __umulhi((uint32_t)d, p.magic);
            const uint32_t slot4 = atomicAdd(reinterpret_cast<uint32_t*>(smem + SCNT_OFF) + own, 4u);
            uint32_t* line = reinterpret_cast<uint32_t*>(smem + STAGE_OFF) + own * (PITCH / 4);
            if (slot4 < 124) {
                line[slot4 >> 2] = ((uint32_t)s << 15) + ((uint32_t)(d - own * p.NPC) << 6) + tag;
            } else {
                uint32_t o = atomicAdd(reinterpret_cast<uint32_t*>(smem + MISC_OFF) + 16, 1u);
                p.g->ovf[(size_t)blockIdx.x * (4 * p.gpc + 4) + o] = make_int2(s, d);
                line[31] = (PAY_MARK << 6) | tag;
            }
        }
    }
}
__device__ __forceinline__ void cold_filter(unsigned char* smem, const Params& p, int e0, int e1, uint32_t tag, int redo) {
    if (redo) {
        if (threadIdx.x < MAXG) reinterpret_cast<uint32_t*>(smem + SCNT_OFF)[threadIdx.x] = 0;
        __syncthreads();
    }
    cold_edges(smem, p, redo ? 4 * e0 : 4 * (e0 + 3 * THREADS), 4 * e1, tag);
    if (blockIdx.x == 0) cold_edges(smem, p, p.E & ~3, p.E, tag);
    __syncthreads();
    if (threadIdx.x == 0) p.g->ovfcnt[blockIdx.x] = reinterpret_cast<uint32_t*>(smem + MISC_OFF)[16];
    __threadfence();
    __syncthreads();
}
__device__ __forceinline__ float distance(float q) {
    float d;
    asm("sqrt.approx.ftz.f32 %0, %1;" : "=f"(d) : "f"(rbf16(rbf16(q) + 1e-8f)));
    return rbf16(d);
}
__device__ __forceinline__ float fcut(float d) {
    return d < 5.0f ? 0.5f * rbf16(rbf16(__cosf(rbf16(rbf16(3.14159265358979f * d) * 0.2f))) + 1.0f) : 0.f;
}
__device__ __forceinline__ uint4 basis8(float d, uint4 f) {
    const float sc = __fdividef(fcut(d), d);
    const uint32_t dd = __byte_perm(__float_as_uint(d), 0, 0x3232);
    uint32_t x[4] = {hmul2(f.x, dd), hmul2(f.y, dd), hmul2(f.z, dd), hmul2(f.w, dd)};
#pragma unroll
    for (int i = 0; i < 4; i++) x[i] = pack2(__sinf(bf_lo(x[i])) * sc, __sinf(bf_hi(x[i])) * sc);
    return make_uint4(x[0], x[1], x[2], x[3]);
}
__device__ __forceinline__ void cold_nodes(unsigned char* smem, const Params& p, int nn, uint32_t tag) {
    float* acc = reinterpret_cast<float*>(smem + RING_OFF);
    const int nbase = blockIdx.x * p.NPC, lane = threadIdx.x & 31;
    const uint32_t* sv = reinterpret_cast<const uint32_t*>(p.sv);
    const volatile uint32_t* xin = reinterpret_cast<const uint32_t*>(p.g->xbuf) + blockIdx.x * p.G * 32;
#pragma unroll 1
    for (int i = threadIdx.x; i < p.G * 32; i += THREADS) {
        if ((int)xin[(i & ~31) + 15] < (int)(PAY_MARK << 6)) {
            uint32_t w;
            int it = 0;
            do {
                w = xin[i];
                if (++it > (1 << 22)) __trap();
            } while ((w ^ tag) & 63u);
            if ((w >> 6) == PAY_MARK) smem[OVL_OFF + atomicAdd(reinterpret_cast<uint32_t*>(smem + MISC_OFF) + 17, 1u)] = (unsigned char)(i >> 5);
        }
    }
    __threadfence();
    __syncthreads();
    const int nmark = reinterpret_cast<uint32_t*>(smem + MISC_OFF)[17];
#pragma unroll 1
    for (int c0 = 0; c0 < nn; c0 += 128) {
        __syncthreads();
#pragma unroll 1
        for (int i = threadIdx.x; i < 128 * 256; i += THREADS) acc[i] = 0.f;
        __syncthreads();
#pragma unroll 1
        for (int m = -1; m < nmark; m++) {
            const int pr = m < 0 ? 0 : smem[OVL_OFF + m];
            const int cnt = m < 0 ? p.G * 32 : __ldcg(&p.g->ovfcnt[pr]);
#pragma unroll 1
            for (int i = threadIdx.x; i - lane < cnt; i += THREADS) {
                int2 e = make_int2(0, -1);
                if (i < cnt) {
                    if (m < 0) {
                        const uint32_t w = xin[i];
                        if (((w ^ tag) & 63u) == 0) e = make_int2((w >> 15) & 0xFFFFu, (w >> 6) & 511u);
                    } else {
                        e = __ldcg(p.g->ovf + (size_t)pr * (4 * p.gpc + 4) + i);
                        e.y -= nbase;
                    }
                }
                uint32_t rxy = 0, rz = 0;
                bool in = e.y >= c0 && e.y < min(c0 + 128, nn);
                if (in) {
                    const uint2 ps = __ldcg(p.g->pos8 + e.x), pd = __ldcg(p.g->pos8 + nbase + e.y);
                    rxy = hsub2(ps.x, pd.x);
                    rz = hsub2(ps.y, pd.y);
                    in = square(rxy, rz) < QMAX;
                }
#pragma unroll 1
                for (uint32_t todo = __ballot_sync(0xffffffffu, in); todo; todo &= todo - 1) {
                    const int l = __ffs(todo) - 1;
                    const uint32_t* row = sv + (size_t)__shfl_sync(0xffffffffu, e.x, l) * 128 + lane;
                    float* o = acc + (__shfl_sync(0xffffffffu, e.y, l) - c0) * 256 + 2 * lane;
                    const uint32_t xy = __shfl_sync(0xffffffffu, rxy, l), z = __shfl_sync(0xffffffffu, rz, l);
                    const float d = distance(square(xy, z)), fc = fcut(d);
                    uint32_t x = __ldg(row);
                    float y0 = 0.f, y1 = 0.f, m2[6];
#pragma unroll 4
                    for (int k = 0; k < 64; k++) {
                        const uint32_t u = __shfl_sync(0xffffffffu, x, k >> 1), w = __ldg(reinterpret_cast<const uint32_t*>(p.w1) + k * 32 + lane);
                        const float a = k & 1 ? bf_hi(u) : bf_lo(u);
                        y0 = fmaf(a, bf_lo(w), y0);
                        y1 = fmaf(a, bf_hi(w), y1);
                    }
                    y0 = rbf16(y0); y1 = rbf16(y1);
                    x = pack2(y0 / (1.f + __expf(-y0)), y1 / (1.f + __expf(-y1)));
                    const float rb = rbf16(rbf16(__sinf(rbf16(d * __bfloat162float(p.freqs[lane & 15])))) / d);
#pragma unroll
                    for (int g = 0; g < 3; g++) {
                        float p0 = 0.f, p1 = 0.f, w0 = 0.f, w1 = 0.f;
#pragma unroll 4
                        for (int k = 0; k < 64; k++) {
                            const uint32_t u = __shfl_sync(0xffffffffu, x, k >> 1), w = __ldg(reinterpret_cast<const uint32_t*>(p.w2) + k * 96 + g * 32 + lane);
                            const float a = k & 1 ? bf_hi(u) : bf_lo(u);
                            p0 = fmaf(a, bf_lo(w), p0);
                            p1 = fmaf(a, bf_hi(w), p1);
                        }
#pragma unroll 4
                        for (int k = 0; k < 16; k++) {
                            const uint32_t w = __ldg(reinterpret_cast<const uint32_t*>(p.wr) + k * 96 + g * 32 + lane);
                            const float a = __shfl_sync(0xffffffffu, rb, k);
                            w0 = fmaf(a, bf_lo(w), w0);
                            w1 = fmaf(a, bf_hi(w), w1);
                        }
                        m2[2 * g] = rbf16(rbf16(p0) * rbf16(rbf16(w0) * fc));
                        m2[2 * g + 1] = rbf16(rbf16(p1) * rbf16(rbf16(w1) * fc));
                    }
                    atomicAdd(o, m2[0]);
                    atomicAdd(o + 1, m2[1]);
#pragma unroll
                    for (int k = 1; k < 4; k++) {
                        const uint32_t v = __ldg(row + 32 * k);
                        const float rh = rbf16((k == 1 ? bf_lo(xy) : k == 2 ? bf_hi(xy) : bf_lo(z)) / d);
                        atomicAdd(o + 64 * k, fmaf(m2[2], bf_lo(v), m2[4] * rh));
                        atomicAdd(o + 64 * k + 1, fmaf(m2[3], bf_hi(v), m2[5] * rh));
                    }
                }
            }
        }
        __syncthreads();
#pragma unroll 1
        for (int i = threadIdx.x; i < min(128, nn - c0) * 128; i += THREADS) {
            const uint32_t v = __ldg(sv + (size_t)(nbase + c0) * 128 + i);
            reinterpret_cast<uint32_t*>(p.out)[(size_t)(nbase + c0) * 128 + i] = pack2(bf_lo(v) + rbf16(acc[2 * i]), bf_hi(v) + rbf16(acc[2 * i + 1]));
        }
    }
}

template <int CN, int CE, int CG>
__global__ void __launch_bounds__(THREADS, 1) painn_kernel(const __grid_constant__ Params p, const __grid_constant__ CUtensorMap tm) {
    extern __shared__ __align__(1024) unsigned char smem_dyn[];
    unsigned char* const smem = static_cast<unsigned char*>(__cvta_shared_to_generic(SB));
    constexpr uint32_t sb = SB;
    const int tid = threadIdx.x, lane = tid & 31;
    const int warp = __shfl_sync(0xffffffffu, tid >> 5, 0);
    constexpr int CNPC = CG ? (CN + CG - 1) / CG : 1, CGPC = CG ? (CE / 4 + CG - 1) / CG : 1;
    const int b = blockIdx.x, G = CG ? CG : p.G, NPC = CG ? CNPC : p.NPC, N = CG ? CN : p.N, gpc = CG ? CGPC : p.gpc;
    const uint32_t magic = CG ? (uint32_t)(((1ull << 32) + CNPC - 1) / CNPC) : p.magic;
    const bool odd_edges = CG ? (CE & 3) != 0 || CGPC > 3 * THREADS : p.odd_edges;
    const int nbase = b * NPC, nn = min(NPC, N - nbase);
    const int e0 = b * gpc, e1 = min((CG ? CE : p.E) >> 2, e0 + gpc);

    uint4* stage4 = reinterpret_cast<uint4*>(smem + STAGE_OFF);
    uint32_t* ncnt = reinterpret_cast<uint32_t*>(smem + NCNT_OFF);
    uint32_t* misc = reinterpret_cast<uint32_t*>(smem + MISC_OFF);
    const uint32_t bar_full = sb + BAR_OFF + (warp & 7) * 40, bar_empty = bar_full + 16, bar_side = bar_full + 32, bar_tab = sb + BAR_OFF + 336;

    auto warm = [&](int first, int n) {
#pragma unroll 1
        for (int i = first; i < first + n; i++) {
            if (elect())
                asm volatile("cp.async.bulk.tensor.2d.shared::cluster.global.mbarrier::complete_tx::bytes [%0], [%1, {0, %3}], [%2];"
                             ::"r"(sb + SINK_OFF), "l"(&tm), "r"(bar_tab + 8), "r"(nbase * 4 + i * 32) : "memory");
        }
    };
    TS0(0);
    int4 es[3], ed[3];
    auto load_edges = [&](int i) {
        const int g = min(e0 + tid + i * THREADS, e1 - 1);
        asm volatile("ld.global.cs.v4.u32 {%0,%1,%2,%3}, [%8];\nld.global.cs.v4.u32 {%4,%5,%6,%7}, [%9];"
                     : "=r"(es[i].x), "=r"(es[i].y), "=r"(es[i].z), "=r"(es[i].w), "=r"(ed[i].x), "=r"(ed[i].y), "=r"(ed[i].z), "=r"(ed[i].w)
                     : "l"(reinterpret_cast<const int4*>(p.src) + g), "l"(reinterpret_cast<const int4*>(p.dst) + g) : "memory");
    };
    unsigned epoch;
    const uint32_t tbytes = ((N + 3) >> 2) * 16;
    {
        uint32_t pxy, pz;
        asm volatile("ld.global.nc.u32 %0, [%3];\nld.global.nc.u32 %1, [%3 + 4];\nld.global.ca.u32 %2, [%4];"
                     : "=r"(pxy), "=r"(pz), "=r"(epoch)
                     : "l"(reinterpret_cast<const uint32_t*>(p.pos) + ((nbase + min(tid, nn - 1)) * 3 >> 1)), "l"(p.g->sync) : "memory");
        const uint32_t sh = ((nbase + tid) & 1) << 4;
        pxy = __funnelshift_r(pxy, pz, sh);
        pz >>= sh;
        if (tid < nn) {
            reinterpret_cast<uint32_t*>(p.g->table)[nbase + tid] = qcode(bf_lo(pxy), bf_hi(pxy), bf_lo(pz), ((epoch & 31u) ^ 0x6Bu) << 24);
            p.g->pos8[nbase + tid] = make_uint2(pxy, pz);
        }
        reinterpret_cast<uint2*>(smem + OPOS_OFF)[tid] = make_uint2(pxy, pz);
        if (pxy == 0xFFFFFFFFu && pz == 0xFFFFFFFFu && epoch == 0xFFFFFFFFu) asm volatile("nanosleep.u32 0;");
        load_edges(0);
    }
    __syncthreads();
    const uint32_t tag = (epoch & 31u) | 32u;
    if (warp == 15) {
        if (elect()) {
            asm volatile("red.relaxed.gpu.global.add.u32 [%0], 1;" ::"l"(p.g->sync + 8 + b * NP / G) : "memory");
            asm volatile("prefetch.tensormap [%0];" ::"l"(&tm) : "memory");
            mbar_init(bar_tab, 1);
            mbar_init(bar_tab + 8, 1);
            mbar_expect_tx(bar_tab, tbytes);
            mbar_expect_tx(bar_tab + 8, (WA + WC + WE) * 512);
        }
        TSX(1, 511);
    }
    if (warp == 14) {
#pragma unroll 1
        for (int c = b * 32 + lane; c < WIMG / 16 + LUTS * 2; c += G * 32) {
            const int row = c >> 3, j = (c ^ row) & 7;
            uint4 v;
            if (c < 512) {
                const uint32_t half = 0x3F003F00u;
                v = __ldg(reinterpret_cast<const uint4*>(p.w1) + row * 8 + j);
                v = make_uint4(hmul2(v.x, half), hmul2(v.y, half), hmul2(v.z, half), hmul2(v.w, half));
            } else if (c >= WIMG / 16) {
                v = basis8(__uint_as_float((0x409D - ((c - WIMG / 16) >> 1)) << 16), __ldg(reinterpret_cast<const uint4*>(p.freqs) + (c & 1)));
            } else {
                const uint32_t* q = (c < 2048 ? reinterpret_cast<const uint32_t*>(p.w2) + (row & 63) * 96 + ((row >> 6) - 1) * 32
                                              : reinterpret_cast<const uint32_t*>(p.wr) + (row & 15) * 96 + ((row >> 4) - 16) * 32) + (j & 4) * 4 + (j & 3);
                v = make_uint4(__ldg(q), __ldg(q + 4), __ldg(q + 8), __ldg(q + 12));
            }
            p.g->wimg[c] = v;
        }
    }
    if (warp < 8 && elect()) {
        mbar_init(bar_full, 32); mbar_init(bar_full + 8, 32);
        mbar_init(bar_empty, 1);
        mbar_init(bar_side, 32);
    }
    if (tid < MAXG) reinterpret_cast<uint32_t*>(smem + SCNT_OFF)[tid] = 0;
    if (tid < 48) misc[tid] = 0;
    {
        const uint32_t inv = (PAY_INVALID << 6) | tag;
        stage4[tid] = stage4[tid + THREADS] = make_uint4(inv, inv, inv, inv);
        if (tid < MAXG * (PITCH / 16) - 2 * THREADS) stage4[tid + 2 * THREADS] = make_uint4(inv, inv, inv, inv);
    }
    if (warp == 15) {
        __syncwarp();
        const int k = lane & (NP - 1), b0 = (k * G + NP - 1) / NP, b1 = ((k + 1) * G + NP - 1) / NP;
        const uint32_t o0 = (b0 * NPC * 4) & ~127u, o1 = k == NP - 1 ? tbytes : (b1 * NPC * 4) & ~127u;
        bool todo = lane < NP, wait = true;
        uint32_t left;
        int it = smem_u32(smem_dyn) == SB ? 0 : 1 << 22;
        do {
            unsigned c;
            asm volatile("ld.relaxed.gpu.global.u32 %0, [%1];" : "=r"(c) : "l"(p.g->sync + 8 + k) : "memory");
            if (todo && c == (epoch + 1) * (b1 - b0)) {
                bulk_g2s(sb + o0, reinterpret_cast<const char*>(p.g->table) + o0, o1 - o0, bar_tab);
                todo = false;
            }
            if (++it > (1 << 22)) __trap();
            left = __ballot_sync(0xffffffffu, todo);
            if (wait && __popc(left) <= NLEFT) {
                asm volatile("bar.arrive 1, 512;" ::: "memory");
                wait = false;
            }
        } while (left);
        asm volatile("bar.sync 2, 512;" ::: "memory");
        TSX(2, 511);
    } else {
        asm volatile("bar.arrive 2, 512;" ::: "memory");
        asm volatile("bar.sync 1, 512;" ::: "memory");
    }
    load_edges(1);
#pragma unroll 1
    for (int r = tid >> 2; r < G; r += THREADS / 4) {
        uint4* const x = p.g->xbuf + (r * G + b) * 8 + (tid & 3);
        stg128_if(x, make_uint4(0, 0, 0, 0), true);
        stg128_if(x + 4, make_uint4(0, 0, 0, 0), ((r ^ epoch) & 15) == 0);
    }
    load_edges(2);
    if (tid == THREADS - 1) asm volatile("fence.acq_rel.gpu;" ::: "memory");
    mbar_wait(bar_tab, 0);
    TS0(3);
    if (warp == 15) warm(0, WA);

    bool over = false;
#pragma unroll 1
    for (int i = 0, g = e0 + tid; i < 3; i++, g += THREADS) {
        const int s[4] = {es[0].x, es[0].y, es[0].z, es[0].w}, d[4] = {ed[0].x, ed[0].y, ed[0].z, ed[0].w};
        uint32_t ca[4], cb[4], own[4], sl[4];
        bool c[4];
#pragma unroll
        for (int j = 0; j < 4; j++) { ca[j] = lds32(sb + 4 * s[j]); cb[j] = lds32(sb + 4 * d[j]); }
#pragma unroll
        for (int j = 0; j < 4; j++) {
            c[j] = near_test(ca[j], cb[j], tag << 24) && g < e1;
            own[j] = __umulhi((uint32_t)d[j], magic);
            sl[j] = atomicAdd(reinterpret_cast<uint32_t*>(smem + SCNT_OFF) + (c[j] ? own[j] : MAXG + lane), 4u);
        }
#pragma unroll
        for (int j = 0; j < 4; j++)
            sts32_if(sb + STAGE_OFF + own[j] * PITCH + sl[j], own[j] * (uint32_t)(-64 * NPC) + (((uint32_t)s[j] << 15) + (((uint32_t)d[j] << 6) + tag)),
                     c[j] && sl[j] < 124);
#pragma unroll
        for (int j = 0; j < 4; j++) over |= c[j] && sl[j] >= 124;
        es[0] = es[1]; es[1] = es[2];
        ed[0] = ed[1]; ed[1] = ed[2];
    }
    {
        const int redo = __syncthreads_or(over);
        if (__builtin_expect(redo || odd_edges, 0)) cold_filter(smem, p, e0, e1, tag, redo);
    }
    TS0(4);
#pragma unroll 1
    for (int r = tid >> 2; r < G; r += THREADS / 4) {
        const int c = r * (PITCH / 16) + (tid & 3);
        uint4* const x = p.g->xbuf + (r * G + b) * 8 + (tid & 3);
        const bool more = reinterpret_cast<uint32_t*>(smem + SCNT_OFF)[r] > 64;
        uint4 v = stage4[c];
        if (more && (tid & 3) == 3) v.w |= 0x80000000u;
        stg128_if(x + 4, stage4[c + 4], more);
        stg128_if(x, v, true);
    }
    ncnt[tid] = 0;
    if (tid < 480) reinterpret_cast<uint32_t*>(smem + SLOT_OFF)[tid] = tid < 32 ? tid * 0x100010 + 0x80000 : tid < 320 ? ~0u : 0u;
    if (tid == 511) reinterpret_cast<uint2*>(smem + NPOS_OFF)[511] = make_uint2(sb + SLOT_OFF + 1278, 0);
    __syncthreads();
    reinterpret_cast<uint4*>(smem + RR_OFF)[tid] = make_uint4(0, 0, 0, 0);
    if (tid < ROUNDS * 80 - THREADS) reinterpret_cast<uint4*>(smem + RR_OFF)[tid + THREADS] = make_uint4(0, 0, 0, 0);
    if (tid < ROUNDS * 32) reinterpret_cast<uint2*>(smem + SRC_OFF)[tid] = make_uint2(~0u, ~0u);
    __nanosleep(PDELAY);
    TS0(5);

    uint32_t rxy[4], gz[4], src[4], rk[4], dn[4];
    const uint32_t sink = sb + NCNT_OFF + 4 * (480 + lane);
    if (warp < 15) {
        uint32_t ew[3][4], bad[2];
        const int u = tid - 3 * G;
        const uint4* const xin = p.g->xbuf + b * G * 8;
        const uint4* cp = xin + (u < 0 ? tid + tid / 3 * 5 : u * 8 + 3);
        bad[0] = u < G;
        bad[1] = u >= 0 && u + 480 - 3 * G < G;
#pragma unroll
        for (int i = 0; i < 3; i++) ew[i][0] = ew[i][1] = ew[i][2] = ew[i][3] = (PAY_INVALID << 6) | tag;
        int it = 0;
#pragma unroll 1
        do {
#pragma unroll
            for (int i = 0; i < 2; i++)
                asm volatile("{\n.reg .pred p;\nsetp.ne.u32 p, %5, 0;\n@p ld.relaxed.gpu.global.v4.u32 {%0,%1,%2,%3}, [%4];\n}\n"
                             : "+r"(ew[i][0]), "+r"(ew[i][1]), "+r"(ew[i][2]), "+r"(ew[i][3]) : "l"(cp + i * (480 - 3 * G) * 8), "r"(bad[i]) : "memory");
#pragma unroll
            for (int i = 0; i < 2; i++) bad[i] = ((ew[i][0] ^ tag) | (ew[i][1] ^ tag) | (ew[i][2] ^ tag) | (ew[i][3] ^ tag)) & 63u;
            if (++it > (1 << 22)) __trap();
        } while (__any_sync(0xffffffffu, bad[0] | bad[1]));
        if (warp >= (3 * G) >> 5) {
            constexpr int EMPTY = (int)(PAY_MARK << 6);
            const bool e0 = ew[0][0] >= (PAY_MARK << 6);
            if (__builtin_expect(__any_sync(0xffffffffu, min((int)ew[0][3], (int)ew[1][3]) < EMPTY || (!e0 && ew[1][0] < (PAY_MARK << 6))), 0)) {
                uint64_t f = (uint64_t)__ballot_sync(0xffffffffu, (int)ew[1][3] < EMPTY) << 32 | __ballot_sync(0xffffffffu, (int)ew[0][3] < EMPTY);
                if ((int)ew[0][3] < EMPTY) ew[0][3] &= 0x7FFFFFFFu;
                if ((int)ew[1][3] < EMPTY) ew[1][3] &= 0x7FFFFFFFu;
#pragma unroll 1
                for (int k = 7 - (lane >> 2); k && f; k--) f &= f - 1;
                if (f) {
                    const int l = __ffsll(f) - 1;
                    do {
                        asm volatile("ld.relaxed.gpu.global.v4.u32 {%0,%1,%2,%3}, [%4];" : "=r"(ew[2][0]), "=r"(ew[2][1]), "=r"(ew[2][2]), "=r"(ew[2][3])
                                     : "l"(xin + (u - lane + l + (l >> 5) * (448 - 3 * G)) * 8 + 4 + (lane & 3)) : "memory");
                        if (++it > (1 << 22)) __trap();
                    } while (((ew[2][0] ^ tag) | (ew[2][1] ^ tag) | (ew[2][2] ^ tag) | (ew[2][3] ^ tag)) & 63u);
                    if ((ew[2][3] >> 6) == PAY_MARK || lane == 0) misc[0] = 1;
                }
                __syncwarp();
#pragma unroll 1
                for (int i = 0; i < 2; i++) {
                    if (ew[0][0] >= (PAY_MARK << 6)) {
#pragma unroll
                        for (int j = 0; j < 4; j++) { ew[0][j] = ew[1][j]; ew[1][j] = ~0u; }
                    }
                    uint32_t from = __ballot_sync(0xffffffffu, ew[1][0] < (PAY_MARK << 6)), to = __ballot_sync(0xffffffffu, ew[0][0] >= (PAY_MARK << 6));
#pragma unroll 1
                    for (; from; from &= from - 1, to &= to - 1) {
                        if (!to) misc[0] = 1;
#pragma unroll
                        for (int j = 0; j < 4; j++) {
                            const uint32_t x = __shfl_sync(0xffffffffu, ew[1][j], __ffs(from) - 1);
                            if (lane == __ffs(to) - 1) ew[0][j] = x;
                        }
                    }
#pragma unroll
                    for (int j = 0; j < 4; j++) ew[1][j] = ew[2][j];
                }
            } else if (e0) {
#pragma unroll
                for (int j = 0; j < 4; j++) ew[0][j] = ew[1][j];
            }
        }
        {
            uint2 ps[4], pd[4];
#pragma unroll
            for (int j = 0; j < 4; j++) {
                dn[j] = (ew[0][j] >> 3) & 4088u;
                src[j] = ew[0][j] >> 15;
                ps[j] = __ldcg(p.g->pos8 + (dn[j] == 4088u ? nbase : src[j]));
            }
#pragma unroll
            for (int j = 0; j < 4; j++) pd[j] = *reinterpret_cast<const uint2*>(smem + OPOS_OFF + dn[j]);
            asm volatile("bar.arrive 1, 512;" ::: "memory");
            float q[4];
#pragma unroll
            for (int j = 0; j < 4; j++) {
                rxy[j] = hsub2(ps[j].x, pd[j].x);
                gz[j] = hsub2(ps[j].y, pd[j].y);
                q[j] = square(rxy[j], gz[j]);
                const bool in = q[j] < QMAX && dn[j] != 4088u;
                rk[j] = atoms_add(in ? sb + NCNT_OFF + (dn[j] >> 1) : sink, 512u);
                if (!in) dn[j] = 4088u;
            }
            uint32_t row[4], n = 0;
            bool single[4];
#pragma unroll
            for (int j = 0; j < 4; j++) {
                q[j] = distance(q[j]);
                row[j] = 0x409D - (__float_as_uint(q[j]) >> 16);
                single[j] = row[j] >= LUTS && dn[j] != 4088u;
                n += single[j];
            }
            n = atoms_add(n ? sb + MISC_OFF + 4 : sink, n) + LUTS;
#pragma unroll
            for (int j = 0; j < 4; j++) {
                float id;
                asm("rcp.approx.ftz.f32 %0, %1;" : "=f"(id) : "f"(q[j]));
                sts32_if(sb + LUT_OFF + min(n, LUTN - 1) * 32, __float_as_uint(q[j]), single[j]);
                if (single[j]) row[j] = n++;
                rxy[j] = pack2(bf_lo(rxy[j]) * id, bf_hi(rxy[j]) * id);
                gz[j] = pack2(0.f, bf_lo(gz[j]) * id) + row[j] * 32;
            }
        }
    } else {
        const uint4 fq = __ldg(reinterpret_cast<const uint4*>(p.freqs) + (lane & 1));
        rxy[0] = fq.x; rxy[1] = fq.y; rxy[2] = fq.z; rxy[3] = fq.w;
        asm volatile("bar.sync 1, 512;" ::: "memory");
        warm(WA, WC);
    }
    __syncthreads();
    TS0(6);

    const uint32_t lt = (1u << lane) - 1;
    uint32_t place = ~0u, mid = 0, last = 0, steps = 0, c = 0;
    if (warp < 15) {
        if (tid < nn) c = ncnt[tid] >> 9;
        steps = min((c + 1) >> 1, 15u);
        const uint32_t bin = sel(tid >= nn, 9, (uint32_t)(0x11223354678ull >> (4 * min(c, 11u))) & 15), sh = (bin & 1) * 16;
        const bool odd = c > 3 && (c & 1);
        const uint32_t peers = __match_any_sync(0xffffffffu, bin), om = __ballot_sync(0xffffffffu, odd);
        uint32_t x = atoms_add(lane == 0 ? sb + MISC_OFF + 4 * 37 : sink, __popc(om));
        uint32_t r = atoms_add((peers & lt) == 0 ? sb + MISC_OFF + 4 * 32 + 2 * (bin & 14) : sink, __popc(peers) << sh);
        x = __shfl_sync(0xffffffffu, x, 0) + __popc(om & lt);
        r = ((__shfl_sync(0xffffffffu, r, __ffs(peers) - 1) >> sh) & 0xFFFFu) + __popc(peers & lt);
        sts16_if(sb + sel(bin == 8, ZL_OFF, sel(bin == 7, YL_OFF, TL_OFF)) + 2 * r, tid, (0x190 >> bin) & 1);
        const uint64_t ones = 0x0001010101010101ull >> (56 - 8 * min(bin, 7u));
        asm volatile("bar.sync 2, 480;" ::: "memory");
        uint32_t h[4];
        lds128(sb + MISC_OFF + 4 * 32, h);
        const int nodd = misc[37], n1 = h[3] >> 16, n3 = h[2] & 0xFFFF, left = max(min(nodd + n3 - n1, n3), 0), half = left >> 1;
        const bool twin = bin == 4 && (int)r < 2 * half;
        x = sel(bin == 4, nodd + r - left, sel(odd, x, 1023));
        const bool pair = twin ? !(r & 1) : (int)x >= (bin == 4 ? nodd : 0) && (int)x < n1;
        const uint32_t y = lds16(sel(twin, sb + TL_OFF + 2 + 2 * r, sb + YL_OFF + 2 * (x & 511)));
        const uint32_t base = __dp2a_lo(h[0], (uint32_t)ones, __dp2a_hi(h[1], (uint32_t)ones, 0u)) +
                              __dp2a_lo(h[2], (uint32_t)(ones >> 32), __dp2a_hi(h[3], (uint32_t)(ones >> 32), 0u));
        r -= sel(bin == 7, nodd + n3, 0);
        const bool unit = (bin < 8 && (int)r >= 0 && (pair || !twin));
        place = sel(unit, base + sel(twin, r >> 1, r - sel(bin < 4, 0, half)), ~0u);
        sts32_if(sb + MISC_OFF + 16, base - half + max(n1 - nodd - n3, 0), bin >= 7);
        steps += twin;
        last = sel(twin, y, tid) | sel(steps > 1, ST_CLOSE, ST_CLOSE | ST_START);
        mid = sel(pair, y | sel(twin, ST_MID, ST_MID | ST_CLOSE) | (tid << 16), last);
        c = sel(pair, c, 2 * steps - 1);
        const uint32_t sa = sb + SLOT_OFF + sel(steps <= ROUNDS, 2 * place, 1278);
        sts64_if(sb + NPOS_OFF + 8 * tid, sa, 0, unit);
        sts64_if(sb + NPOS_OFF + 8 * y, sa, c << 9, pair);
        asm volatile("{\n.reg .pred p;\nsetp.ne.u32 p, %2, 0;\n@p st.shared.u8 [%0], %1;\n}\n" ::"r"(sb + SIZE_OFF + place), "r"(steps), "r"((uint32_t)unit) : "memory");
    } else {
        if (elect()) {
            if (b == 0) p.g->sync[0] = epoch + 1;
            asm volatile("fence.proxy.async.global;" ::: "memory");
            mbar_expect_tx(bar_tab, WIMG + LUTS * 32);
            bulk_g2s(sb, p.g->wimg, WIMG, bar_tab);
            bulk_g2s(sb + LUT_OFF, p.g->wimg + WIMG / 16, LUTS * 32, bar_tab);
        }
        warm(WA + WC, WE);
#pragma unroll 1
        for (uint32_t i = lane; i - lane < 2 * min(misc[1], LUTN - LUTS); i += 32) {
            const uint32_t d = lds32(sb + LUT_OFF + (LUTS + (i >> 1)) * 32);
            __syncwarp();
            reinterpret_cast<uint4*>(smem + LUT_OFF)[2 * LUTS + i] = basis8(__uint_as_float(d), make_uint4(rxy[0], rxy[1], rxy[2], rxy[3]));
        }
        TSX(12, 511);
    }
    __syncthreads();
    TS0(7);
    uint32_t st[4];
    if (warp == 15) {
        uint32_t until0 = lds16(sb + SIZE_OFF + 2 * lane), until1 = until0 >> 8, next = 64, s0, s1;
        const uint32_t nsched = misc[4];
        until0 &= 255;
        uint32_t t = __reduce_min_sync(0xffffffffu, min(until0, until1));
        bool go = true;
#pragma unroll 1
        while (go) {
            go = t < ROUNDS && next < nsched;
            const bool n0 = until0 == t, n1 = until1 == t;
            const uint32_t i = next + __popc(__ballot_sync(0xffffffffu, n0) & lt) + __popc(__ballot_sync(0xffffffffu, n1) & lt), j = i + n0;
            next += __reduce_add_sync(0xffffffffu, n0 + n1);
            asm volatile("{\n.reg .pred p, q;\nsetp.ne.u32 p, %4, 0;\nsetp.ne.u32 q, %5, 0;\nmov.u32 %0, 0;\nmov.u32 %1, 0;\n@p ld.shared.u8 %0, [%2];\n@q ld.shared.u8 %1, [%3];\n}\n"
                         : "=&r"(s0), "=&r"(s1) : "r"(sb + SIZE_OFF + i), "r"(sb + SIZE_OFF + j), "r"((uint32_t)n0), "r"((uint32_t)n1) : "memory");
            until0 += s0;
            until1 += s1;
            sts16_if(sb + SLOT_OFF + 2 * i, 1024 * t + 16 * lane, n0 && until0 <= ROUNDS);
            sts16_if(sb + SLOT_OFF + 2 * j, 1024 * t + 16 * lane + 8, n1 && until1 <= ROUNDS);
            t++;
        }
        until0 = __reduce_max_sync(lane < 16 ? 0xFFFFu : 0xFFFF0000u, max(until0, until1));
        if ((lane & 15) == 0) misc[2 + (lane >> 4)] = until0;
        __syncthreads();
        lds128(sb + MISC_OFF, st);
    } else {
#pragma unroll
        for (int j = 0; j < 4; j++) {
            const uint2 np = *reinterpret_cast<const uint2*>(smem + NPOS_OFF + dn[j]);
            dn[j] = np.x;
            rk[j] += np.y;
        }
#pragma unroll 1
        for (int pass = 0; pass < 2; pass++) {
            uint32_t e[4];
#pragma unroll
            for (int j = 0; j < 4; j++) e[j] = lds16(dn[j]);
            const uint32_t x = lds16(sb + SLOT_OFF + 2 * min(place, 639u));
#pragma unroll
            for (int j = 0; j < 4; j++) {
                sts16_if(sb + SRC_OFF + ((rk[j] + e[j]) >> 2), src[j], e[j] != 0xFFFFu);
                sts64_if(sb + RR_OFF + rk[j] + e[j], rxy[j], gz[j], e[j] != 0xFFFFu);
                if (e[j] != 0xFFFFu) dn[j] = sb + SLOT_OFF + 1278;
            }
            if (pass) {
                const uint32_t nd = sb + ND_OFF + ((x >> 2) & 0xFF00) + ((x >> 1) & 0xFC);
                sts32_if(nd, tid | ST_START, x != 0xFFFFu);
                sts32_if(nd + steps * 256 - 256, last, x != 0xFFFFu && steps <= ROUNDS);
                sts32_if(nd + c * 128 - 128, mid, x != 0xFFFFu && steps <= ROUNDS);
                break;
            }
            asm volatile("bar.sync 2, 480;" ::: "memory");
            if (warp < 8) {
                const int s = lane >> 3, c = lane & 7;
                const uint32_t dst = sb + RING_OFF + warp * 16384 + s * 128, y = sb + SRC_OFF + (warp * 8 + s) * 2;
                const uint32_t sdst = dst + ((c ^ s) << 4), vdst = dst + ((c ^ ((s & 1) << 2)) << 4);
                const uint32_t s0 = lds16(y), s1 = lds16(y + 8), s2 = lds16(y + 128), s3 = lds16(y + 136);
                const char* svl = reinterpret_cast<const char*>(p.sv) + c * 16;
                gather_s(sdst, svl, s0);
                gather_s((sdst ^ 64) + 512, svl, s1);
                gather_s(sdst + 8192, svl, s2);
                gather_s((sdst ^ 64) + 8704, svl, s3);
                cp_async_arrive(bar_full);
                TS0(10);
                __nanosleep(warp & 4 ? P1W : P0);
                gather_v(vdst, svl, s0);
                __nanosleep(P0);
                gather_v(vdst + 512, svl, s1);
                __nanosleep(P0);
                gather_v(vdst + 8192, svl, s2);
                __nanosleep(P0);
                gather_v(vdst + 8704, svl, s3);
                asm volatile("cp.async.mbarrier.arrive.shared::cta.b64 [%0];" ::"r"(bar_side) : "memory");
            }
            __syncthreads();
            TS0(8);
            lds128(sb + MISC_OFF, st);
        }
    }
    __syncthreads();
    if (__builtin_expect(max(st[2], st[3]) > ROUNDS || st[1] > LUTN - LUTS || st[0], 0)) {
        asm volatile("cp.async.wait_all;" ::: "memory");
        mbar_wait(bar_tab, 1);
        mbar_wait(bar_tab + 8, 0);
        cold_nodes(smem, p, nn, tag);
        return;
    }
    TS0(9);
    const int T = __shfl_sync(0xffffffffu, warp & 4 ? st[3] : st[2], 0);

    if (warp < 8) {
        asm volatile("setmaxnreg.inc.sync.aligned.u32 %0;" ::"n"(REG_C));
        const int lane = fresh_lane();
        const int g = lane >> 2, q = lane & 3;
        const uint64_t d0 = (uint64_t)__shfl_sync(0xffffffffu, pin((uint32_t)(p.desc0 >> 32)), 0) << 32 | __shfl_sync(0xffffffffu, pin((uint32_t)p.desc0), 0);
        const uint32_t swz = g * 128 + ((q ^ ((g & 1) << 2)) << 4);
        const uint32_t srow = pin(sb + SIDE_OFF + warp * 4096 + swz);
        uint32_t vrow = pin(sb + RING_OFF + warp * 16384 + swz + 4096);
        uint32_t ent = pin(sb + RR_OFF + (warp * 8 + g) * 8), fent = pin(sb + ND_OFF + (warp * 8 + g) * 4);
        uint32_t lent = pin(sb + RR_OFF + (warp * 8 + (lane & 7)) * 8 + 4 + (lane & 8) * 64);
        const uint32_t lutq = pin(sb + LUT_OFF + (lane >> 4) * 16);
        uint64_t outq;
        {
            const uint64_t a = reinterpret_cast<uint64_t>(p.out) + (size_t)nbase * 512 + q * 16;
            const uint32_t lo = pin((uint32_t)a), hi = pin((uint32_t)(a >> 32));
            asm volatile("mov.b64 %0, {%1, %2};" : "=l"(outq) : "r"(lo), "r"(hi));
        }
        uint32_t acc[32], rf[4], h[16], rr[4], fl = 0;
#pragma unroll
        for (int i = 0; i < 32; i++) asm volatile("" : "=r"(acc[i]));
#pragma unroll
        for (int i = 0; i < 16; i++) asm volatile("" : "=r"(h[i]));
#pragma unroll
        for (int i = 0; i < 4; i++) asm volatile("" : "=r"(rf[i]), "=r"(rr[i]));
        int t = -1;
        TSX(18, 0);
        mbar_wait(bar_tab, 1);
        TSX(14, 0);
        const int Tm = __shfl_sync(0xffffffffu, min(st[2], st[3]), 0);
        if (warp >= 4 && Tm > 0) asm volatile("bar.arrive 3, 256;" ::: "memory");
        bool more = T < 0x7FFFFFFF;
#pragma unroll 1
        while (more) {
            float y[32], p1[32], w1[32], p2[32], w2[32], p3[32], w3[32];
            uint32_t m1[16], m2[16], v[3][16], ts[8];
            auto products = [](uint32_t* m, const float* P, const float* W) {
#pragma unroll
                for (int j = 0; j < 8; j++) {
                    m[j] = pack2(P[4 * j] * W[4 * j], P[4 * j + 1] * W[4 * j + 1]);
                    m[8 + j] = pack2(P[4 * j + 2] * W[4 * j + 2], P[4 * j + 3] * W[4 * j + 3]);
                }
            };
            auto vterm = [&](int k, int o) {
#pragma unroll
                for (int j = 0; j < 8; j++) acc[8 * k + 8 + j] = hfma2(m1[o + j], v[k][o + j], acc[8 * k + 8 + j]);
            };
            auto rterm = [&](int k, int o) {
#pragma unroll
                for (int j = 0; j < 8; j++)
                    acc[8 * k + 8 + j] = k == 0 ? hfma2_lo(m2[o + j], rr[o / 4], acc[8 * k + 8 + j]) : hfma2_hi(m2[o + j], rr[o / 4 + k / 2], acc[8 * k + 8 + j]);
            };
            TR(0, 0, t);
            uint64_t om, op;
#pragma unroll
            for (int j = 0; j < 8; j++) asm volatile("" : "=r"(ts[j]), "=r"(m1[8 + j]), "=r"(m2[8 + j]), "=r"(v[0][8 + j]), "=r"(v[1][8 + j]), "=r"(v[2][8 + j]));
            asm volatile("" : "=l"(om));
            if (t >= 0) {
            TC(0);
            if (t < Tm) asm volatile("bar.sync %0, 256;" ::"r"(3 + (warp >> 2)) : "memory");
            wg_fence();
            wgmma_rs2<W2_OFF + 8192, 8192, 0>(p1, p2, h, d0);
            wgmma_rs2<W2_OFF + 10240, 8192, 1>(p1, p2, h + 4, d0);
            wgmma_rs2<W2_OFF + 12288, 8192, 1>(p1, p2, h + 8, d0);
            wgmma_rs2<W2_OFF + 14336, 8192, 1>(p1, p2, h + 12, d0);
            wgmma_rs2<WR_OFF + 2048, 2048, 0>(w1, w2, rf, d0);
            wg_commit();
            TC(1);
            mbar_wait(bar_side, t & 1);
            TC(2);
#pragma unroll
            for (int k = 0; k < 4; k++) lds2_if(srow + 1024 * k, (srow ^ 64) + 1024 * k, acc + 8 * k, fl & ST_START);
            wg_wait<0>();
            fence_regs(p1); fence_regs(w1);
            TC(3);
            products(m1, p1, w1);
#pragma unroll
            for (int k = 0; k < 3; k++) { lds128(vrow + 1024 + 1024 * k, v[k]); lds128((vrow ^ 64) + 1024 + 1024 * k, v[k] + 4); }
            fence_regs(p2); fence_regs(w2);
            products(m2, p2, w2);
            asm("mad.wide.u32 %0, %1, 512, %2;" : "=l"(om) : "r"(fl >> 16), "l"(outq));
#pragma unroll
            for (int k = 0; k < 3; k++) { lds128(vrow + 9216 + 1024 * k, v[k] + 8); lds128((vrow ^ 64) + 9216 + 1024 * k, v[k] + 12); }
#pragma unroll
            for (int j = 0; j < 8; j++) asm volatile("" : "=r"(ts[j]));
            lds2_if(srow, srow ^ 64, ts, fl & ST_MID);
#pragma unroll
            for (int k = 0; k < 3; k++) { vterm(k, 0); rterm(k, 0); stg2_if(om + 128 + 128 * k, acc + 8 + 8 * k, fl & ST_MID); }
            TC(4);
            if (t + (warp >> 2) < Tm) asm volatile("bar.arrive %0, 256;" ::"r"(4 - (warp >> 2)) : "memory");
            }
            t++;
            wg_fence();
            wgmma_group<0>(p3, w3, h, rf, d0);
            wg_commit();
            if (T > 1000000) asm volatile("nanosleep.u32 0;");
#pragma unroll
            for (int k = 1; k < 4; k++) lds2_if(srow + 1024 * k, (srow ^ 64) + 1024 * k, acc + 8 * k, fl & ST_MID);
            uint32_t lo;
            asm volatile("ld.shared.u16 %0, [%1];" : "=r"(lo) : "r"(lent) : "memory");
            __syncwarp();
            if (lane == 0 && t > 0) mbar_arrive(bar_empty);
            if (t > 0) TC(5);
            if (t >= T) {
                asm("mad.wide.u32 %0, %1, 512, %2;" : "=l"(op) : "r"(fl & 511), "l"(outq));
#pragma unroll
                for (int k = 0; k < 3; k++) { vterm(k, 8); rterm(k, 8); stg2_if(op + 128 + 128 * k, acc + 8 + 8 * k, fl & ST_CLOSE); }
                wg_wait<0>();
                fence_regs(p3); fence_regs(w3);
                products(m1, p3, w3);
#pragma unroll
                for (int j = 0; j < 8; j++) acc[j] = hadd2(acc[j], m1[j]);
                stg2_if(om, acc, fl & ST_MID);
#pragma unroll
                for (int j = 0; j < 8; j++) acc[j] = hadd2(fl & ST_MID ? ts[j] : acc[j], m1[8 + j]);
                stg2_if(op, acc, fl & ST_CLOSE);
                asm volatile("cp.async.wait_all;" ::: "memory");
                break;
            }
            mbar_wait(bar_full + 8 * (t & 1), (t >> 1) & 1);
            if (t > 0) TC(6);
            wg_fence();
            wgmma_ss_k64(y, d0 + ((RING_OFF >> 4) + (warp >> 2) * 4096 + (t & 1) * 256 + ((uint64_t)(512 - 64) << 32)), d0);
            wg_commit();
            if (T > 1000000) asm volatile("nanosleep.u32 0;");
            asm("mad.wide.u32 %0, %1, 512, %2;" : "=l"(op) : "r"(fl & 511), "l"(outq));
            vrow ^= 4096;
#pragma unroll
            for (int k = 0; k < 3; k++) vterm(k, 8);
#define BBS if (T > 1000000) asm volatile("nanosleep.u32 0;")
            auto silu = [&](int i0, int i1) {
#pragma unroll
                for (int i = i0; i < i1; i++)
                    h[i] = pack2(fmaf(y[2 * i], tanh_fast(y[2 * i]), y[2 * i]), fmaf(y[2 * i + 1], tanh_fast(y[2 * i + 1]), y[2 * i + 1]));
            };
#pragma unroll
            for (int k = 0; k < 3; k++) rterm(k, 8);
            const uint32_t fo = fl;
            asm volatile("ld.shared.v2.u32 {%0,%1}, [%4];\nld.shared.v2.u32 {%2,%3}, [%4 + 512];" : "=r"(rr[0]), "=r"(rr[1]), "=r"(rr[2]), "=r"(rr[3]) : "r"(ent) : "memory");
            asm volatile("ld.shared.u32 %0, [%1];" : "=r"(fl) : "r"(fent) : "memory");
            stg2_if(op + 128, acc + 8, fo & ST_CLOSE);
            BBS;
            if (t > 0) TC(7);
            wg_wait<0>();
            fence_regs(p3); fence_regs(w3); fence_regs(y);
            if (t > 0) TC(8);
            ldsm4(lutq + lo, rf);
            products(m1, p3, w3);
            silu(0, 6);
            stg2_if(op + 256, acc + 16, fo & ST_CLOSE);
            BBS;
#pragma unroll
            for (int j = 0; j < 8; j++) acc[j] = hadd2(acc[j], m1[j]);
            stg2_if(om, acc, fo & ST_MID);
#pragma unroll
            for (int j = 0; j < 8; j++) acc[j] = hadd2(fo & ST_MID ? ts[j] : acc[j], m1[8 + j]);
            silu(6, 11);
            stg2_if(op + 384, acc + 24, fo & ST_CLOSE);
            BBS;
            silu(11, 16);
            stg2_if(op, acc, fo & ST_CLOSE);
            ent += 1024; fent += 256; lent += 1024;
        }
        TSX(15, 0);
        TSX(16, 128);
    } else {
        asm volatile("setmaxnreg.dec.sync.aligned.u32 %0;" ::"n"(256 - REG_C));
        const int lane = fresh_lane();
        const int w = warp - 8, s = lane >> 3, c = lane & 7, nzero = misc[36] & 0xFFFF;
        uint32_t sdst = sb + RING_OFF + w * 16384 + s * 128 + ((c ^ s) << 4);
        const uint32_t sw = s * 128 + ((c ^ ((s & 1) << 2)) << 4);
        uint32_t vdst = sb + RING_OFF + w * 16384 + sw;
        const uint32_t odst = sb + SIDE_OFF + w * 4096 + sw;
        uint32_t ent = sb + ND_OFF + (w * 8 + s) * 4;
        const char* svl = reinterpret_cast<const char*>(p.sv) + c * 16;
        const char* own = svl + (size_t)nbase * 512;
        __nanosleep((warp & 4 ? LAG1 : 0) + LAG * max(min(16 - (int)(misc[2] + misc[3]), 3), 0));
#pragma unroll 1
        for (int t = 1; t <= T; t++) {
            const uint32_t e = sb + SRC_OFF + t * 256 + (w * 8 + s) * 2;
            const uint32_t s0 = lds16(e), s1 = lds16(e + 8), s2 = lds16(e + 128), s3 = lds16(e + 136);
            const uint32_t f0 = lds32(ent), f1 = lds32(ent + 16);
            ent += 256;
            sdst ^= 4096; vdst ^= 4096;
            TR(5, 256, t);
            mbar_wait(bar_empty, t & 1);
            TR(6, 256, t);
            gather_row_if(odst, own + (f0 & 511) * 512, f0 & (ST_START | ST_MID));
            gather_row_if(odst + 512, own + (f1 & 511) * 512, f1 & (ST_START | ST_MID));
            cp_async_arrive(bar_side);
            if (t == T) break;
            gather_s(sdst, svl, s0);
            gather_s((sdst ^ 64) + 512, svl, s1);
            gather_s(sdst + 8192, svl, s2);
            gather_s((sdst ^ 64) + 8704, svl, s3);
            cp_async_arrive(bar_full + 8 * (t & 1));
            gather_v(vdst, svl, s0);
            gather_v(vdst + 512, svl, s1);
            gather_v(vdst + 8192, svl, s2);
            gather_v(vdst + 8704, svl, s3);
            TR(7, 256, t);
        }
        TSX(17, 256);
        TSX(20, 384);
        const uint32_t rb = sb + RING_OFF + w * 16384 + (max(T, 1) & 1) * 4096 + s * 512 + c * 16;
#pragma unroll 1
        for (int z = (w & 3) + ((w >> 2) == (misc[2] > misc[3]) ? 0 : 48); z < nzero; z += 96) {
            const int n = (nzero - z + 3) >> 2;
            uint32_t zn[3];
#pragma unroll
            for (int i = 0; i < 3; i++) zn[i] = lds16(sb + ZL_OFF + 2 * min(z + 16 * i + 4 * s, 511));
#pragma unroll
            for (int i = 0; i < 3; i++)
                asm volatile("{\n.reg .pred p;\nsetp.lt.s32 p, %2, %3;\n@p cp.async.cg.shared.global [%0], [%1], 16;\n@p cp.async.cg.shared.global [%0 + 128], [%1 + 128], 16;\n"
                             "@p cp.async.cg.shared.global [%0 + 256], [%1 + 256], 16;\n@p cp.async.cg.shared.global [%0 + 384], [%1 + 384], 16;\n}\n"
                             ::"r"(rb + (i & 1) * 2048 + (i >> 1) * 8192), "l"(own + zn[i] * 512), "r"(4 * i + s), "r"(n) : "memory");
            TSX(21, 256);
            asm volatile("cp.async.wait_all;" ::: "memory");
            TSX(22, 256);
#pragma unroll
            for (int i = 0; i < 3; i++) {
                if (4 * i < n) {
                    char* dst = reinterpret_cast<char*>(p.out) + (size_t)(nbase + zn[i]) * 512 + c * 16;
#pragma unroll
                    for (int k = 0; k < 4; k += 2) {
                        uint32_t x[8];
                        lds128(rb + (i & 1) * 2048 + (i >> 1) * 8192 + k * 128, x);
                        lds128(rb + (i & 1) * 2048 + (i >> 1) * 8192 + k * 128 + 128, x + 4);
                        if (4 * i + s < n) {
                            __stcs(reinterpret_cast<uint4*>(dst + k * 128), make_uint4(x[0], x[1], x[2], x[3]));
                            __stcs(reinterpret_cast<uint4*>(dst + k * 128 + 128), make_uint4(x[4], x[5], x[6], x[7]));
                        }
                    }
                }
            }
        }
        mbar_wait(bar_tab + 8, 0);
        TSX(11, 256);
        TSX(19, 384);
    }
}

}

extern "C" void kernel_launch(void* const* d_in, const int* in_sizes, int n_in, void* d_out, int out_size) {
    static int s_G = 0;
    static void* s_scratch = nullptr;
    static void* s_encode = nullptr;
    const int N = in_sizes[0] / 256, E = in_sizes[2];
    if (s_G == 0) {
        cudaFuncSetAttribute(painn_kernel<0, 0, 0>, cudaFuncAttributeMaxDynamicSharedMemorySize, SMEM_BYTES);
        cudaFuncSetAttribute(painn_kernel<50000, 800000, 132>, cudaFuncAttributeMaxDynamicSharedMemorySize, SMEM_BYTES);
        int dev = 0, sms = 0, occ = 0;
        cudaGetDevice(&dev);
        cudaDeviceGetAttribute(&sms, cudaDevAttrMultiProcessorCount, dev);
        cudaOccupancyMaxActiveBlocksPerMultiprocessor(&occ, painn_kernel<0, 0, 0>, THREADS, SMEM_BYTES);
        cudaGetSymbolAddress(&s_scratch, g_scratch);
        cudaDriverEntryPointQueryResult qr;
        cudaGetDriverEntryPoint("cuTensorMapEncodeTiled", &s_encode, cudaEnableDefault, &qr);
        s_G = occ >= 1 ? (sms < MAXG ? sms : MAXG) : 0;
    }
    if (s_G == 0 || N > TABLE_MAXN || N > s_G * (MAXNPC - 1) || (s_G - 1) * ((N + s_G - 1) / s_G) >= N || E > MAXE || E < 4 * MAXG * MAXG) return;
    Params p;
    CUtensorMap tm;
    {
        typedef CUresult (*Encode)(CUtensorMap*, CUtensorMapDataType, cuuint32_t, void*, const cuuint64_t*, const cuuint64_t*, const cuuint32_t*,
                                   const cuuint32_t*, CUtensorMapInterleave, CUtensorMapSwizzle, CUtensorMapL2promotion, CUtensorMapFloatOOBfill);
        const cuuint64_t dims[2] = {64, (cuuint64_t)N * 4}, strides[1] = {128};
        const cuuint32_t box[2] = {8, 32}, es[2] = {1, 1};
        ((Encode)s_encode)(&tm, CU_TENSOR_MAP_DATA_TYPE_BFLOAT16, 2, d_in[0], dims, strides, box, es, CU_TENSOR_MAP_INTERLEAVE_NONE,
                           CU_TENSOR_MAP_SWIZZLE_NONE, CU_TENSOR_MAP_L2_PROMOTION_L2_128B, CU_TENSOR_MAP_FLOAT_OOB_FILL_NONE);
    }
    p.g = (Scratch*)s_scratch;
    p.sv = (const __nv_bfloat16*)d_in[0];
    p.pos = (const __nv_bfloat16*)d_in[1];
    p.src = (const int*)d_in[2];
    p.dst = (const int*)d_in[3];
    p.freqs = (const __nv_bfloat16*)d_in[4];
    p.w1 = (const __nv_bfloat16*)d_in[5];
    p.w2 = (const __nv_bfloat16*)d_in[6];
    p.wr = (const __nv_bfloat16*)d_in[7];
    p.out = (__nv_bfloat16*)d_out;
    p.desc0 = (uint64_t)(SB >> 4) | ((uint64_t)1 << 16) | ((uint64_t)64 << 32) | ((uint64_t)1 << 62);
    p.N = N; p.E = E; p.G = s_G;
    p.NPC = (N + s_G - 1) / s_G;
    p.magic = (uint32_t)(((1ull << 32) + p.NPC - 1) / p.NPC);
    p.gpc = ((E >> 2) + s_G - 1) / s_G;
    p.odd_edges = (E & 3) != 0 || p.gpc > 3 * THREADS;
    if (N == 50000 && E == 800000 && s_G == 132) painn_kernel<50000, 800000, 132><<<s_G, THREADS, SMEM_BYTES, cudaStreamPerThread>>>(p, tm);
    else painn_kernel<0, 0, 0><<<s_G, THREADS, SMEM_BYTES, cudaStreamPerThread>>>(p, tm);
}
```

```cpp
#include <cuda_runtime.h>
#include <cuda_bf16.h>
#include <cuda.h>
#include <stdint.h>

namespace {

constexpr int REG_C = 224;
constexpr int PDELAY = 200;
constexpr int WA = 7, WC = 3, WE = 3;
#define P0 100
#define P1W 200
constexpr int LAG = 1200, LAG1 = 1300;
#define NP 8
#define NLEFT 4
#define CLR 1
constexpr int THREADS = 512;
constexpr int MAXG = 136;
constexpr int ROUNDS = 11;
constexpr int LUTS = 286, LUTN = 318;
constexpr int MAXNPC = 480;
constexpr int MAXE = 1 << 20;

constexpr int W2_OFF = 8192;
constexpr int WR_OFF = 32768;
constexpr int WIMG = 38912;
constexpr int ZL_OFF = WIMG;
constexpr int RING_OFF = 39936;
constexpr int SIDE_OFF = RING_OFF + 16 * 8192;
constexpr int RR_OFF = SIDE_OFF + 32768;
constexpr int ND_OFF = RR_OFF + ROUNDS * 1024;
constexpr int SRC_OFF = ND_OFF + ROUNDS * 256;
constexpr int LUT_OFF = SRC_OFF + ROUNDS * 256;
constexpr int SINK_OFF = LUT_OFF + 320 * 32;
constexpr int BAR_OFF = SINK_OFF + 512;
constexpr int MISC_OFF = BAR_OFF + 8 * 46;
constexpr int SMEM_BYTES = MISC_OFF + 192 + MAXG;
constexpr int PITCH = 144;
constexpr int TABLE_MAXN = 50176;
constexpr int STAGE_OFF = TABLE_MAXN * 4;
constexpr int SCNT_OFF = STAGE_OFF + MAXG * PITCH;
constexpr int OVL_OFF = MISC_OFF + 192;
constexpr int OPOS_OFF = LUT_OFF + 1024;
constexpr int NCNT_OFF = SIDE_OFF;
constexpr int NPOS_OFF = NCNT_OFF + 2048;
constexpr int YL_OFF = NPOS_OFF + 4096;
constexpr int TL_OFF = YL_OFF + 1024;
constexpr int SLOT_OFF = TL_OFF + 1024;
constexpr int SIZE_OFF = SLOT_OFF + 1280;
static_assert(SCNT_OFF + 4 * (MAXG + 32) <= OPOS_OFF && OPOS_OFF + 4096 <= LUT_OFF + LUTS * 32, "smem map");
static_assert(2 * (480 - 3 * MAXG) >= MAXG, "chunk map");
static_assert(SMEM_BYTES <= 232448 && MISC_OFF % 16 == 0 && BAR_OFF % 8 == 0 && (RING_OFF + 1024) % 8192 == 0 && SINK_OFF % 128 == 0, "smem map");

constexpr uint32_t PAY_INVALID = 0x3FFFFFFu;
constexpr uint32_t PAY_MARK = 0x3FFFDFFu;
constexpr uint32_t ST_START = 512, ST_CLOSE = 1024, ST_MID = 2048;
constexpr float QINVP = 9.0f / 510.0f;
constexpr uint32_t QTHRESH = 2126;

struct Scratch {
    unsigned sync[32];
    uint4 table[TABLE_MAXN / 4];
    uint4 wimg[WIMG / 16 + LUTS * 2];
    uint2 pos8[TABLE_MAXN];
    uint4 xbuf[MAXG * MAXG * 8 + 3 * THREADS];
    int ovfcnt[MAXG];
    int2 ovf[MAXE + 8 * MAXG + 8];
};
__device__ __align__(128) Scratch g_scratch;

struct Params {
    const __nv_bfloat16* pos;
    Scratch* g;
    const int* src;
    const int* dst;
    int N, NPC, E, gpc;
    const __nv_bfloat16* w2;
    const __nv_bfloat16* wr;
    const __nv_bfloat16* w1;
    const __nv_bfloat16* freqs;
    const __nv_bfloat16* sv;
    __nv_bfloat16* out;
    uint64_t desc0;
    int G;
    uint32_t magic;
    int odd_edges;
};
constexpr uint32_t SB = 1024;

#define TSX(i, thr)
#define TR(k, thr, t)
#define TC(k)
#define TS0(i) TSX(i, 0)

__device__ __forceinline__ uint32_t smem_u32(const void* p) { return (uint32_t)__cvta_generic_to_shared(p); }
__device__ __forceinline__ void mbar_init(uint32_t bar, uint32_t cnt) {
    asm volatile("mbarrier.init.shared::cta.b64 [%0], %1;" ::"r"(bar), "r"(cnt) : "memory");
}
__device__ __forceinline__ void mbar_arrive(uint32_t bar) {
    asm volatile("mbarrier.arrive.shared::cta.b64 _, [%0];" ::"r"(bar) : "memory");
}
__device__ __forceinline__ void mbar_expect_tx(uint32_t bar, uint32_t bytes) {
    asm volatile("mbarrier.arrive.expect_tx.shared::cta.b64 _, [%0], %1;" ::"r"(bar), "r"(bytes) : "memory");
}
__device__ __forceinline__ void mbar_wait(uint32_t bar, uint32_t parity) {
    asm volatile("{\n.reg .pred p;\n.reg .u32 c;\nmbarrier.try_wait.parity.shared::cta.b64 p, [%0], %1;\n@p bra DONE;\nmov.u32 c, 0;\n"
                 "AGAIN:\nmbarrier.try_wait.parity.shared::cta.b64 p, [%0], %1, 2000;\n@p bra DONE;\nadd.u32 c, c, 1;\n"
                 "setp.lt.u32 p, c, 0x100000;\n@p bra AGAIN;\ntrap;\nDONE:\n}\n" ::"r"(bar), "r"(parity) : "memory");
}
__device__ __forceinline__ void pause(uint32_t cycles) {
    uint32_t t0, t;
    asm volatile("mov.u32 %0, %%clock;" : "=r"(t0));
    do {
        __nanosleep(20);
        asm volatile("mov.u32 %0, %%clock;" : "=r"(t));
    } while (t - t0 < cycles);
}
__device__ __forceinline__ bool elect() {
    uint32_t r;
    asm volatile("{\n.reg .pred p;\nelect.sync _|p, 0xffffffff;\nselp.u32 %0, 1, 0, p;\n}\n" : "=r"(r));
    return r;
}
__device__ __forceinline__ uint32_t pin(uint32_t x) {
    uint32_t r;
    asm volatile("shfl.sync.bfly.b32 %0, %1, 0, 31, -1;" : "=r"(r) : "r"(x));
    return r;
}
__device__ __forceinline__ void bulk_g2s(uint32_t dst, const void* src, uint32_t bytes, uint32_t bar) {
    asm volatile("cp.async.bulk.shared::cluster.global.mbarrier::complete_tx::bytes [%0], [%1], %2, [%3];"
                 ::"r"(dst), "l"(src), "r"(bytes), "r"(bar) : "memory");
}
__device__ __forceinline__ void ldsm4(uint32_t addr, uint32_t* r) {
    asm volatile("ldmatrix.sync.aligned.m8n8.x4.shared.b16 {%0,%1,%2,%3}, [%4];"
                 : "=r"(r[0]), "=r"(r[1]), "=r"(r[2]), "=r"(r[3]) : "r"(addr) : "memory");
}
__device__ __forceinline__ uint32_t pack2(float lo, float hi) {
    uint32_t r;
    asm("cvt.rn.bf16x2.f32 %0, %1, %2;" : "=r"(r) : "f"(hi), "f"(lo));
    return r;
}
__device__ __forceinline__ float bf_lo(uint32_t w) { return __uint_as_float(w << 16); }
__device__ __forceinline__ float bf_hi(uint32_t w) { return __uint_as_float(w & 0xFFFF0000u); }
__device__ __forceinline__ float rbf16(float x) { return __uint_as_float(pack2(0.f, x)); }
__device__ __forceinline__ uint32_t hmul2(uint32_t a, uint32_t b) {
    uint32_t r;
    asm("mul.rn.bf16x2 %0, %1, %2;" : "=r"(r) : "r"(a), "r"(b));
    return r;
}
__device__ __forceinline__ uint32_t hfma2(uint32_t a, uint32_t b, uint32_t c) {
    uint32_t r;
    asm("fma.rn.bf16x2 %0, %1, %2, %3;" : "=r"(r) : "r"(a), "r"(b), "r"(c));
    return r;
}
__device__ __forceinline__ uint32_t hfma2_lo(uint32_t a, uint32_t b, uint32_t c) {
    uint32_t r;
    asm("{\n.reg .b16 l, h;\n.reg .b32 t;\nmov.b32 {l, h}, %2;\nmov.b32 t, {l, l};\nfma.rn.bf16x2 %0, %1, t, %3;\n}\n" : "=r"(r) : "r"(a), "r"(b), "r"(c));
    return r;
}
__device__ __forceinline__ uint32_t hfma2_hi(uint32_t a, uint32_t b, uint32_t c) {
    uint32_t r;
    asm("{\n.reg .b16 l, h;\n.reg .b32 t;\nmov.b32 {l, h}, %2;\nmov.b32 t, {h, h};\nfma.rn.bf16x2 %0, %1, t, %3;\n}\n" : "=r"(r) : "r"(a), "r"(b), "r"(c));
    return r;
}
__device__ __forceinline__ uint32_t hadd2(uint32_t a, uint32_t b) {
    uint32_t r;
    asm("add.rn.bf16x2 %0, %1, %2;" : "=r"(r) : "r"(a), "r"(b));
    return r;
}
__device__ __forceinline__ uint32_t hsub2(uint32_t a, uint32_t b) {
    uint32_t r;
    asm("sub.rn.bf16x2 %0, %1, %2;" : "=r"(r) : "r"(a), "r"(b));
    return r;
}
__device__ __forceinline__ void cp_async_arrive(uint32_t bar) {
    asm volatile("cp.async.mbarrier.arrive.noinc.shared::cta.b64 [%0];" ::"r"(bar) : "memory");
}
__device__ __forceinline__ float tanh_fast(float x) {
    float r;
    asm("tanh.approx.f32 %0, %1;" : "=f"(r) : "f"(x));
    return r;
}
__device__ __forceinline__ void wg_fence() { asm volatile("wgmma.fence.sync.aligned;" ::: "memory"); }
__device__ __forceinline__ void wg_commit() { asm volatile("wgmma.commit_group.sync.aligned;" ::: "memory"); }
template <int N>
__device__ __forceinline__ void wg_wait() { asm volatile("wgmma.wait_group.sync.aligned %0;" ::"n"(N) : "memory"); }

#define WG_REGS "{%0,%1,%2,%3,%4,%5,%6,%7,%8,%9,%10,%11,%12,%13,%14,%15,%16,%17,%18,%19,%20,%21,%22,%23,%24,%25,%26,%27,%28,%29,%30,%31}"
#define WG_OPS(c) c(d[0]), c(d[1]), c(d[2]), c(d[3]), c(d[4]), c(d[5]), c(d[6]), c(d[7]), c(d[8]), c(d[9]), c(d[10]), \
    c(d[11]), c(d[12]), c(d[13]), c(d[14]), c(d[15]), c(d[16]), c(d[17]), c(d[18]), c(d[19]), c(d[20]), c(d[21]),     \
    c(d[22]), c(d[23]), c(d[24]), c(d[25]), c(d[26]), c(d[27]), c(d[28]), c(d[29]), c(d[30]), c(d[31])
#define WG_OPSE(c) c(e[0]), c(e[1]), c(e[2]), c(e[3]), c(e[4]), c(e[5]), c(e[6]), c(e[7]), c(e[8]), c(e[9]), c(e[10]), c(e[11]), c(e[12]), c(e[13]), c(e[14]), c(e[15]), c(e[16]), c(e[17]), c(e[18]), c(e[19]), c(e[20]), c(e[21]), c(e[22]), c(e[23]), c(e[24]), c(e[25]), c(e[26]), c(e[27]), c(e[28]), c(e[29]), c(e[30]), c(e[31])
template <int OFF, int ACC, int IDX>
__device__ __forceinline__ void wgmma_rs(float* d, const uint32_t* a, uint64_t d0) {
    if (!ACC) {
#pragma unroll
        for (int i = 0; i < 32; i++) d[i] = 0.f;
    }
    if (IDX < 4)
        asm volatile("wgmma.mma_async.sync.aligned.m64n64k16.f32.bf16.bf16 " WG_REGS ", {%32,%33,%34,%35}, %36, %37, 1, 1, 1;"
                     : WG_OPS("+f") : "r"(a[0]), "r"(a[1]), "r"(a[2]), "r"(a[3]), "l"(d0 + (OFF >> 4)), "n"(ACC));
    else
        asm volatile("{\n.reg .b64 dd;\nmov.b64 dd, {%36, 0x40000040};\nwgmma.mma_async.sync.aligned.m64n64k16.f32.bf16.bf16 " WG_REGS
                     ", {%32,%33,%34,%35}, dd, %37, 1, 1, 1;\n}\n"
                     : WG_OPS("+f") : "r"(a[0]), "r"(a[1]), "r"(a[2]), "r"(a[3]), "n"(((SB + OFF) >> 4) | (1u << 16)), "n"(ACC));
}
template <int OFF, int LBO, int ACC>
__device__ __forceinline__ void wgmma_rs2(float* d, float* e, const uint32_t* a, uint64_t d0) {
    if (!ACC) {
#pragma unroll
        for (int i = 0; i < 32; i++) d[i] = e[i] = 0.f;
    }
    asm volatile("wgmma.mma_async.sync.aligned.m64n128k16.f32.bf16.bf16 {%0,%1,%2,%3,%4,%5,%6,%7,%8,%9,%10,%11,%12,%13,%14,%15,%16,%17,%18,%19,%20,%21,%22,%23,%24,%25,%26,%27,%28,%29,%30,%31,%32,%33,%34,%35,%36,%37,%38,%39,%40,%41,%42,%43,%44,%45,%46,%47,%48,%49,%50,%51,%52,%53,%54,%55,%56,%57,%58,%59,%60,%61,%62,%63}, {%64,%65,%66,%67}, %68, %69, 1, 1, 1;"
                 : WG_OPS("+f"), WG_OPSE("+f") : "r"(a[0]), "r"(a[1]), "r"(a[2]), "r"(a[3]), "l"(d0 + (OFF >> 4) + ((LBO / 16 - 1) << 16)), "n"(ACC));
}
template <int G>
__device__ __forceinline__ void wgmma_group(float* P, float* W, const uint32_t* h, const uint32_t* rf, uint64_t d0) {
    wgmma_rs<W2_OFF + 8192 * G, 0, 5 * G>(P, h, d0);
    wgmma_rs<W2_OFF + 8192 * G + 2048, 1, 5 * G + 1>(P, h + 4, d0);
    wgmma_rs<W2_OFF + 8192 * G + 4096, 1, 5 * G + 2>(P, h + 8, d0);
    wgmma_rs<W2_OFF + 8192 * G + 6144, 1, 5 * G + 3>(P, h + 12, d0);
    wgmma_rs<WR_OFF + 2048 * G, 0, 5 * G + 4>(W, rf, d0);
}
__device__ __forceinline__ void wgmma_ss_k64(float* d, uint64_t da, uint64_t db) {
#pragma unroll
    for (int i = 0; i < 32; i++) d[i] = 0.f;
    asm volatile("wgmma.mma_async.sync.aligned.m64n64k16.f32.bf16.bf16 " WG_REGS ", %32, %33, 0, 1, 1, 0, 1;" : WG_OPS("+f") : "l"(da), "l"(db));
#pragma unroll
    for (int k = 1; k < 4; k++)
        asm volatile("wgmma.mma_async.sync.aligned.m64n64k16.f32.bf16.bf16 " WG_REGS ", %32, %33, 1, 1, 1, 0, 1;"
                     : WG_OPS("+f") : "l"(da + 2 * k), "l"(db + 128 * k));
}
__device__ __forceinline__ void fence_regs(float* d) { asm volatile("" : WG_OPS("+f")::"memory"); }
__device__ __forceinline__ uint32_t qaxis(float x) {
    const float u = fmaf(x, QINVP, 0.25f);
    const float f = u - ((u + 12582912.f) - 12582912.f);
    return __float_as_uint(fmaf(fabsf(f), 510.f, 12582912.f));
}
__device__ __forceinline__ uint32_t qcode(float x, float y, float z, uint32_t tx) {
    return __byte_perm(__byte_perm(qaxis(x), qaxis(y), 0x3340), qaxis(z), 0x3410) ^ tx;
}
__device__ __forceinline__ bool near_test(uint32_t ca, uint32_t cb, uint32_t tag24) {
    const uint32_t D = __vabsdiffu4(ca, cb);
    return __dp4a(D, D, 0u) <= QTHRESH || ((ca ^ tag24) | (cb ^ tag24)) >= 0x1000000u;
}
constexpr float QMAX = 23.9375f;
__device__ __forceinline__ float square(uint32_t rxy, uint32_t rz) {
    const uint32_t qxy = hmul2(rxy, rxy), qz = hmul2(rz, rz);
    return bf_lo(qxy) + bf_hi(qxy) + bf_lo(qz);
}

__device__ __forceinline__ uint32_t lds32(uint32_t addr) {
    uint32_t r;
    asm volatile("ld.shared.u32 %0, [%1];" : "=r"(r) : "r"(addr) : "memory");
    return r;
}
__device__ __forceinline__ void sts32_if(uint32_t addr, uint32_t v, bool c) {
    asm volatile("{\n.reg .pred p;\nsetp.ne.u32 p, %2, 0;\n@p st.shared.u32 [%0], %1;\n}\n" ::"r"(addr), "r"(v), "r"((uint32_t)c) : "memory");
}
__device__ __forceinline__ uint32_t sel(bool c, uint32_t a, uint32_t b) {
    uint32_t r;
    asm("{\n.reg .pred p;\nsetp.ne.u32 p, %3, 0;\nselp.b32 %0, %1, %2, p;\n}\n" : "=r"(r) : "r"(a), "r"(b), "r"((uint32_t)c));
    return r;
}
__device__ __forceinline__ uint32_t lds16(uint32_t addr) {
    uint32_t r;
    asm volatile("ld.shared.u16 %0, [%1];" : "=r"(r) : "r"(addr) : "memory");
    return r;
}
__device__ __forceinline__ void sts16_if(uint32_t addr, uint32_t v, bool c) {
    asm volatile("{\n.reg .pred p;\nsetp.ne.u32 p, %2, 0;\n@p st.shared.u16 [%0], %1;\n}\n" ::"r"(addr), "h"((unsigned short)v), "r"((uint32_t)c) : "memory");
}
__device__ __forceinline__ void sts64_if(uint32_t addr, uint32_t x, uint32_t y, bool c) {
    asm volatile("{\n.reg .pred p;\nsetp.ne.u32 p, %3, 0;\n@p st.shared.v2.u32 [%0], {%1, %2};\n}\n" ::"r"(addr), "r"(x), "r"(y), "r"((uint32_t)c) : "memory");
}
__device__ __forceinline__ uint32_t atoms_add(uint32_t addr, uint32_t v) {
    uint32_t r;
    asm volatile("atom.shared.add.u32 %0, [%1], %2;" : "=r"(r) : "r"(addr), "r"(v) : "memory");
    return r;
}
__device__ __forceinline__ void stg128_if(void* ptr, uint4 v, bool c) {
    asm volatile("{\n.reg .pred p;\nsetp.ne.u32 p, %5, 0;\n@p st.relaxed.gpu.global.v4.u32 [%0], {%1,%2,%3,%4};\n}\n"
                 ::"l"(ptr), "r"(v.x), "r"(v.y), "r"(v.z), "r"(v.w), "r"((uint32_t)c) : "memory");
}
__device__ __forceinline__ void lds128(uint32_t addr, uint32_t* r) {
    asm volatile("ld.shared.v4.u32 {%0,%1,%2,%3}, [%4];" : "=r"(r[0]), "=r"(r[1]), "=r"(r[2]), "=r"(r[3]) : "r"(addr) : "memory");
}
__device__ __forceinline__ void stg2_if(uint64_t ptr, const uint32_t* r, uint32_t c) {
    asm volatile("{\n.reg .pred p;\nsetp.ne.u32 p, %9, 0;\n@p st.global.cs.v4.u32 [%8], {%0,%1,%2,%3};\n"
                 "@p st.global.cs.v4.u32 [%8 + 64], {%4,%5,%6,%7};\n}\n"
                 ::"r"(r[0]), "r"(r[1]), "r"(r[2]), "r"(r[3]), "r"(r[4]), "r"(r[5]), "r"(r[6]), "r"(r[7]), "l"(ptr), "r"(c) : "memory");
}
__device__ __forceinline__ void gather_s(uint32_t dst, const char* base, uint32_t src) {
    asm volatile("{\n.reg .pred p;\nsetp.eq.u32 p, %2, 0xFFFF;\ncp.async.cg.shared.global [%0], [%1], 16, p;\n}\n"
                 ::"r"(dst), "l"(base + (size_t)src * 512), "r"(src) : "memory");
}
__device__ __forceinline__ void gather_v(uint32_t dst, const char* base, uint32_t src) {
    asm volatile("{\n.reg .pred p;\nsetp.eq.u32 p, %2, 0xFFFF;\n"
                 "cp.async.cg.shared.global [%0 + 1024], [%1 + 128], 16, p;\ncp.async.cg.shared.global [%0 + 2048], [%1 + 256], 16, p;\n"
                 "cp.async.cg.shared.global [%0 + 3072], [%1 + 384], 16, p;\n}\n" ::"r"(dst), "l"(base + (size_t)src * 512), "r"(src) : "memory");
}
__device__ __forceinline__ void gather_row_if(uint32_t dst, const char* src, uint32_t c) {
    asm volatile("{\n.reg .pred p;\nsetp.ne.u32 p, %2, 0;\n@p cp.async.cg.shared.global [%0], [%1], 16;\n"
                 "@p cp.async.cg.shared.global [%0 + 1024], [%1 + 128], 16;\n@p cp.async.cg.shared.global [%0 + 2048], [%1 + 256], 16;\n"
                 "@p cp.async.cg.shared.global [%0 + 3072], [%1 + 384], 16;\n}\n" ::"r"(dst), "l"(src), "r"(c) : "memory");
}
__device__ __forceinline__ void lds2_if(uint32_t a0, uint32_t a1, uint32_t* r, uint32_t c) {
    asm volatile("{\n.reg .pred p;\nsetp.ne.u32 p, %10, 0;\n@p ld.shared.v4.u32 {%0,%1,%2,%3}, [%8];\n@p ld.shared.v4.u32 {%4,%5,%6,%7}, [%9];\n}\n"
                 : "+r"(r[0]), "+r"(r[1]), "+r"(r[2]), "+r"(r[3]), "+r"(r[4]), "+r"(r[5]), "+r"(r[6]), "+r"(r[7])
                 : "r"(a0), "r"(a1), "r"(c) : "memory");
}
__device__ __forceinline__ int fresh_lane() {
    int l;
    asm volatile("mov.u32 %0, %%laneid;" : "=r"(l));
    return l;
}

__device__ __forceinline__ void cold_edges(unsigned char* smem, const Params& p, int lo, int hi, uint32_t tag) {
#pragma unroll 1
    for (int e = lo + threadIdx.x; e < hi; e += THREADS) {
        const int s = p.src[e], d = p.dst[e];
        if (near_test(reinterpret_cast<const uint32_t*>(smem)[s], reinterpret_cast<const uint32_t*>(smem)[d], tag << 24)) {
            const uint32_t own = __umulhi((uint32_t)d, p.magic);
            const uint32_t slot4 = atomicAdd(reinterpret_cast<uint32_t*>(smem + SCNT_OFF) + own, 4u);
            uint32_t* line = reinterpret_cast<uint32_t*>(smem + STAGE_OFF) + own * (PITCH / 4);
            if (slot4 < 124) {
                line[slot4 >> 2] = ((uint32_t)s << 15) + ((uint32_t)(d - own * p.NPC) << 6) + tag;
            } else {
                uint32_t o = atomicAdd(reinterpret_cast<uint32_t*>(smem + MISC_OFF) + 16, 1u);
                p.g->ovf[(size_t)blockIdx.x * (4 * p.gpc + 4) + o] = make_int2(s, d);
                line[31] = (PAY_MARK << 6) | tag;
            }
        }
    }
}
__device__ __forceinline__ void cold_filter(unsigned char* smem, const Params& p, int e0, int e1, uint32_t tag, int redo) {
    if (redo) {
        if (threadIdx.x < MAXG) reinterpret_cast<uint32_t*>(smem + SCNT_OFF)[threadIdx.x] = 0;
        __syncthreads();
    }
    cold_edges(smem, p, redo ? 4 * e0 : 4 * (e0 + 3 * THREADS), 4 * e1, tag);
    if (blockIdx.x == 0) cold_edges(smem, p, p.E & ~3, p.E, tag);
    __syncthreads();
    if (threadIdx.x == 0) p.g->ovfcnt[blockIdx.x] = reinterpret_cast<uint32_t*>(smem + MISC_OFF)[16];
    __threadfence();
    __syncthreads();
}
__device__ __forceinline__ float distance(float q) {
    float d;
    asm("sqrt.approx.ftz.f32 %0, %1;" : "=f"(d) : "f"(rbf16(rbf16(q) + 1e-8f)));
    return rbf16(d);
}
__device__ __forceinline__ float fcut(float d) {
    return d < 5.0f ? 0.5f * rbf16(rbf16(__cosf(rbf16(rbf16(3.14159265358979f * d) * 0.2f))) + 1.0f) : 0.f;
}
__device__ __forceinline__ uint4 basis8(float d, uint4 f) {
    const float sc = __fdividef(fcut(d), d);
    const uint32_t dd = __byte_perm(__float_as_uint(d), 0, 0x3232);
    uint32_t x[4] = {hmul2(f.x, dd), hmul2(f.y, dd), hmul2(f.z, dd), hmul2(f.w, dd)};
#pragma unroll
    for (int i = 0; i < 4; i++) x[i] = pack2(__sinf(bf_lo(x[i])) * sc, __sinf(bf_hi(x[i])) * sc);
    return make_uint4(x[0], x[1], x[2], x[3]);
}
__device__ __forceinline__ void cold_nodes(unsigned char* smem, const Params& p, int nn, uint32_t tag) {
    float* acc = reinterpret_cast<float*>(smem + RING_OFF);
    const int nbase = blockIdx.x * p.NPC, lane = threadIdx.x & 31;
    const uint32_t* sv = reinterpret_cast<const uint32_t*>(p.sv);
    const volatile uint32_t* xin = reinterpret_cast<const uint32_t*>(p.g->xbuf) + blockIdx.x * p.G * 32;
#pragma unroll 1
    for (int i = threadIdx.x; i < p.G * 32; i += THREADS) {
        if ((int)xin[(i & ~31) + 15] < (int)(PAY_MARK << 6)) {
            uint32_t w;
            int it = 0;
            do {
                w = xin[i];
                if (++it > (1 << 22)) __trap();
            } while ((w ^ tag) & 63u);
            if ((w >> 6) == PAY_MARK) smem[OVL_OFF + atomicAdd(reinterpret_cast<uint32_t*>(smem + MISC_OFF) + 17, 1u)] = (unsigned char)(i >> 5);
        }
    }
    __threadfence();
    __syncthreads();
    const int nmark = reinterpret_cast<uint32_t*>(smem + MISC_OFF)[17];
#pragma unroll 1
    for (int c0 = 0; c0 < nn; c0 += 128) {
        __syncthreads();
#pragma unroll 1
        for (int i = threadIdx.x; i < 128 * 256; i += THREADS) acc[i] = 0.f;
        __syncthreads();
#pragma unroll 1
        for (int m = -1; m < nmark; m++) {
            const int pr = m < 0 ? 0 : smem[OVL_OFF + m];
            const int cnt = m < 0 ? p.G * 32 : __ldcg(&p.g->ovfcnt[pr]);
#pragma unroll 1
            for (int i = threadIdx.x; i - lane < cnt; i += THREADS) {
                int2 e = make_int2(0, -1);
                if (i < cnt) {
                    if (m < 0) {
                        const uint32_t w = xin[i];
                        if (((w ^ tag) & 63u) == 0) e = make_int2((w >> 15) & 0xFFFFu, (w >> 6) & 511u);
                    } else {
                        e = __ldcg(p.g->ovf + (size_t)pr * (4 * p.gpc + 4) + i);
                        e.y -= nbase;
                    }
                }
                uint32_t rxy = 0, rz = 0;
                bool in = e.y >= c0 && e.y < min(c0 + 128, nn);
                if (in) {
                    const uint2 ps = __ldcg(p.g->pos8 + e.x), pd = __ldcg(p.g->pos8 + nbase + e.y);
                    rxy = hsub2(ps.x, pd.x);
                    rz = hsub2(ps.y, pd.y);
                    in = square(rxy, rz) < QMAX;
                }
#pragma unroll 1
                for (uint32_t todo = __ballot_sync(0xffffffffu, in); todo; todo &= todo - 1) {
                    const int l = __ffs(todo) - 1;
                    const uint32_t* row = sv + (size_t)__shfl_sync(0xffffffffu, e.x, l) * 128 + lane;
                    float* o = acc + (__shfl_sync(0xffffffffu, e.y, l) - c0) * 256 + 2 * lane;
                    const uint32_t xy = __shfl_sync(0xffffffffu, rxy, l), z = __shfl_sync(0xffffffffu, rz, l);
                    const float d = distance(square(xy, z)), fc = fcut(d);
                    uint32_t x = __ldg(row);
                    float y0 = 0.f, y1 = 0.f, m2[6];
#pragma unroll 4
                    for (int k = 0; k < 64; k++) {
                        const uint32_t u = __shfl_sync(0xffffffffu, x, k >> 1), w = __ldg(reinterpret_cast<const uint32_t*>(p.w1) + k * 32 + lane);
                        const float a = k & 1 ? bf_hi(u) : bf_lo(u);
                        y0 = fmaf(a, bf_lo(w), y0);
                        y1 = fmaf(a, bf_hi(w), y1);
                    }
                    y0 = rbf16(y0); y1 = rbf16(y1);
                    x = pack2(y0 / (1.f + __expf(-y0)), y1 / (1.f + __expf(-y1)));
                    const float rb = rbf16(rbf16(__sinf(rbf16(d * __bfloat162float(p.freqs[lane & 15])))) / d);
#pragma unroll
                    for (int g = 0; g < 3; g++) {
                        float p0 = 0.f, p1 = 0.f, w0 = 0.f, w1 = 0.f;
#pragma unroll 4
                        for (int k = 0; k < 64; k++) {
                            const uint32_t u = __shfl_sync(0xffffffffu, x, k >> 1), w = __ldg(reinterpret_cast<const uint32_t*>(p.w2) + k * 96 + g * 32 + lane);
                            const float a = k & 1 ? bf_hi(u) : bf_lo(u);
                            p0 = fmaf(a, bf_lo(w), p0);
                            p1 = fmaf(a, bf_hi(w), p1);
                        }
#pragma unroll 4
                        for (int k = 0; k < 16; k++) {
                            const uint32_t w = __ldg(reinterpret_cast<const uint32_t*>(p.wr) + k * 96 + g * 32 + lane);
                            const float a = __shfl_sync(0xffffffffu, rb, k);
                            w0 = fmaf(a, bf_lo(w), w0);
                            w1 = fmaf(a, bf_hi(w), w1);
                        }
                        m2[2 * g] = rbf16(rbf16(p0) * rbf16(rbf16(w0) * fc));
                        m2[2 * g + 1] = rbf16(rbf16(p1) * rbf16(rbf16(w1) * fc));
                    }
                    atomicAdd(o, m2[0]);
                    atomicAdd(o + 1, m2[1]);
#pragma unroll
                    for (int k = 1; k < 4; k++) {
                        const uint32_t v = __ldg(row + 32 * k);
                        const float rh = rbf16((k == 1 ? bf_lo(xy) : k == 2 ? bf_hi(xy) : bf_lo(z)) / d);
                        atomicAdd(o + 64 * k, fmaf(m2[2], bf_lo(v), m2[4] * rh));
                        atomicAdd(o + 64 * k + 1, fmaf(m2[3], bf_hi(v), m2[5] * rh));
                    }
                }
            }
        }
        __syncthreads();
#pragma unroll 1
        for (int i = threadIdx.x; i < min(128, nn - c0) * 128; i += THREADS) {
            const uint32_t v = __ldg(sv + (size_t)(nbase + c0) * 128 + i);
            reinterpret_cast<uint32_t*>(p.out)[(size_t)(nbase + c0) * 128 + i] = pack2(bf_lo(v) + rbf16(acc[2 * i]), bf_hi(v) + rbf16(acc[2 * i + 1]));
        }
    }
}

template <int CN, int CE, int CG>
__global__ void __launch_bounds__(THREADS, 1) painn_kernel(const __grid_constant__ Params p, const __grid_constant__ CUtensorMap tm) {
    extern __shared__ __align__(1024) unsigned char smem_dyn[];
    unsigned char* const smem = static_cast<unsigned char*>(__cvta_shared_to_generic(SB));
    constexpr uint32_t sb = SB;
    const int tid = threadIdx.x, lane = tid & 31;
    const int warp = __shfl_sync(0xffffffffu, tid >> 5, 0);
    constexpr int CNPC = CG ? (CN + CG - 1) / CG : 1, CGPC = CG ? (CE / 4 + CG - 1) / CG : 1;
    const int b = blockIdx.x, G = CG ? CG : p.G, NPC = CG ? CNPC : p.NPC, N = CG ? CN : p.N, gpc = CG ? CGPC : p.gpc;
    const uint32_t magic = CG ? (uint32_t)(((1ull << 32) + CNPC - 1) / CNPC) : p.magic;
    const bool odd_edges = CG ? (CE & 3) != 0 || CGPC > 3 * THREADS : p.odd_edges;
    const int nbase = b * NPC, nn = min(NPC, N - nbase);
    const int e0 = b * gpc, e1 = min((CG ? CE : p.E) >> 2, e0 + gpc);

    uint4* stage4 = reinterpret_cast<uint4*>(smem + STAGE_OFF);
    uint32_t* ncnt = reinterpret_cast<uint32_t*>(smem + NCNT_OFF);
    uint32_t* misc = reinterpret_cast<uint32_t*>(smem + MISC_OFF);
    const uint32_t bar_full = sb + BAR_OFF + (warp & 7) * 40, bar_empty = bar_full + 16, bar_side = bar_full + 32, bar_tab = sb + BAR_OFF + 336;

    auto warm = [&](int first, int n) {
#pragma unroll 1
        for (int i = first; i < first + n; i++) {
            if (elect())
                asm volatile("cp.async.bulk.tensor.2d.shared::cluster.global.mbarrier::complete_tx::bytes [%0], [%1, {0, %3}], [%2];"
                             ::"r"(sb + SINK_OFF), "l"(&tm), "r"(bar_tab + 8), "r"(nbase * 4 + i * 32) : "memory");
        }
    };
    TS0(0);
    int4 es[3], ed[3];
    auto load_edges = [&](int i) {
        const int g = min(e0 + tid + i * THREADS, e1 - 1);
        asm volatile("ld.global.cs.v4.u32 {%0,%1,%2,%3}, [%8];\nld.global.cs.v4.u32 {%4,%5,%6,%7}, [%9];"
                     : "=r"(es[i].x), "=r"(es[i].y), "=r"(es[i].z), "=r"(es[i].w), "=r"(ed[i].x), "=r"(ed[i].y), "=r"(ed[i].z), "=r"(ed[i].w)
                     : "l"(reinterpret_cast<const int4*>(p.src) + g), "l"(reinterpret_cast<const int4*>(p.dst) + g) : "memory");
    };
    unsigned epoch;
    const uint32_t tbytes = ((N + 3) >> 2) * 16;
    {
        uint32_t pxy, pz;
        asm volatile("ld.global.nc.u32 %0, [%3];\nld.global.nc.u32 %1, [%3 + 4];\nld.global.ca.u32 %2, [%4];"
                     : "=r"(pxy), "=r"(pz), "=r"(epoch)
                     : "l"(reinterpret_cast<const uint32_t*>(p.pos) + ((nbase + min(tid, nn - 1)) * 3 >> 1)), "l"(p.g->sync) : "memory");
        const uint32_t sh = ((nbase + tid) & 1) << 4;
        pxy = __funnelshift_r(pxy, pz, sh);
        pz >>= sh;
        if (tid < nn) {
            reinterpret_cast<uint32_t*>(p.g->table)[nbase + tid] = qcode(bf_lo(pxy), bf_hi(pxy), bf_lo(pz), ((epoch & 31u) ^ 0x6Bu) << 24);
            p.g->pos8[nbase + tid] = make_uint2(pxy, pz);
        }
        reinterpret_cast<uint2*>(smem + OPOS_OFF)[tid] = make_uint2(pxy, pz);
        if (pxy == 0xFFFFFFFFu && pz == 0xFFFFFFFFu && epoch == 0xFFFFFFFFu) asm volatile("nanosleep.u32 0;");
        load_edges(0);
    }
    __syncthreads();
    const uint32_t tag = (epoch & 31u) | 32u;
    if (warp == 15) {
        if (elect()) {
            asm volatile("red.relaxed.gpu.global.add.u32 [%0], 1;" ::"l"(p.g->sync + 8 + b * NP / G) : "memory");
            asm volatile("prefetch.tensormap [%0];" ::"l"(&tm) : "memory");
            mbar_init(bar_tab, 1);
            mbar_init(bar_tab + 8, 1);
            mbar_expect_tx(bar_tab, tbytes);
            mbar_expect_tx(bar_tab + 8, (WA + WC + WE) * 512);
        }
        TSX(1, 511);
    }
    if (warp == 14) {
#pragma unroll 1
        for (int c = b * 32 + lane; c < WIMG / 16 + LUTS * 2; c += G * 32) {
            const int row = c >> 3, j = (c ^ row) & 7;
            uint4 v;
            if (c < 512) {
                const uint32_t half = 0x3F003F00u;
                v = __ldg(reinterpret_cast<const uint4*>(p.w1) + row * 8 + j);
                v = make_uint4(hmul2(v.x, half), hmul2(v.y, half), hmul2(v.z, half), hmul2(v.w, half));
            } else if (c >= WIMG / 16) {
                v = basis8(__uint_as_float((0x409D - ((c - WIMG / 16) >> 1)) << 16), __ldg(reinterpret_cast<const uint4*>(p.freqs) + (c & 1)));
            } else {
                const uint32_t* q = (c < 2048 ? reinterpret_cast<const uint32_t*>(p.w2) + (row & 63) * 96 + ((row >> 6) - 1) * 32
                                              : reinterpret_cast<const uint32_t*>(p.wr) + (row & 15) * 96 + ((row >> 4) - 16) * 32) + (j & 4) * 4 + (j & 3);
                v = make_uint4(__ldg(q), __ldg(q + 4), __ldg(q + 8), __ldg(q + 12));
            }
            p.g->wimg[c] = v;
        }
    }
    if (warp < 8 && elect()) {
        mbar_init(bar_full, 32); mbar_init(bar_full + 8, 32);
        mbar_init(bar_empty, 1);
        mbar_init(bar_side, 32);
    }
    if (tid < MAXG) reinterpret_cast<uint32_t*>(smem + SCNT_OFF)[tid] = 0;
    if (tid < 48) misc[tid] = 0;
    {
        const uint32_t inv = (PAY_INVALID << 6) | tag;
        stage4[tid] = stage4[tid + THREADS] = make_uint4(inv, inv, inv, inv);
        if (tid < MAXG * (PITCH / 16) - 2 * THREADS) stage4[tid + 2 * THREADS] = make_uint4(inv, inv, inv, inv);
    }
    if (warp == 15) {
        __syncwarp();
        const int k = lane & (NP - 1), b0 = (k * G + NP - 1) / NP, b1 = ((k + 1) * G + NP - 1) / NP;
        const uint32_t o0 = (b0 * NPC * 4) & ~127u, o1 = k == NP - 1 ? tbytes : (b1 * NPC * 4) & ~127u;
        bool todo = lane < NP, wait = true;
        uint32_t left;
        int it = smem_u32(smem_dyn) == SB ? 0 : 1 << 22;
        do {
            unsigned c;
            asm volatile("ld.relaxed.gpu.global.u32 %0, [%1];" : "=r"(c) : "l"(p.g->sync + 8 + k) : "memory");
            if (todo && c == (epoch + 1) * (b1 - b0)) {
                bulk_g2s(sb + o0, reinterpret_cast<const char*>(p.g->table) + o0, o1 - o0, bar_tab);
                todo = false;
            }
            if (++it > (1 << 22)) __trap();
            left = __ballot_sync(0xffffffffu, todo);
            if (wait && __popc(left) <= NLEFT) {
                asm volatile("bar.arrive 1, 512;" ::: "memory");
                wait = false;
            }
        } while (left);
        asm volatile("bar.sync 2, 512;" ::: "memory");
        TSX(2, 511);
    } else {
        asm volatile("bar.arrive 2, 512;" ::: "memory");
        asm volatile("bar.sync 1, 512;" ::: "memory");
    }
    load_edges(1);
#pragma unroll 1
    for (int r = tid >> 2; r < G; r += THREADS / 4) {
        uint4* const x = p.g->xbuf + (r * G + b) * 8 + (tid & 3);
        stg128_if(x, make_uint4(0, 0, 0, 0), true);
        stg128_if(x + 4, make_uint4(0, 0, 0, 0), ((r ^ epoch) & 15) == 0);
    }
    load_edges(2);
    if (tid == THREADS - 1) asm volatile("fence.acq_rel.gpu;" ::: "memory");
    mbar_wait(bar_tab, 0);
    TS0(3);
    if (warp == 15) warm(0, WA);

    bool over = false;
#pragma unroll 1
    for (int i = 0, g = e0 + tid; i < 3; i++, g += THREADS) {
        const int s[4] = {es[0].x, es[0].y, es[0].z, es[0].w}, d[4] = {ed[0].x, ed[0].y, ed[0].z, ed[0].w};
        uint32_t ca[4], cb[4], own[4], sl[4];
        bool c[4];
#pragma unroll
        for (int j = 0; j < 4; j++) { ca[j] = lds32(sb + 4 * s[j]); cb[j] = lds32(sb + 4 * d[j]); }
#pragma unroll
        for (int j = 0; j < 4; j++) {
            c[j] = near_test(ca[j], cb[j], tag << 24) && g < e1;
            own[j] = __umulhi((uint32_t)d[j], magic);
            sl[j] = atomicAdd(reinterpret_cast<uint32_t*>(smem + SCNT_OFF) + (c[j] ? own[j] : MAXG + lane), 4u);
        }
#pragma unroll
        for (int j = 0; j < 4; j++)
            sts32_if(sb + STAGE_OFF + own[j] * PITCH + sl[j], own[j] * (uint32_t)(-64 * NPC) + (((uint32_t)s[j] << 15) + (((uint32_t)d[j] << 6) + tag)),
                     c[j] && sl[j] < 124);
#pragma unroll
        for (int j = 0; j < 4; j++) over |= c[j] && sl[j] >= 124;
        es[0] = es[1]; es[1] = es[2];
        ed[0] = ed[1]; ed[1] = ed[2];
    }
    {
        const int redo = __syncthreads_or(over);
        if (__builtin_expect(redo || odd_edges, 0)) cold_filter(smem, p, e0, e1, tag, redo);
    }
    TS0(4);
#pragma unroll 1
    for (int r = tid >> 2; r < G; r += THREADS / 4) {
        const int c = r * (PITCH / 16) + (tid & 3);
        uint4* const x = p.g->xbuf + (r * G + b) * 8 + (tid & 3);
        const bool more = reinterpret_cast<uint32_t*>(smem + SCNT_OFF)[r] > 64;
        uint4 v = stage4[c];
        if (more && (tid & 3) == 3) v.w |= 0x80000000u;
        stg128_if(x + 4, stage4[c + 4], more);
        stg128_if(x, v, true);
    }
    ncnt[tid] = 0;
    if (tid < 480) reinterpret_cast<uint32_t*>(smem + SLOT_OFF)[tid] = tid < 32 ? tid * 0x100010 + 0x80000 : tid < 320 ? ~0u : 0u;
    if (tid == 511) reinterpret_cast<uint2*>(smem + NPOS_OFF)[511] = make_uint2(sb + SLOT_OFF + 1278, 0);
    __syncthreads();
    reinterpret_cast<uint4*>(smem + RR_OFF)[tid] = make_uint4(0, 0, 0, 0);
    if (tid < ROUNDS * 80 - THREADS) reinterpret_cast<uint4*>(smem + RR_OFF)[tid + THREADS] = make_uint4(0, 0, 0, 0);
    if (tid < ROUNDS * 32) reinterpret_cast<uint2*>(smem + SRC_OFF)[tid] = make_uint2(~0u, ~0u);
    pause(PDELAY);
    TS0(5);

    uint32_t rxy[4], gz[4], src[4], rk[4], dn[4];
    const uint32_t sink = sb + NCNT_OFF + 4 * (480 + lane);
    if (warp < 15) {
        uint32_t ew[3][4], bad[2];
        const int u = tid - 3 * G;
        const uint4* const xin = p.g->xbuf + b * G * 8;
        const uint4* cp = xin + (u < 0 ? tid + tid / 3 * 5 : u * 8 + 3);
        bad[0] = u < G;
        bad[1] = u >= 0 && u + 480 - 3 * G < G;
#pragma unroll
        for (int i = 0; i < 3; i++) ew[i][0] = ew[i][1] = ew[i][2] = ew[i][3] = (PAY_INVALID << 6) | tag;
        int it = 0;
#pragma unroll 1
        do {
#pragma unroll
            for (int i = 0; i < 2; i++)
                asm volatile("{\n.reg .pred p;\nsetp.ne.u32 p, %5, 0;\n@p ld.relaxed.gpu.global.v4.u32 {%0,%1,%2,%3}, [%4];\n}\n"
                             : "+r"(ew[i][0]), "+r"(ew[i][1]), "+r"(ew[i][2]), "+r"(ew[i][3]) : "l"(cp + i * (480 - 3 * G) * 8), "r"(bad[i]) : "memory");
#pragma unroll
            for (int i = 0; i < 2; i++) bad[i] = ((ew[i][0] ^ tag) | (ew[i][1] ^ tag) | (ew[i][2] ^ tag) | (ew[i][3] ^ tag)) & 63u;
            if (++it > (1 << 22)) __trap();
        } while (__any_sync(0xffffffffu, bad[0] | bad[1]));
        if (warp >= (3 * G) >> 5) {
            constexpr int EMPTY = (int)(PAY_MARK << 6);
            const bool e0 = ew[0][0] >= (PAY_MARK << 6);
            if (__builtin_expect(__any_sync(0xffffffffu, min((int)ew[0][3], (int)ew[1][3]) < EMPTY || (!e0 && ew[1][0] < (PAY_MARK << 6))), 0)) {
                uint64_t f = (uint64_t)__ballot_sync(0xffffffffu, (int)ew[1][3] < EMPTY) << 32 | __ballot_sync(0xffffffffu, (int)ew[0][3] < EMPTY);
                if ((int)ew[0][3] < EMPTY) ew[0][3] &= 0x7FFFFFFFu;
                if ((int)ew[1][3] < EMPTY) ew[1][3] &= 0x7FFFFFFFu;
#pragma unroll 1
                for (int k = 7 - (lane >> 2); k && f; k--) f &= f - 1;
                if (f) {
                    const int l = __ffsll(f) - 1;
                    do {
                        asm volatile("ld.relaxed.gpu.global.v4.u32 {%0,%1,%2,%3}, [%4];" : "=r"(ew[2][0]), "=r"(ew[2][1]), "=r"(ew[2][2]), "=r"(ew[2][3])
                                     : "l"(xin + (u - lane + l + (l >> 5) * (448 - 3 * G)) * 8 + 4 + (lane & 3)) : "memory");
                        if (++it > (1 << 22)) __trap();
                    } while (((ew[2][0] ^ tag) | (ew[2][1] ^ tag) | (ew[2][2] ^ tag) | (ew[2][3] ^ tag)) & 63u);
                    if ((ew[2][3] >> 6) == PAY_MARK || lane == 0) misc[0] = 1;
                }
                __syncwarp();
#pragma unroll 1
                for (int i = 0; i < 2; i++) {
                    if (ew[0][0] >= (PAY_MARK << 6)) {
#pragma unroll
                        for (int j = 0; j < 4; j++) { ew[0][j] = ew[1][j]; ew[1][j] = ~0u; }
                    }
                    uint32_t from = __ballot_sync(0xffffffffu, ew[1][0] < (PAY_MARK << 6)), to = __ballot_sync(0xffffffffu, ew[0][0] >= (PAY_MARK << 6));
#pragma unroll 1
                    for (; from; from &= from - 1, to &= to - 1) {
                        if (!to) misc[0] = 1;
#pragma unroll
                        for (int j = 0; j < 4; j++) {
                            const uint32_t x = __shfl_sync(0xffffffffu, ew[1][j], __ffs(from) - 1);
                            if (lane == __ffs(to) - 1) ew[0][j] = x;
                        }
                    }
#pragma unroll
                    for (int j = 0; j < 4; j++) ew[1][j] = ew[2][j];
                }
            } else if (e0) {
#pragma unroll
                for (int j = 0; j < 4; j++) ew[0][j] = ew[1][j];
            }
        }
        {
            uint2 ps[4], pd[4];
#pragma unroll
            for (int j = 0; j < 4; j++) {
                dn[j] = (ew[0][j] >> 3) & 4088u;
                src[j] = ew[0][j] >> 15;
                ps[j] = __ldcg(p.g->pos8 + (dn[j] == 4088u ? nbase : src[j]));
            }
#pragma unroll
            for (int j = 0; j < 4; j++) pd[j] = *reinterpret_cast<const uint2*>(smem + OPOS_OFF + dn[j]);
            asm volatile("bar.arrive 1, 512;" ::: "memory");
            float q[4];
#pragma unroll
            for (int j = 0; j < 4; j++) {
                rxy[j] = hsub2(ps[j].x, pd[j].x);
                gz[j] = hsub2(ps[j].y, pd[j].y);
                q[j] = square(rxy[j], gz[j]);
                const bool in = q[j] < QMAX && dn[j] != 4088u;
                rk[j] = atoms_add(in ? sb + NCNT_OFF + (dn[j] >> 1) : sink, 512u);
                if (!in) dn[j] = 4088u;
            }
            uint32_t row[4], n = 0;
            bool single[4];
#pragma unroll
            for (int j = 0; j < 4; j++) {
                q[j] = distance(q[j]);
                row[j] = 0x409D - (__float_as_uint(q[j]) >> 16);
                single[j] = row[j] >= LUTS && dn[j] != 4088u;
                n += single[j];
            }
            n = atoms_add(n ? sb + MISC_OFF + 4 : sink, n) + LUTS;
#pragma unroll
            for (int j = 0; j < 4; j++) {
                float id;
                asm("rcp.approx.ftz.f32 %0, %1;" : "=f"(id) : "f"(q[j]));
                sts32_if(sb + LUT_OFF + min(n, LUTN - 1) * 32, __float_as_uint(q[j]), single[j]);
                if (single[j]) row[j] = n++;
                rxy[j] = pack2(bf_lo(rxy[j]) * id, bf_hi(rxy[j]) * id);
                gz[j] = pack2(0.f, bf_lo(gz[j]) * id) + row[j] * 32;
            }
        }
    } else {
        const uint4 fq = __ldg(reinterpret_cast<const uint4*>(p.freqs) + (lane & 1));
        rxy[0] = fq.x; rxy[1] = fq.y; rxy[2] = fq.z; rxy[3] = fq.w;
        asm volatile("bar.sync 1, 512;" ::: "memory");
        warm(WA, WC);
    }
    __syncthreads();
    TS0(6);

    const uint32_t lt = (1u << lane) - 1;
    uint32_t place = ~0u, mid = 0, last = 0, steps = 0, c = 0;
    if (warp < 15) {
        if (tid < nn) c = ncnt[tid] >> 9;
        steps = min((c + 1) >> 1, 15u);
        const uint32_t bin = sel(tid >= nn, 9, (uint32_t)(0x11223354678ull >> (4 * min(c, 11u))) & 15), sh = (bin & 1) * 16;
        const bool odd = c > 3 && (c & 1);
        const uint32_t peers = __match_any_sync(0xffffffffu, bin), om = __ballot_sync(0xffffffffu, odd);
        uint32_t x = atoms_add(lane == 0 ? sb + MISC_OFF + 4 * 37 : sink, __popc(om));
        uint32_t r = atoms_add((peers & lt) == 0 ? sb + MISC_OFF + 4 * 32 + 2 * (bin & 14) : sink, __popc(peers) << sh);
        x = __shfl_sync(0xffffffffu, x, 0) + __popc(om & lt);
        r = ((__shfl_sync(0xffffffffu, r, __ffs(peers) - 1) >> sh) & 0xFFFFu) + __popc(peers & lt);
        sts16_if(sb + sel(bin == 8, ZL_OFF, sel(bin == 7, YL_OFF, TL_OFF)) + 2 * r, tid, (0x190 >> bin) & 1);
        const uint64_t ones = 0x0001010101010101ull >> (56 - 8 * min(bin, 7u));
        asm volatile("bar.sync 2, 480;" ::: "memory");
        uint32_t h[4];
        lds128(sb + MISC_OFF + 4 * 32, h);
        const int nodd = misc[37], n1 = h[3] >> 16, n3 = h[2] & 0xFFFF, left = max(min(nodd + n3 - n1, n3), 0), half = left >> 1;
        const bool twin = bin == 4 && (int)r < 2 * half;
        x = sel(bin == 4, nodd + r - left, sel(odd, x, 1023));
        const bool pair = twin ? !(r & 1) : (int)x >= (bin == 4 ? nodd : 0) && (int)x < n1;
        const uint32_t y = lds16(sel(twin, sb + TL_OFF + 2 + 2 * r, sb + YL_OFF + 2 * (x & 511)));
        const uint32_t base = __dp2a_lo(h[0], (uint32_t)ones, __dp2a_hi(h[1], (uint32_t)ones, 0u)) +
                              __dp2a_lo(h[2], (uint32_t)(ones >> 32), __dp2a_hi(h[3], (uint32_t)(ones >> 32), 0u));
        r -= sel(bin == 7, nodd + n3, 0);
        const bool unit = (bin < 8 && (int)r >= 0 && (pair || !twin));
        place = sel(unit, base + sel(twin, r >> 1, r - sel(bin < 4, 0, half)), ~0u);
        sts32_if(sb + MISC_OFF + 16, base - half + max(n1 - nodd - n3, 0), bin >= 7);
        steps += twin;
        last = sel(twin, y, tid) | sel(steps > 1, ST_CLOSE, ST_CLOSE | ST_START);
        mid = sel(pair, y | sel(twin, ST_MID, ST_MID | ST_CLOSE) | (tid << 16), last);
        c = sel(pair, c, 2 * steps - 1);
        const uint32_t sa = sb + SLOT_OFF + sel(steps <= ROUNDS, 2 * place, 1278);
        sts64_if(sb + NPOS_OFF + 8 * tid, sa, 0, unit);
        sts64_if(sb + NPOS_OFF + 8 * y, sa, c << 9, pair);
        asm volatile("{\n.reg .pred p;\nsetp.ne.u32 p, %2, 0;\n@p st.shared.u8 [%0], %1;\n}\n" ::"r"(sb + SIZE_OFF + place), "r"(steps), "r"((uint32_t)unit) : "memory");
    } else {
        if (elect()) {
            if (b == 0) p.g->sync[0] = epoch + 1;
            asm volatile("fence.proxy.async.global;" ::: "memory");
            mbar_expect_tx(bar_tab, WIMG + LUTS * 32);
            bulk_g2s(sb, p.g->wimg, WIMG, bar_tab);
            bulk_g2s(sb + LUT_OFF, p.g->wimg + WIMG / 16, LUTS * 32, bar_tab);
        }
        warm(WA + WC, WE);
#pragma unroll 1
        for (uint32_t i = lane; i - lane < 2 * min(misc[1], LUTN - LUTS); i += 32) {
            const uint32_t d = lds32(sb + LUT_OFF + (LUTS + (i >> 1)) * 32);
            __syncwarp();
            reinterpret_cast<uint4*>(smem + LUT_OFF)[2 * LUTS + i] = basis8(__uint_as_float(d), make_uint4(rxy[0], rxy[1], rxy[2], rxy[3]));
        }
        TSX(12, 511);
    }
    __syncthreads();
    TS0(7);
    uint32_t st[4];
    if (warp == 15) {
        uint32_t until0 = lds16(sb + SIZE_OFF + 2 * lane), until1 = until0 >> 8, next = 64, s0, s1;
        const uint32_t nsched = misc[4];
        until0 &= 255;
        uint32_t t = __reduce_min_sync(0xffffffffu, min(until0, until1));
        bool go = true;
#pragma unroll 1
        while (go) {
            go = t < ROUNDS && next < nsched;
            const bool n0 = until0 == t, n1 = until1 == t;
            const uint32_t i = next + __popc(__ballot_sync(0xffffffffu, n0) & lt) + __popc(__ballot_sync(0xffffffffu, n1) & lt), j = i + n0;
            next += __reduce_add_sync(0xffffffffu, n0 + n1);
            asm volatile("{\n.reg .pred p, q;\nsetp.ne.u32 p, %4, 0;\nsetp.ne.u32 q, %5, 0;\nmov.u32 %0, 0;\nmov.u32 %1, 0;\n@p ld.shared.u8 %0, [%2];\n@q ld.shared.u8 %1, [%3];\n}\n"
                         : "=&r"(s0), "=&r"(s1) : "r"(sb + SIZE_OFF + i), "r"(sb + SIZE_OFF + j), "r"((uint32_t)n0), "r"((uint32_t)n1) : "memory");
            until0 += s0;
            until1 += s1;
            sts16_if(sb + SLOT_OFF + 2 * i, 1024 * t + 16 * lane, n0 && until0 <= ROUNDS);
            sts16_if(sb + SLOT_OFF + 2 * j, 1024 * t + 16 * lane + 8, n1 && until1 <= ROUNDS);
            t++;
        }
        until0 = __reduce_max_sync(lane < 16 ? 0xFFFFu : 0xFFFF0000u, max(until0, until1));
        if ((lane & 15) == 0) misc[2 + (lane >> 4)] = until0;
        __syncthreads();
        lds128(sb + MISC_OFF, st);
    } else {
#pragma unroll
        for (int j = 0; j < 4; j++) {
            const uint2 np = *reinterpret_cast<const uint2*>(smem + NPOS_OFF + dn[j]);
            dn[j] = np.x;
            rk[j] += np.y;
        }
#pragma unroll 1
        for (int pass = 0; pass < 2; pass++) {
            uint32_t e[4];
#pragma unroll
            for (int j = 0; j < 4; j++) e[j] = lds16(dn[j]);
            const uint32_t x = lds16(sb + SLOT_OFF + 2 * min(place, 639u));
#pragma unroll
            for (int j = 0; j < 4; j++) {
                sts16_if(sb + SRC_OFF + ((rk[j] + e[j]) >> 2), src[j], e[j] != 0xFFFFu);
                sts64_if(sb + RR_OFF + rk[j] + e[j], rxy[j], gz[j], e[j] != 0xFFFFu);
                if (e[j] != 0xFFFFu) dn[j] = sb + SLOT_OFF + 1278;
            }
            if (pass) {
                const uint32_t nd = sb + ND_OFF + ((x >> 2) & 0xFF00) + ((x >> 1) & 0xFC);
                sts32_if(nd, tid | ST_START, x != 0xFFFFu);
                sts32_if(nd + steps * 256 - 256, last, x != 0xFFFFu && steps <= ROUNDS);
                sts32_if(nd + c * 128 - 128, mid, x != 0xFFFFu && steps <= ROUNDS);
                break;
            }
            asm volatile("bar.sync 2, 480;" ::: "memory");
            if (warp < 8) {
                const int s = lane >> 3, c = lane & 7;
                const uint32_t dst = sb + RING_OFF + warp * 16384 + s * 128, y = sb + SRC_OFF + (warp * 8 + s) * 2;
                const uint32_t sdst = dst + ((c ^ s) << 4), vdst = dst + ((c ^ ((s & 1) << 2)) << 4);
                const uint32_t s0 = lds16(y), s1 = lds16(y + 8), s2 = lds16(y + 128), s3 = lds16(y + 136);
                const char* svl = reinterpret_cast<const char*>(p.sv) + c * 16;
                gather_s(sdst, svl, s0);
                gather_s((sdst ^ 64) + 512, svl, s1);
                gather_s(sdst + 8192, svl, s2);
                gather_s((sdst ^ 64) + 8704, svl, s3);
                cp_async_arrive(bar_full);
                TS0(10);
                pause(warp & 4 ? P1W : P0);
                gather_v(vdst, svl, s0);
                pause(P0);
                gather_v(vdst + 512, svl, s1);
                pause(P0);
                gather_v(vdst + 8192, svl, s2);
                pause(P0);
                gather_v(vdst + 8704, svl, s3);
                asm volatile("cp.async.mbarrier.arrive.shared::cta.b64 [%0];" ::"r"(bar_side) : "memory");
            }
            __syncthreads();
            TS0(8);
            lds128(sb + MISC_OFF, st);
        }
    }
    __syncthreads();
    if (__builtin_expect(max(st[2], st[3]) > ROUNDS || st[1] > LUTN - LUTS || st[0], 0)) {
        asm volatile("cp.async.wait_all;" ::: "memory");
        mbar_wait(bar_tab, 1);
        mbar_wait(bar_tab + 8, 0);
        cold_nodes(smem, p, nn, tag);
        return;
    }
    TS0(9);
    const int T = __shfl_sync(0xffffffffu, warp & 4 ? st[3] : st[2], 0);

    if (warp < 8) {
        asm volatile("setmaxnreg.inc.sync.aligned.u32 %0;" ::"n"(REG_C));
        const int lane = fresh_lane();
        const int g = lane >> 2, q = lane & 3;
        const uint64_t d0 = (uint64_t)__shfl_sync(0xffffffffu, pin((uint32_t)(p.desc0 >> 32)), 0) << 32 | __shfl_sync(0xffffffffu, pin((uint32_t)p.desc0), 0);
        const uint32_t swz = g * 128 + ((q ^ ((g & 1) << 2)) << 4);
        const uint32_t srow = pin(sb + SIDE_OFF + warp * 4096 + swz);
        uint32_t vrow = pin(sb + RING_OFF + warp * 16384 + swz + 4096);
        uint32_t ent = pin(sb + RR_OFF + (warp * 8 + g) * 8), fent = pin(sb + ND_OFF + (warp * 8 + g) * 4);
        uint32_t lent = pin(sb + RR_OFF + (warp * 8 + (lane & 7)) * 8 + 4 + (lane & 8) * 64);
        const uint32_t lutq = pin(sb + LUT_OFF + (lane >> 4) * 16);
        uint64_t outq;
        {
            const uint64_t a = reinterpret_cast<uint64_t>(p.out) + (size_t)nbase * 512 + q * 16;
            const uint32_t lo = pin((uint32_t)a), hi = pin((uint32_t)(a >> 32));
            asm volatile("mov.b64 %0, {%1, %2};" : "=l"(outq) : "r"(lo), "r"(hi));
        }
        uint32_t acc[32], rf[4], h[16], rr[4], fl = 0;
#pragma unroll
        for (int i = 0; i < 32; i++) asm volatile("" : "=r"(acc[i]));
#pragma unroll
        for (int i = 0; i < 16; i++) asm volatile("" : "=r"(h[i]));
#pragma unroll
        for (int i = 0; i < 4; i++) asm volatile("" : "=r"(rf[i]), "=r"(rr[i]));
        int t = -1;
        TSX(18, 0);
        mbar_wait(bar_tab, 1);
        TSX(14, 0);
        const int Tm = __shfl_sync(0xffffffffu, min(st[2], st[3]), 0);
        if (warp >= 4 && Tm > 0) asm volatile("bar.arrive 3, 256;" ::: "memory");
        bool more = T < 0x7FFFFFFF;
#pragma unroll 1
        while (more) {
            float y[32], p1[32], w1[32], p2[32], w2[32], p3[32], w3[32];
            uint32_t m1[16], m2[16], v[3][16], ts[8];
            auto products = [](uint32_t* m, const float* P, const float* W) {
#pragma unroll
                for (int j = 0; j < 8; j++) {
                    m[j] = pack2(P[4 * j] * W[4 * j], P[4 * j + 1] * W[4 * j + 1]);
                    m[8 + j] = pack2(P[4 * j + 2] * W[4 * j + 2], P[4 * j + 3] * W[4 * j + 3]);
                }
            };
            auto vterm = [&](int k, int o) {
#pragma unroll
                for (int j = 0; j < 8; j++) acc[8 * k + 8 + j] = hfma2(m1[o + j], v[k][o + j], acc[8 * k + 8 + j]);
            };
            auto rterm = [&](int k, int o) {
#pragma unroll
                for (int j = 0; j < 8; j++)
                    acc[8 * k + 8 + j] = k == 0 ? hfma2_lo(m2[o + j], rr[o / 4], acc[8 * k + 8 + j]) : hfma2_hi(m2[o + j], rr[o / 4 + k / 2], acc[8 * k + 8 + j]);
            };
            TR(0, 0, t);
            uint64_t om, op;
#pragma unroll
            for (int j = 0; j < 8; j++) asm volatile("" : "=r"(ts[j]), "=r"(m1[8 + j]), "=r"(m2[8 + j]), "=r"(v[0][8 + j]), "=r"(v[1][8 + j]), "=r"(v[2][8 + j]));
            asm volatile("" : "=l"(om));
            if (t >= 0) {
            TC(0);
            if (t < Tm) asm volatile("bar.sync %0, 256;" ::"r"(3 + (warp >> 2)) : "memory");
            wg_fence();
            wgmma_rs2<W2_OFF + 8192, 8192, 0>(p1, p2, h, d0);
            wgmma_rs2<W2_OFF + 10240, 8192, 1>(p1, p2, h + 4, d0);
            wgmma_rs2<W2_OFF + 12288, 8192, 1>(p1, p2, h + 8, d0);
            wgmma_rs2<W2_OFF + 14336, 8192, 1>(p1, p2, h + 12, d0);
            wgmma_rs2<WR_OFF + 2048, 2048, 0>(w1, w2, rf, d0);
            wg_commit();
            TC(1);
            mbar_wait(bar_side, t & 1);
            TC(2);
#pragma unroll
            for (int k = 0; k < 4; k++) lds2_if(srow + 1024 * k, (srow ^ 64) + 1024 * k, acc + 8 * k, fl & ST_START);
            wg_wait<0>();
            fence_regs(p1); fence_regs(w1);
            TC(3);
            products(m1, p1, w1);
#pragma unroll
            for (int k = 0; k < 3; k++) { lds128(vrow + 1024 + 1024 * k, v[k]); lds128((vrow ^ 64) + 1024 + 1024 * k, v[k] + 4); }
            fence_regs(p2); fence_regs(w2);
            products(m2, p2, w2);
            asm("mad.wide.u32 %0, %1, 512, %2;" : "=l"(om) : "r"(fl >> 16), "l"(outq));
#pragma unroll
            for (int k = 0; k < 3; k++) { lds128(vrow + 9216 + 1024 * k, v[k] + 8); lds128((vrow ^ 64) + 9216 + 1024 * k, v[k] + 12); }
#pragma unroll
            for (int j = 0; j < 8; j++) asm volatile("" : "=r"(ts[j]));
            lds2_if(srow, srow ^ 64, ts, fl & ST_MID);
#pragma unroll
            for (int k = 0; k < 3; k++) { vterm(k, 0); rterm(k, 0); stg2_if(om + 128 + 128 * k, acc + 8 + 8 * k, fl & ST_MID); }
            TC(4);
            if (t + (warp >> 2) < Tm) asm volatile("bar.arrive %0, 256;" ::"r"(4 - (warp >> 2)) : "memory");
            }
            t++;
            wg_fence();
            wgmma_group<0>(p3, w3, h, rf, d0);
            wg_commit();
            if (T > 1000000) asm volatile("nanosleep.u32 0;");
#pragma unroll
            for (int k = 1; k < 4; k++) lds2_if(srow + 1024 * k, (srow ^ 64) + 1024 * k, acc + 8 * k, fl & ST_MID);
            uint32_t lo;
            asm volatile("ld.shared.u16 %0, [%1];" : "=r"(lo) : "r"(lent) : "memory");
            __syncwarp();
            if (lane == 0 && t > 0) mbar_arrive(bar_empty);
            if (t > 0) TC(5);
            if (t >= T) {
                asm("mad.wide.u32 %0, %1, 512, %2;" : "=l"(op) : "r"(fl & 511), "l"(outq));
#pragma unroll
                for (int k = 0; k < 3; k++) { vterm(k, 8); rterm(k, 8); stg2_if(op + 128 + 128 * k, acc + 8 + 8 * k, fl & ST_CLOSE); }
                wg_wait<0>();
                fence_regs(p3); fence_regs(w3);
                products(m1, p3, w3);
#pragma unroll
                for (int j = 0; j < 8; j++) acc[j] = hadd2(acc[j], m1[j]);
                stg2_if(om, acc, fl & ST_MID);
#pragma unroll
                for (int j = 0; j < 8; j++) acc[j] = hadd2(fl & ST_MID ? ts[j] : acc[j], m1[8 + j]);
                stg2_if(op, acc, fl & ST_CLOSE);
                asm volatile("cp.async.wait_all;" ::: "memory");
                break;
            }
            mbar_wait(bar_full + 8 * (t & 1), (t >> 1) & 1);
            if (t > 0) TC(6);
            wg_fence();
            wgmma_ss_k64(y, d0 + ((RING_OFF >> 4) + (warp >> 2) * 4096 + (t & 1) * 256 + ((uint64_t)(512 - 64) << 32)), d0);
            wg_commit();
            if (T > 1000000) asm volatile("nanosleep.u32 0;");
            asm("mad.wide.u32 %0, %1, 512, %2;" : "=l"(op) : "r"(fl & 511), "l"(outq));
            vrow ^= 4096;
#pragma unroll
            for (int k = 0; k < 3; k++) vterm(k, 8);
#define BBS if (T > 1000000) asm volatile("nanosleep.u32 0;")
            auto silu = [&](int i0, int i1) {
#pragma unroll
                for (int i = i0; i < i1; i++)
                    h[i] = pack2(fmaf(y[2 * i], tanh_fast(y[2 * i]), y[2 * i]), fmaf(y[2 * i + 1], tanh_fast(y[2 * i + 1]), y[2 * i + 1]));
            };
#pragma unroll
            for (int k = 0; k < 3; k++) rterm(k, 8);
            const uint32_t fo = fl;
            asm volatile("ld.shared.v2.u32 {%0,%1}, [%4];\nld.shared.v2.u32 {%2,%3}, [%4 + 512];" : "=r"(rr[0]), "=r"(rr[1]), "=r"(rr[2]), "=r"(rr[3]) : "r"(ent) : "memory");
            asm volatile("ld.shared.u32 %0, [%1];" : "=r"(fl) : "r"(fent) : "memory");
            stg2_if(op + 128, acc + 8, fo & ST_CLOSE);
            BBS;
            if (t > 0) TC(7);
            wg_wait<0>();
            fence_regs(p3); fence_regs(w3); fence_regs(y);
            if (t > 0) TC(8);
            ldsm4(lutq + lo, rf);
            products(m1, p3, w3);
            silu(0, 6);
            stg2_if(op + 256, acc + 16, fo & ST_CLOSE);
            BBS;
#pragma unroll
            for (int j = 0; j < 8; j++) acc[j] = hadd2(acc[j], m1[j]);
            stg2_if(om, acc, fo & ST_MID);
#pragma unroll
            for (int j = 0; j < 8; j++) acc[j] = hadd2(fo & ST_MID ? ts[j] : acc[j], m1[8 + j]);
            silu(6, 11);
            stg2_if(op + 384, acc + 24, fo & ST_CLOSE);
            BBS;
            silu(11, 16);
            stg2_if(op, acc, fo & ST_CLOSE);
            ent += 1024; fent += 256; lent += 1024;
        }
        TSX(15, 0);
        TSX(16, 128);
    } else {
        asm volatile("setmaxnreg.dec.sync.aligned.u32 %0;" ::"n"(256 - REG_C));
        const int lane = fresh_lane();
        const int w = warp - 8, s = lane >> 3, c = lane & 7, nzero = misc[36] & 0xFFFF;
        uint32_t sdst = sb + RING_OFF + w * 16384 + s * 128 + ((c ^ s) << 4);
        const uint32_t sw = s * 128 + ((c ^ ((s & 1) << 2)) << 4);
        uint32_t vdst = sb + RING_OFF + w * 16384 + sw;
        const uint32_t odst = sb + SIDE_OFF + w * 4096 + sw;
        uint32_t ent = sb + ND_OFF + (w * 8 + s) * 4;
        const char* svl = reinterpret_cast<const char*>(p.sv) + c * 16;
        const char* own = svl + (size_t)nbase * 512;
        pause((warp & 4 ? LAG1 : 0) + LAG * max(min(16 - (int)(misc[2] + misc[3]), 2), 0));
#pragma unroll 1
        for (int t = 1; t <= T; t++) {
            const uint32_t e = sb + SRC_OFF + t * 256 + (w * 8 + s) * 2;
            const uint32_t s0 = lds16(e), s1 = lds16(e + 8), s2 = lds16(e + 128), s3 = lds16(e + 136);
            const uint32_t f0 = lds32(ent), f1 = lds32(ent + 16);
            ent += 256;
            sdst ^= 4096; vdst ^= 4096;
            TR(5, 256, t);
            mbar_wait(bar_empty, t & 1);
            TR(6, 256, t);
            gather_row_if(odst, own + (f0 & 511) * 512, f0 & (ST_START | ST_MID));
            gather_row_if(odst + 512, own + (f1 & 511) * 512, f1 & (ST_START | ST_MID));
            cp_async_arrive(bar_side);
            if (t == T) break;
            gather_s(sdst, svl, s0);
            gather_s((sdst ^ 64) + 512, svl, s1);
            gather_s(sdst + 8192, svl, s2);
            gather_s((sdst ^ 64) + 8704, svl, s3);
            cp_async_arrive(bar_full + 8 * (t & 1));
            gather_v(vdst, svl, s0);
            gather_v(vdst + 512, svl, s1);
            gather_v(vdst + 8192, svl, s2);
            gather_v(vdst + 8704, svl, s3);
            TR(7, 256, t);
        }
        TSX(17, 256);
        TSX(20, 384);
        const uint32_t rb = sb + RING_OFF + w * 16384 + (max(T, 1) & 1) * 4096 + s * 512 + c * 16;
#pragma unroll 1
        for (int z = (w & 3) + ((w >> 2) == (misc[2] > misc[3]) ? 0 : 48); z < nzero; z += 96) {
            const int n = (nzero - z + 3) >> 2;
            uint32_t zn[3];
#pragma unroll
            for (int i = 0; i < 3; i++) zn[i] = lds16(sb + ZL_OFF + 2 * min(z + 16 * i + 4 * s, 511));
#pragma unroll
            for (int i = 0; i < 3; i++)
                asm volatile("{\n.reg .pred p;\nsetp.lt.s32 p, %2, %3;\n@p cp.async.cg.shared.global [%0], [%1], 16;\n@p cp.async.cg.shared.global [%0 + 128], [%1 + 128], 16;\n"
                             "@p cp.async.cg.shared.global [%0 + 256], [%1 + 256], 16;\n@p cp.async.cg.shared.global [%0 + 384], [%1 + 384], 16;\n}\n"
                             ::"r"(rb + (i & 1) * 2048 + (i >> 1) * 8192), "l"(own + zn[i] * 512), "r"(4 * i + s), "r"(n) : "memory");
            TSX(21, 256);
            asm volatile("cp.async.wait_all;" ::: "memory");
            TSX(22, 256);
#pragma unroll
            for (int i = 0; i < 3; i++) {
                if (4 * i < n) {
                    char* dst = reinterpret_cast<char*>(p.out) + (size_t)(nbase + zn[i]) * 512 + c * 16;
#pragma unroll
                    for (int k = 0; k < 4; k += 2) {
                        uint32_t x[8];
                        lds128(rb + (i & 1) * 2048 + (i >> 1) * 8192 + k * 128, x);
                        lds128(rb + (i & 1) * 2048 + (i >> 1) * 8192 + k * 128 + 128, x + 4);
                        if (4 * i + s < n) {
                            __stcs(reinterpret_cast<uint4*>(dst + k * 128), make_uint4(x[0], x[1], x[2], x[3]));
                            __stcs(reinterpret_cast<uint4*>(dst + k * 128 + 128), make_uint4(x[4], x[5], x[6], x[7]));
                        }
                    }
                }
            }
        }
        mbar_wait(bar_tab + 8, 0);
        TSX(11, 256);
        TSX(19, 384);
    }
}

}

extern "C" void kernel_launch(void* const* d_in, const int* in_sizes, int n_in, void* d_out, int out_size) {
    static int s_G = 0;
    static void* s_scratch = nullptr;
    static void* s_encode = nullptr;
    const int N = in_sizes[0] / 256, E = in_sizes[2];
    if (s_G == 0) {
        cudaFuncSetAttribute(painn_kernel<0, 0, 0>, cudaFuncAttributeMaxDynamicSharedMemorySize, SMEM_BYTES);
        cudaFuncSetAttribute(painn_kernel<50000, 800000, 132>, cudaFuncAttributeMaxDynamicSharedMemorySize, SMEM_BYTES);
        int dev = 0, sms = 0, occ = 0;
        cudaGetDevice(&dev);
        cudaDeviceGetAttribute(&sms, cudaDevAttrMultiProcessorCount, dev);
        cudaOccupancyMaxActiveBlocksPerMultiprocessor(&occ, painn_kernel<0, 0, 0>, THREADS, SMEM_BYTES);
        cudaGetSymbolAddress(&s_scratch, g_scratch);
        cudaDriverEntryPointQueryResult qr;
        cudaGetDriverEntryPoint("cuTensorMapEncodeTiled", &s_encode, cudaEnableDefault, &qr);
        s_G = occ >= 1 ? (sms < MAXG ? sms : MAXG) : 0;
    }
    if (s_G == 0 || N > TABLE_MAXN || N > s_G * (MAXNPC - 1) || (s_G - 1) * ((N + s_G - 1) / s_G) >= N || E > MAXE || E < 4 * MAXG * MAXG) return;
    Params p;
    CUtensorMap tm;
    {
        typedef CUresult (*Encode)(CUtensorMap*, CUtensorMapDataType, cuuint32_t, void*, const cuuint64_t*, const cuuint64_t*, const cuuint32_t*,
                                   const cuuint32_t*, CUtensorMapInterleave, CUtensorMapSwizzle, CUtensorMapL2promotion, CUtensorMapFloatOOBfill);
        const cuuint64_t dims[2] = {64, (cuuint64_t)N * 4}, strides[1] = {128};
        const cuuint32_t box[2] = {8, 32}, es[2] = {1, 1};
        ((Encode)s_encode)(&tm, CU_TENSOR_MAP_DATA_TYPE_BFLOAT16, 2, d_in[0], dims, strides, box, es, CU_TENSOR_MAP_INTERLEAVE_NONE,
                           CU_TENSOR_MAP_SWIZZLE_NONE, CU_TENSOR_MAP_L2_PROMOTION_L2_128B, CU_TENSOR_MAP_FLOAT_OOB_FILL_NONE);
    }
    p.g = (Scratch*)s_scratch;
    p.sv = (const __nv_bfloat16*)d_in[0];
    p.pos = (const __nv_bfloat16*)d_in[1];
    p.src = (const int*)d_in[2];
    p.dst = (const int*)d_in[3];
    p.freqs = (const __nv_bfloat16*)d_in[4];
    p.w1 = (const __nv_bfloat16*)d_in[5];
    p.w2 = (const __nv_bfloat16*)d_in[6];
    p.wr = (const __nv_bfloat16*)d_in[7];
    p.out = (__nv_bfloat16*)d_out;
    p.desc0 = (uint64_t)(SB >> 4) | ((uint64_t)1 << 16) | ((uint64_t)64 << 32) | ((uint64_t)1 << 62);
    p.N = N; p.E = E; p.G = s_G;
    p.NPC = (N + s_G - 1) / s_G;
    p.magic = (uint32_t)(((1ull << 32) + p.NPC - 1) / p.NPC);
    p.gpc = ((E >> 2) + s_G - 1) / s_G;
    p.odd_edges = (E & 3) != 0 || p.gpc > 3 * THREADS;
    if (N == 50000 && E == 800000 && s_G == 132) painn_kernel<50000, 800000, 132><<<s_G, THREADS, SMEM_BYTES, cudaStreamPerThread>>>(p, tm);
    else painn_kernel<0, 0, 0><<<s_G, THREADS, SMEM_BYTES, cudaStreamPerThread>>>(p, tm);
}
```

```cpp
#include <cuda_runtime.h>
#include <cuda_bf16.h>
#include <cuda.h>
#include <stdint.h>

namespace {

constexpr int REG_C = 224;
constexpr int PDELAY = 200;
#define XA 7
#define XC 3
#define XE 3
#define XL 1200
#define XL1 1300
constexpr int WA = XA, WC = XC, WE = XE;
#define P0 100
#define P1W 200
constexpr int LAG = XL, LAG1 = XL1;
#define NP 8
#define NLEFT 4
#define CLR 1
constexpr int THREADS = 512;
constexpr int MAXG = 136;
constexpr int ROUNDS = 11;
constexpr int LUTS = 286, LUTN = 318;
constexpr int MAXNPC = 480;
constexpr int MAXE = 1 << 20;

constexpr int W2_OFF = 8192;
constexpr int WR_OFF = 32768;
constexpr int WIMG = 38912;
constexpr int ZL_OFF = WIMG;
constexpr int RING_OFF = 39936;
constexpr int SIDE_OFF = RING_OFF + 16 * 8192;
constexpr int RR_OFF = SIDE_OFF + 32768;
constexpr int ND_OFF = RR_OFF + ROUNDS * 1024;
constexpr int SRC_OFF = ND_OFF + ROUNDS * 256;
constexpr int LUT_OFF = SRC_OFF + ROUNDS * 256;
constexpr int SINK_OFF = LUT_OFF + 320 * 32;
constexpr int BAR_OFF = SINK_OFF + 512;
constexpr int MISC_OFF = BAR_OFF + 8 * 46;
constexpr int SMEM_BYTES = MISC_OFF + 192 + MAXG;
constexpr int PITCH = 144;
constexpr int TABLE_MAXN = 50176;
constexpr int STAGE_OFF = TABLE_MAXN * 4;
constexpr int SCNT_OFF = STAGE_OFF + MAXG * PITCH;
constexpr int OVL_OFF = MISC_OFF + 192;
constexpr int OPOS_OFF = LUT_OFF + 1024;
constexpr int NCNT_OFF = SIDE_OFF;
constexpr int NPOS_OFF = NCNT_OFF + 2048;
constexpr int YL_OFF = NPOS_OFF + 4096;
constexpr int TL_OFF = YL_OFF + 1024;
constexpr int E0_OFF = TL_OFF + 1024;
constexpr int SLOT_OFF = E0_OFF + 2048;
constexpr int SIZE_OFF = SLOT_OFF + 1280;
static_assert(SCNT_OFF + 4 * (MAXG + 32) <= OPOS_OFF && OPOS_OFF + 4096 <= LUT_OFF + LUTS * 32, "smem map");
static_assert(2 * (480 - 3 * MAXG) >= MAXG, "chunk map");
static_assert(SMEM_BYTES <= 232448 && MISC_OFF % 16 == 0 && BAR_OFF % 8 == 0 && (RING_OFF + 1024) % 8192 == 0 && SINK_OFF % 128 == 0, "smem map");

constexpr uint32_t PAY_INVALID = 0x3FFFFFFu;
constexpr uint32_t PAY_MARK = 0x3FFFDFFu;
constexpr uint32_t ST_START = 512, ST_CLOSE = 1024, ST_MID = 2048;
constexpr float QINVP = 9.0f / 510.0f;
constexpr uint32_t QTHRESH = 2126;

struct Scratch {
    unsigned sync[32];
    uint4 table[TABLE_MAXN / 4];
    uint4 wimg[WIMG / 16 + LUTS * 2];
    uint2 pos8[TABLE_MAXN];
    uint4 xbuf[MAXG * MAXG * 8 + 3 * THREADS];
    int ovfcnt[MAXG];
    int2 ovf[MAXE + 8 * MAXG + 8];
};
__device__ __align__(128) Scratch g_scratch;

struct Params {
    const __nv_bfloat16* pos;
    Scratch* g;
    const int* src;
    const int* dst;
    int N, NPC, E, gpc;
    const __nv_bfloat16* w2;
    const __nv_bfloat16* wr;
    const __nv_bfloat16* w1;
    const __nv_bfloat16* freqs;
    const __nv_bfloat16* sv;
    __nv_bfloat16* out;
    uint64_t desc0;
    int G;
    uint32_t magic;
    int odd_edges;
};
constexpr uint32_t SB = 1024;

#define TSX(i, thr)
#define TR(k, thr, t)
#define TC(k)
#define TS0(i) TSX(i, 0)

__device__ __forceinline__ uint32_t smem_u32(const void* p) { return (uint32_t)__cvta_generic_to_shared(p); }
__device__ __forceinline__ void mbar_init(uint32_t bar, uint32_t cnt) {
    asm volatile("mbarrier.init.shared::cta.b64 [%0], %1;" ::"r"(bar), "r"(cnt) : "memory");
}
__device__ __forceinline__ void mbar_arrive(uint32_t bar) {
    asm volatile("mbarrier.arrive.shared::cta.b64 _, [%0];" ::"r"(bar) : "memory");
}
__device__ __forceinline__ void mbar_expect_tx(uint32_t bar, uint32_t bytes) {
    asm volatile("mbarrier.arrive.expect_tx.shared::cta.b64 _, [%0], %1;" ::"r"(bar), "r"(bytes) : "memory");
}
__device__ __forceinline__ void mbar_wait(uint32_t bar, uint32_t parity) {
    asm volatile("{\n.reg .pred p;\n.reg .u32 c;\nmbarrier.try_wait.parity.shared::cta.b64 p, [%0], %1;\n@p bra DONE;\nmov.u32 c, 0;\n"
                 "AGAIN:\nmbarrier.try_wait.parity.shared::cta.b64 p, [%0], %1, 2000;\n@p bra DONE;\nadd.u32 c, c, 1;\n"
                 "setp.lt.u32 p, c, 0x100000;\n@p bra AGAIN;\ntrap;\nDONE:\n}\n" ::"r"(bar), "r"(parity) : "memory");
}
__device__ __forceinline__ void pause(uint32_t cycles) {
    uint32_t t0, t;
    asm volatile("mov.u32 %0, %%clock;" : "=r"(t0));
    do {
        __nanosleep(20);
        asm volatile("mov.u32 %0, %%clock;" : "=r"(t));
    } while (t - t0 < cycles);
}
__device__ __forceinline__ bool elect() {
    uint32_t r;
    asm volatile("{\n.reg .pred p;\nelect.sync _|p, 0xffffffff;\nselp.u32 %0, 1, 0, p;\n}\n" : "=r"(r));
    return r;
}
__device__ __forceinline__ uint32_t pin(uint32_t x) {
    uint32_t r;
    asm volatile("shfl.sync.bfly.b32 %0, %1, 0, 31, -1;" : "=r"(r) : "r"(x));
    return r;
}
__device__ __forceinline__ void bulk_g2s(uint32_t dst, const void* src, uint32_t bytes, uint32_t bar) {
    asm volatile("cp.async.bulk.shared::cluster.global.mbarrier::complete_tx::bytes [%0], [%1], %2, [%3];"
                 ::"r"(dst), "l"(src), "r"(bytes), "r"(bar) : "memory");
}
__device__ __forceinline__ void ldsm4(uint32_t addr, uint32_t* r) {
    asm volatile("ldmatrix.sync.aligned.m8n8.x4.shared.b16 {%0,%1,%2,%3}, [%4];"
                 : "=r"(r[0]), "=r"(r[1]), "=r"(r[2]), "=r"(r[3]) : "r"(addr) : "memory");
}
__device__ __forceinline__ uint32_t pack2(float lo, float hi) {
    uint32_t r;
    asm("cvt.rn.bf16x2.f32 %0, %1, %2;" : "=r"(r) : "f"(hi), "f"(lo));
    return r;
}
__device__ __forceinline__ float bf_lo(uint32_t w) { return __uint_as_float(w << 16); }
__device__ __forceinline__ float bf_hi(uint32_t w) { return __uint_as_float(w & 0xFFFF0000u); }
__device__ __forceinline__ float rbf16(float x) { return __uint_as_float(pack2(0.f, x)); }
__device__ __forceinline__ uint32_t hmul2(uint32_t a, uint32_t b) {
    uint32_t r;
    asm("mul.rn.bf16x2 %0, %1, %2;" : "=r"(r) : "r"(a), "r"(b));
    return r;
}
__device__ __forceinline__ uint32_t hfma2(uint32_t a, uint32_t b, uint32_t c) {
    uint32_t r;
    asm("fma.rn.bf16x2 %0, %1, %2, %3;" : "=r"(r) : "r"(a), "r"(b), "r"(c));
    return r;
}
__device__ __forceinline__ uint32_t hfma2_lo(uint32_t a, uint32_t b, uint32_t c) {
    uint32_t r;
    asm("{\n.reg .b16 l, h;\n.reg .b32 t;\nmov.b32 {l, h}, %2;\nmov.b32 t, {l, l};\nfma.rn.bf16x2 %0, %1, t, %3;\n}\n" : "=r"(r) : "r"(a), "r"(b), "r"(c));
    return r;
}
__device__ __forceinline__ uint32_t hfma2_hi(uint32_t a, uint32_t b, uint32_t c) {
    uint32_t r;
    asm("{\n.reg .b16 l, h;\n.reg .b32 t;\nmov.b32 {l, h}, %2;\nmov.b32 t, {h, h};\nfma.rn.bf16x2 %0, %1, t, %3;\n}\n" : "=r"(r) : "r"(a), "r"(b), "r"(c));
    return r;
}
__device__ __forceinline__ uint32_t hadd2(uint32_t a, uint32_t b) {
    uint32_t r;
    asm("add.rn.bf16x2 %0, %1, %2;" : "=r"(r) : "r"(a), "r"(b));
    return r;
}
__device__ __forceinline__ uint32_t hsub2(uint32_t a, uint32_t b) {
    uint32_t r;
    asm("sub.rn.bf16x2 %0, %1, %2;" : "=r"(r) : "r"(a), "r"(b));
    return r;
}
__device__ __forceinline__ void cp_async_arrive(uint32_t bar) {
    asm volatile("cp.async.mbarrier.arrive.noinc.shared::cta.b64 [%0];" ::"r"(bar) : "memory");
}
__device__ __forceinline__ float tanh_fast(float x) {
    float r;
    asm("tanh.approx.f32 %0, %1;" : "=f"(r) : "f"(x));
    return r;
}
__device__ __forceinline__ void wg_fence() { asm volatile("wgmma.fence.sync.aligned;" ::: "memory"); }
__device__ __forceinline__ void wg_commit() { asm volatile("wgmma.commit_group.sync.aligned;" ::: "memory"); }
template <int N>
__device__ __forceinline__ void wg_wait() { asm volatile("wgmma.wait_group.sync.aligned %0;" ::"n"(N) : "memory"); }

#define WG_REGS "{%0,%1,%2,%3,%4,%5,%6,%7,%8,%9,%10,%11,%12,%13,%14,%15,%16,%17,%18,%19,%20,%21,%22,%23,%24,%25,%26,%27,%28,%29,%30,%31}"
#define WG_OPS(c) c(d[0]), c(d[1]), c(d[2]), c(d[3]), c(d[4]), c(d[5]), c(d[6]), c(d[7]), c(d[8]), c(d[9]), c(d[10]), \
    c(d[11]), c(d[12]), c(d[13]), c(d[14]), c(d[15]), c(d[16]), c(d[17]), c(d[18]), c(d[19]), c(d[20]), c(d[21]),     \
    c(d[22]), c(d[23]), c(d[24]), c(d[25]), c(d[26]), c(d[27]), c(d[28]), c(d[29]), c(d[30]), c(d[31])
#define WG_OPSE(c) c(e[0]), c(e[1]), c(e[2]), c(e[3]), c(e[4]), c(e[5]), c(e[6]), c(e[7]), c(e[8]), c(e[9]), c(e[10]), c(e[11]), c(e[12]), c(e[13]), c(e[14]), c(e[15]), c(e[16]), c(e[17]), c(e[18]), c(e[19]), c(e[20]), c(e[21]), c(e[22]), c(e[23]), c(e[24]), c(e[25]), c(e[26]), c(e[27]), c(e[28]), c(e[29]), c(e[30]), c(e[31])
template <int OFF, int ACC, int IDX>
__device__ __forceinline__ void wgmma_rs(float* d, const uint32_t* a, uint64_t d0) {
    if (!ACC) {
#pragma unroll
        for (int i = 0; i < 32; i++) d[i] = 0.f;
    }
    if (IDX < 4)
        asm volatile("wgmma.mma_async.sync.aligned.m64n64k16.f32.bf16.bf16 " WG_REGS ", {%32,%33,%34,%35}, %36, %37, 1, 1, 1;"
                     : WG_OPS("+f") : "r"(a[0]), "r"(a[1]), "r"(a[2]), "r"(a[3]), "l"(d0 + (OFF >> 4)), "n"(ACC));
    else
        asm volatile("{\n.reg .b64 dd;\nmov.b64 dd, {%36, 0x40000040};\nwgmma.mma_async.sync.aligned.m64n64k16.f32.bf16.bf16 " WG_REGS
                     ", {%32,%33,%34,%35}, dd, %37, 1, 1, 1;\n}\n"
                     : WG_OPS("+f") : "r"(a[0]), "r"(a[1]), "r"(a[2]), "r"(a[3]), "n"(((SB + OFF) >> 4) | (1u << 16)), "n"(ACC));
}
template <int OFF, int LBO, int ACC>
__device__ __forceinline__ void wgmma_rs2(float* d, float* e, const uint32_t* a, uint64_t d0) {
    if (!ACC) {
#pragma unroll
        for (int i = 0; i < 32; i++) d[i] = e[i] = 0.f;
    }
    asm volatile("wgmma.mma_async.sync.aligned.m64n128k16.f32.bf16.bf16 {%0,%1,%2,%3,%4,%5,%6,%7,%8,%9,%10,%11,%12,%13,%14,%15,%16,%17,%18,%19,%20,%21,%22,%23,%24,%25,%26,%27,%28,%29,%30,%31,%32,%33,%34,%35,%36,%37,%38,%39,%40,%41,%42,%43,%44,%45,%46,%47,%48,%49,%50,%51,%52,%53,%54,%55,%56,%57,%58,%59,%60,%61,%62,%63}, {%64,%65,%66,%67}, %68, %69, 1, 1, 1;"
                 : WG_OPS("+f"), WG_OPSE("+f") : "r"(a[0]), "r"(a[1]), "r"(a[2]), "r"(a[3]), "l"(d0 + (OFF >> 4) + ((LBO / 16 - 1) << 16)), "n"(ACC));
}
template <int G>
__device__ __forceinline__ void wgmma_group(float* P, float* W, const uint32_t* h, const uint32_t* rf, uint64_t d0) {
    wgmma_rs<W2_OFF + 8192 * G, 0, 5 * G>(P, h, d0);
    wgmma_rs<W2_OFF + 8192 * G + 2048, 1, 5 * G + 1>(P, h + 4, d0);
    wgmma_rs<W2_OFF + 8192 * G + 4096, 1, 5 * G + 2>(P, h + 8, d0);
    wgmma_rs<W2_OFF + 8192 * G + 6144, 1, 5 * G + 3>(P, h + 12, d0);
    wgmma_rs<WR_OFF + 2048 * G, 0, 5 * G + 4>(W, rf, d0);
}
__device__ __forceinline__ void wgmma_ss_k64(float* d, uint64_t da, uint64_t db) {
#pragma unroll
    for (int i = 0; i < 32; i++) d[i] = 0.f;
    asm volatile("wgmma.mma_async.sync.aligned.m64n64k16.f32.bf16.bf16 " WG_REGS ", %32, %33, 0, 1, 1, 0, 1;" : WG_OPS("+f") : "l"(da), "l"(db));
#pragma unroll
    for (int k = 1; k < 4; k++)
        asm volatile("wgmma.mma_async.sync.aligned.m64n64k16.f32.bf16.bf16 " WG_REGS ", %32, %33, 1, 1, 1, 0, 1;"
                     : WG_OPS("+f") : "l"(da + 2 * k), "l"(db + 128 * k));
}
__device__ __forceinline__ void fence_regs(float* d) { asm volatile("" : WG_OPS("+f")::"memory"); }
__device__ __forceinline__ uint32_t qaxis(float x) {
    const float u = fmaf(x, QINVP, 0.25f);
    const float f = u - ((u + 12582912.f) - 12582912.f);
    return __float_as_uint(fmaf(fabsf(f), 510.f, 12582912.f));
}
__device__ __forceinline__ uint32_t qcode(float x, float y, float z, uint32_t tx) {
    return __byte_perm(__byte_perm(qaxis(x), qaxis(y), 0x3340), qaxis(z), 0x3410) ^ tx;
}
__device__ __forceinline__ bool near_test(uint32_t ca, uint32_t cb, uint32_t tag24) {
    const uint32_t D = __vabsdiffu4(ca, cb);
    return __dp4a(D, D, 0u) <= QTHRESH || ((ca ^ tag24) | (cb ^ tag24)) >= 0x1000000u;
}
constexpr float QMAX = 23.9375f;
__device__ __forceinline__ float square(uint32_t rxy, uint32_t rz) {
    const uint32_t qxy = hmul2(rxy, rxy), qz = hmul2(rz, rz);
    return bf_lo(qxy) + bf_hi(qxy) + bf_lo(qz);
}

__device__ __forceinline__ uint32_t lds32(uint32_t addr) {
    uint32_t r;
    asm volatile("ld.shared.u32 %0, [%1];" : "=r"(r) : "r"(addr) : "memory");
    return r;
}
__device__ __forceinline__ void sts32_if(uint32_t addr, uint32_t v, bool c) {
    asm volatile("{\n.reg .pred p;\nsetp.ne.u32 p, %2, 0;\n@p st.shared.u32 [%0], %1;\n}\n" ::"r"(addr), "r"(v), "r"((uint32_t)c) : "memory");
}
__device__ __forceinline__ uint32_t sel(bool c, uint32_t a, uint32_t b) {
    uint32_t r;
    asm("{\n.reg .pred p;\nsetp.ne.u32 p, %3, 0;\nselp.b32 %0, %1, %2, p;\n}\n" : "=r"(r) : "r"(a), "r"(b), "r"((uint32_t)c));
    return r;
}
__device__ __forceinline__ uint32_t lds16(uint32_t addr) {
    uint32_t r;
    asm volatile("ld.shared.u16 %0, [%1];" : "=r"(r) : "r"(addr) : "memory");
    return r;
}
__device__ __forceinline__ void sts16_if(uint32_t addr, uint32_t v, bool c) {
    asm volatile("{\n.reg .pred p;\nsetp.ne.u32 p, %2, 0;\n@p st.shared.u16 [%0], %1;\n}\n" ::"r"(addr), "h"((unsigned short)v), "r"((uint32_t)c) : "memory");
}
__device__ __forceinline__ void sts64_if(uint32_t addr, uint32_t x, uint32_t y, bool c) {
    asm volatile("{\n.reg .pred p;\nsetp.ne.u32 p, %3, 0;\n@p st.shared.v2.u32 [%0], {%1, %2};\n}\n" ::"r"(addr), "r"(x), "r"(y), "r"((uint32_t)c) : "memory");
}
__device__ __forceinline__ uint32_t atoms_add(uint32_t addr, uint32_t v) {
    uint32_t r;
    asm volatile("atom.shared.add.u32 %0, [%1], %2;" : "=r"(r) : "r"(addr), "r"(v) : "memory");
    return r;
}
__device__ __forceinline__ void stg128_if(void* ptr, uint4 v, bool c) {
    asm volatile("{\n.reg .pred p;\nsetp.ne.u32 p, %5, 0;\n@p st.relaxed.gpu.global.v4.u32 [%0], {%1,%2,%3,%4};\n}\n"
                 ::"l"(ptr), "r"(v.x), "r"(v.y), "r"(v.z), "r"(v.w), "r"((uint32_t)c) : "memory");
}
__device__ __forceinline__ void lds128(uint32_t addr, uint32_t* r) {
    asm volatile("ld.shared.v4.u32 {%0,%1,%2,%3}, [%4];" : "=r"(r[0]), "=r"(r[1]), "=r"(r[2]), "=r"(r[3]) : "r"(addr) : "memory");
}
__device__ __forceinline__ void stg2_if(uint64_t ptr, const uint32_t* r, uint32_t c) {
    asm volatile("{\n.reg .pred p;\nsetp.ne.u32 p, %9, 0;\n@p st.global.cs.v4.u32 [%8], {%0,%1,%2,%3};\n"
                 "@p st.global.cs.v4.u32 [%8 + 64], {%4,%5,%6,%7};\n}\n"
                 ::"r"(r[0]), "r"(r[1]), "r"(r[2]), "r"(r[3]), "r"(r[4]), "r"(r[5]), "r"(r[6]), "r"(r[7]), "l"(ptr), "r"(c) : "memory");
}
__device__ __forceinline__ void gather_s(uint32_t dst, const char* base, uint32_t src) {
    asm volatile("{\n.reg .pred p;\nsetp.eq.u32 p, %2, 0xFFFF;\ncp.async.cg.shared.global [%0], [%1], 16, p;\n}\n"
                 ::"r"(dst), "l"(base + (size_t)src * 512), "r"(src) : "memory");
}
__device__ __forceinline__ void gather_v(uint32_t dst, const char* base, uint32_t src) {
    asm volatile("{\n.reg .pred p;\nsetp.eq.u32 p, %2, 0xFFFF;\n"
                 "cp.async.cg.shared.global [%0 + 1024], [%1 + 128], 16, p;\ncp.async.cg.shared.global [%0 + 2048], [%1 + 256], 16, p;\n"
                 "cp.async.cg.shared.global [%0 + 3072], [%1 + 384], 16, p;\n}\n" ::"r"(dst), "l"(base + (size_t)src * 512), "r"(src) : "memory");
}
__device__ __forceinline__ void gather_row_if(uint32_t dst, const char* src, uint32_t c) {
    asm volatile("{\n.reg .pred p;\nsetp.ne.u32 p, %2, 0;\n@p cp.async.cg.shared.global [%0], [%1], 16;\n"
                 "@p cp.async.cg.shared.global [%0 + 1024], [%1 + 128], 16;\n@p cp.async.cg.shared.global [%0 + 2048], [%1 + 256], 16;\n"
                 "@p cp.async.cg.shared.global [%0 + 3072], [%1 + 384], 16;\n}\n" ::"r"(dst), "l"(src), "r"(c) : "memory");
}
__device__ __forceinline__ void lds2_if(uint32_t a0, uint32_t a1, uint32_t* r, uint32_t c) {
    asm volatile("{\n.reg .pred p;\nsetp.ne.u32 p, %10, 0;\n@p ld.shared.v4.u32 {%0,%1,%2,%3}, [%8];\n@p ld.shared.v4.u32 {%4,%5,%6,%7}, [%9];\n}\n"
                 : "+r"(r[0]), "+r"(r[1]), "+r"(r[2]), "+r"(r[3]), "+r"(r[4]), "+r"(r[5]), "+r"(r[6]), "+r"(r[7])
                 : "r"(a0), "r"(a1), "r"(c) : "memory");
}
__device__ __forceinline__ int fresh_lane() {
    int l;
    asm volatile("mov.u32 %0, %%laneid;" : "=r"(l));
    return l;
}

__device__ __forceinline__ void cold_edges(unsigned char* smem, const Params& p, int lo, int hi, uint32_t tag) {
#pragma unroll 1
    for (int e = lo + threadIdx.x; e < hi; e += THREADS) {
        const int s = p.src[e], d = p.dst[e];
        if (near_test(reinterpret_cast<const uint32_t*>(smem)[s], reinterpret_cast<const uint32_t*>(smem)[d], tag << 24)) {
            const uint32_t own = __umulhi((uint32_t)d, p.magic);
            const uint32_t slot4 = atomicAdd(reinterpret_cast<uint32_t*>(smem + SCNT_OFF) + own, 4u);
            uint32_t* line = reinterpret_cast<uint32_t*>(smem + STAGE_OFF) + own * (PITCH / 4);
            if (slot4 < 124) {
                line[slot4 >> 2] = ((uint32_t)s << 15) + ((uint32_t)(d - own * p.NPC) << 6) + tag;
            } else {
                uint32_t o = atomicAdd(reinterpret_cast<uint32_t*>(smem + MISC_OFF) + 16, 1u);
                p.g->ovf[(size_t)blockIdx.x * (4 * p.gpc + 4) + o] = make_int2(s, d);
                line[31] = (PAY_MARK << 6) | tag;
            }
        }
    }
}
__device__ __forceinline__ void cold_filter(unsigned char* smem, const Params& p, int e0, int e1, uint32_t tag, int redo) {
    if (redo) {
        if (threadIdx.x < MAXG) reinterpret_cast<uint32_t*>(smem + SCNT_OFF)[threadIdx.x] = 0;
        __syncthreads();
    }
    cold_edges(smem, p, redo ? 4 * e0 : 4 * (e0 + 3 * THREADS), 4 * e1, tag);
    if (blockIdx.x == 0) cold_edges(smem, p, p.E & ~3, p.E, tag);
    __syncthreads();
    if (threadIdx.x == 0) p.g->ovfcnt[blockIdx.x] = reinterpret_cast<uint32_t*>(smem + MISC_OFF)[16];
    __threadfence();
    __syncthreads();
}
__device__ __forceinline__ float distance(float q) {
    float d;
    asm("sqrt.approx.ftz.f32 %0, %1;" : "=f"(d) : "f"(rbf16(rbf16(q) + 1e-8f)));
    return rbf16(d);
}
__device__ __forceinline__ float fcut(float d) {
    return d < 5.0f ? 0.5f * rbf16(rbf16(__cosf(rbf16(rbf16(3.14159265358979f * d) * 0.2f))) + 1.0f) : 0.f;
}
__device__ __forceinline__ uint4 basis8(float d, uint4 f) {
    const float sc = __fdividef(fcut(d), d);
    const uint32_t dd = __byte_perm(__float_as_uint(d), 0, 0x3232);
    uint32_t x[4] = {hmul2(f.x, dd), hmul2(f.y, dd), hmul2(f.z, dd), hmul2(f.w, dd)};
#pragma unroll
    for (int i = 0; i < 4; i++) x[i] = pack2(__sinf(bf_lo(x[i])) * sc, __sinf(bf_hi(x[i])) * sc);
    return make_uint4(x[0], x[1], x[2], x[3]);
}
__device__ __forceinline__ void cold_nodes(unsigned char* smem, const Params& p, int nn, uint32_t tag) {
    float* acc = reinterpret_cast<float*>(smem + RING_OFF);
    const int nbase = blockIdx.x * p.NPC, lane = threadIdx.x & 31;
    const uint32_t* sv = reinterpret_cast<const uint32_t*>(p.sv);
    const volatile uint32_t* xin = reinterpret_cast<const uint32_t*>(p.g->xbuf) + blockIdx.x * p.G * 32;
#pragma unroll 1
    for (int i = threadIdx.x; i < p.G * 32; i += THREADS) {
        if ((int)xin[(i & ~31) + 15] < (int)(PAY_MARK << 6)) {
            uint32_t w;
            int it = 0;
            do {
                w = xin[i];
                if (++it > (1 << 22)) __trap();
            } while ((w ^ tag) & 63u);
            if ((w >> 6) == PAY_MARK) smem[OVL_OFF + atomicAdd(reinterpret_cast<uint32_t*>(smem + MISC_OFF) + 17, 1u)] = (unsigned char)(i >> 5);
        }
    }
    __threadfence();
    __syncthreads();
    const int nmark = reinterpret_cast<uint32_t*>(smem + MISC_OFF)[17];
#pragma unroll 1
    for (int c0 = 0; c0 < nn; c0 += 128) {
        __syncthreads();
#pragma unroll 1
        for (int i = threadIdx.x; i < 128 * 256; i += THREADS) acc[i] = 0.f;
        __syncthreads();
#pragma unroll 1
        for (int m = -1; m < nmark; m++) {
            const int pr = m < 0 ? 0 : smem[OVL_OFF + m];
            const int cnt = m < 0 ? p.G * 32 : __ldcg(&p.g->ovfcnt[pr]);
#pragma unroll 1
            for (int i = threadIdx.x; i - lane < cnt; i += THREADS) {
                int2 e = make_int2(0, -1);
                if (i < cnt) {
                    if (m < 0) {
                        const uint32_t w = xin[i];
                        if (((w ^ tag) & 63u) == 0) e = make_int2((w >> 15) & 0xFFFFu, (w >> 6) & 511u);
                    } else {
                        e = __ldcg(p.g->ovf + (size_t)pr * (4 * p.gpc + 4) + i);
                        e.y -= nbase;
                    }
                }
                uint32_t rxy = 0, rz = 0;
                bool in = e.y >= c0 && e.y < min(c0 + 128, nn);
                if (in) {
                    const uint2 ps = __ldcg(p.g->pos8 + e.x), pd = __ldcg(p.g->pos8 + nbase + e.y);
                    rxy = hsub2(ps.x, pd.x);
                    rz = hsub2(ps.y, pd.y);
                    in = square(rxy, rz) < QMAX;
                }
#pragma unroll 1
                for (uint32_t todo = __ballot_sync(0xffffffffu, in); todo; todo &= todo - 1) {
                    const int l = __ffs(todo) - 1;
                    const uint32_t* row = sv + (size_t)__shfl_sync(0xffffffffu, e.x, l) * 128 + lane;
                    float* o = acc + (__shfl_sync(0xffffffffu, e.y, l) - c0) * 256 + 2 * lane;
                    const uint32_t xy = __shfl_sync(0xffffffffu, rxy, l), z = __shfl_sync(0xffffffffu, rz, l);
                    const float d = distance(square(xy, z)), fc = fcut(d);
                    uint32_t x = __ldg(row);
                    float y0 = 0.f, y1 = 0.f, m2[6];
#pragma unroll 4
                    for (int k = 0; k < 64; k++) {
                        const uint32_t u = __shfl_sync(0xffffffffu, x, k >> 1), w = __ldg(reinterpret_cast<const uint32_t*>(p.w1) + k * 32 + lane);
                        const float a = k & 1 ? bf_hi(u) : bf_lo(u);
                        y0 = fmaf(a, bf_lo(w), y0);
                        y1 = fmaf(a, bf_hi(w), y1);
                    }
                    y0 = rbf16(y0); y1 = rbf16(y1);
                    x = pack2(y0 / (1.f + __expf(-y0)), y1 / (1.f + __expf(-y1)));
                    const float rb = rbf16(rbf16(__sinf(rbf16(d * __bfloat162float(p.freqs[lane & 15])))) / d);
#pragma unroll
                    for (int g = 0; g < 3; g++) {
                        float p0 = 0.f, p1 = 0.f, w0 = 0.f, w1 = 0.f;
#pragma unroll 4
                        for (int k = 0; k < 64; k++) {
                            const uint32_t u = __shfl_sync(0xffffffffu, x, k >> 1), w = __ldg(reinterpret_cast<const uint32_t*>(p.w2) + k * 96 + g * 32 + lane);
                            const float a = k & 1 ? bf_hi(u) : bf_lo(u);
                            p0 = fmaf(a, bf_lo(w), p0);
                            p1 = fmaf(a, bf_hi(w), p1);
                        }
#pragma unroll 4
                        for (int k = 0; k < 16; k++) {
                            const uint32_t w = __ldg(reinterpret_cast<const uint32_t*>(p.wr) + k * 96 + g * 32 + lane);
                            const float a = __shfl_sync(0xffffffffu, rb, k);
                            w0 = fmaf(a, bf_lo(w), w0);
                            w1 = fmaf(a, bf_hi(w), w1);
                        }
                        m2[2 * g] = rbf16(rbf16(p0) * rbf16(rbf16(w0) * fc));
                        m2[2 * g + 1] = rbf16(rbf16(p1) * rbf16(rbf16(w1) * fc));
                    }
                    atomicAdd(o, m2[0]);
                    atomicAdd(o + 1, m2[1]);
#pragma unroll
                    for (int k = 1; k < 4; k++) {
                        const uint32_t v = __ldg(row + 32 * k);
                        const float rh = rbf16((k == 1 ? bf_lo(xy) : k == 2 ? bf_hi(xy) : bf_lo(z)) / d);
                        atomicAdd(o + 64 * k, fmaf(m2[2], bf_lo(v), m2[4] * rh));
                        atomicAdd(o + 64 * k + 1, fmaf(m2[3], bf_hi(v), m2[5] * rh));
                    }
                }
            }
        }
        __syncthreads();
#pragma unroll 1
        for (int i = threadIdx.x; i < min(128, nn - c0) * 128; i += THREADS) {
            const uint32_t v = __ldg(sv + (size_t)(nbase + c0) * 128 + i);
            reinterpret_cast<uint32_t*>(p.out)[(size_t)(nbase + c0) * 128 + i] = pack2(bf_lo(v) + rbf16(acc[2 * i]), bf_hi(v) + rbf16(acc[2 * i + 1]));
        }
    }
}

template <int CN, int CE, int CG>
__global__ void __launch_bounds__(THREADS, 1) painn_kernel(const __grid_constant__ Params p, const __grid_constant__ CUtensorMap tm) {
    extern __shared__ __align__(1024) unsigned char smem_dyn[];
    unsigned char* const smem = static_cast<unsigned char*>(__cvta_shared_to_generic(SB));
    constexpr uint32_t sb = SB;
    const int tid = threadIdx.x, lane = tid & 31;
    const int warp = __shfl_sync(0xffffffffu, tid >> 5, 0);
    constexpr int CNPC = CG ? (CN + CG - 1) / CG : 1, CGPC = CG ? (CE / 4 + CG - 1) / CG : 1;
    const int b = blockIdx.x, G = CG ? CG : p.G, NPC = CG ? CNPC : p.NPC, N = CG ? CN : p.N, gpc = CG ? CGPC : p.gpc;
    const uint32_t magic = CG ? (uint32_t)(((1ull << 32) + CNPC - 1) / CNPC) : p.magic;
    const bool odd_edges = CG ? (CE & 3) != 0 || CGPC > 3 * THREADS : p.odd_edges;
    const int nbase = b * NPC, nn = min(NPC, N - nbase);
    const int e0 = b * gpc, e1 = min((CG ? CE : p.E) >> 2, e0 + gpc);

    uint4* stage4 = reinterpret_cast<uint4*>(smem + STAGE_OFF);
    uint32_t* ncnt = reinterpret_cast<uint32_t*>(smem + NCNT_OFF);
    uint32_t* misc = reinterpret_cast<uint32_t*>(smem + MISC_OFF);
    const uint32_t bar_full = sb + BAR_OFF + (warp & 7) * 40, bar_empty = bar_full + 16, bar_side = bar_full + 32, bar_tab = sb + BAR_OFF + 336;

    auto warm = [&](int first, int n) {
#pragma unroll 1
        for (int i = first; i < first + n; i++) {
            if (elect())
                asm volatile("cp.async.bulk.tensor.2d.shared::cluster.global.mbarrier::complete_tx::bytes [%0], [%1, {0, %3}], [%2];"
                             ::"r"(sb + SINK_OFF), "l"(&tm), "r"(bar_tab + 8), "r"(nbase * 4 + i * 32) : "memory");
        }
    };
    TS0(0);
    int4 es[3], ed[3];
    auto load_edges = [&](int i) {
        const int g = min(e0 + tid + i * THREADS, e1 - 1);
        asm volatile("ld.global.cs.v4.u32 {%0,%1,%2,%3}, [%8];\nld.global.cs.v4.u32 {%4,%5,%6,%7}, [%9];"
                     : "=r"(es[i].x), "=r"(es[i].y), "=r"(es[i].z), "=r"(es[i].w), "=r"(ed[i].x), "=r"(ed[i].y), "=r"(ed[i].z), "=r"(ed[i].w)
                     : "l"(reinterpret_cast<const int4*>(p.src) + g), "l"(reinterpret_cast<const int4*>(p.dst) + g) : "memory");
    };
    unsigned epoch;
    const uint32_t tbytes = ((N + 3) >> 2) * 16;
    {
        uint32_t pxy, pz;
        asm volatile("ld.global.nc.u32 %0, [%3];\nld.global.nc.u32 %1, [%3 + 4];\nld.global.ca.u32 %2, [%4];"
                     : "=r"(pxy), "=r"(pz), "=r"(epoch)
                     : "l"(reinterpret_cast<const uint32_t*>(p.pos) + ((nbase + min(tid, nn - 1)) * 3 >> 1)), "l"(p.g->sync) : "memory");
        const uint32_t sh = ((nbase + tid) & 1) << 4;
        pxy = __funnelshift_r(pxy, pz, sh);
        pz >>= sh;
        if (tid < nn) {
            reinterpret_cast<uint32_t*>(p.g->table)[nbase + tid] = qcode(bf_lo(pxy), bf_hi(pxy), bf_lo(pz), ((epoch & 31u) ^ 0x6Bu) << 24);
            p.g->pos8[nbase + tid] = make_uint2(pxy, pz);
        }
        reinterpret_cast<uint2*>(smem + OPOS_OFF)[tid] = make_uint2(pxy, pz);
        if (pxy == 0xFFFFFFFFu && pz == 0xFFFFFFFFu && epoch == 0xFFFFFFFFu) asm volatile("nanosleep.u32 0;");
        load_edges(0);
    }
    __syncthreads();
    const uint32_t tag = (epoch & 31u) | 32u;
    if (warp == 15) {
        if (elect()) {
            asm volatile("red.relaxed.gpu.global.add.u32 [%0], 1;" ::"l"(p.g->sync + 8 + b * NP / G) : "memory");
            asm volatile("prefetch.tensormap [%0];" ::"l"(&tm) : "memory");
            mbar_init(bar_tab, 1);
            mbar_init(bar_tab + 8, 1);
            mbar_expect_tx(bar_tab, tbytes);
            mbar_expect_tx(bar_tab + 8, (WA + WC + WE) * 512);
        }
        TSX(1, 511);
    }
    if (warp == 14) {
#pragma unroll 1
        for (int c = b * 32 + lane; c < WIMG / 16 + LUTS * 2; c += G * 32) {
            const int row = c >> 3, j = (c ^ row) & 7;
            uint4 v;
            if (c < 512) {
                const uint32_t half = 0x3F003F00u;
                v = __ldg(reinterpret_cast<const uint4*>(p.w1) + row * 8 + j);
                v = make_uint4(hmul2(v.x, half), hmul2(v.y, half), hmul2(v.z, half), hmul2(v.w, half));
            } else if (c >= WIMG / 16) {
                v = basis8(__uint_as_float((0x409D - ((c - WIMG / 16) >> 1)) << 16), __ldg(reinterpret_cast<const uint4*>(p.freqs) + (c & 1)));
            } else {
                const uint32_t* q = (c < 2048 ? reinterpret_cast<const uint32_t*>(p.w2) + (row & 63) * 96 + ((row >> 6) - 1) * 32
                                              : reinterpret_cast<const uint32_t*>(p.wr) + (row & 15) * 96 + ((row >> 4) - 16) * 32) + (j & 4) * 4 + (j & 3);
                v = make_uint4(__ldg(q), __ldg(q + 4), __ldg(q + 8), __ldg(q + 12));
            }
            p.g->wimg[c] = v;
        }
    }
    if (warp < 8 && elect()) {
        mbar_init(bar_full, 32); mbar_init(bar_full + 8, 32);
        mbar_init(bar_empty, 1);
        mbar_init(bar_side, 32);
    }
    if (tid < MAXG) reinterpret_cast<uint32_t*>(smem + SCNT_OFF)[tid] = 0;
    if (tid < 48) misc[tid] = 0;
    {
        const uint32_t inv = (PAY_INVALID << 6) | tag;
        stage4[tid] = stage4[tid + THREADS] = make_uint4(inv, inv, inv, inv);
        if (tid < MAXG * (PITCH / 16) - 2 * THREADS) stage4[tid + 2 * THREADS] = make_uint4(inv, inv, inv, inv);
    }
    if (warp == 15) {
        __syncwarp();
        const int k = lane & (NP - 1), b0 = (k * G + NP - 1) / NP, b1 = ((k + 1) * G + NP - 1) / NP;
        const uint32_t o0 = (b0 * NPC * 4) & ~127u, o1 = k == NP - 1 ? tbytes : (b1 * NPC * 4) & ~127u;
        bool todo = lane < NP, wait = true;
        uint32_t left;
        int it = smem_u32(smem_dyn) == SB ? 0 : 1 << 22;
        do {
            unsigned c;
            asm volatile("ld.relaxed.gpu.global.u32 %0, [%1];" : "=r"(c) : "l"(p.g->sync + 8 + k) : "memory");
            if (todo && c == (epoch + 1) * (b1 - b0)) {
                bulk_g2s(sb + o0, reinterpret_cast<const char*>(p.g->table) + o0, o1 - o0, bar_tab);
                todo = false;
            }
            if (++it > (1 << 22)) __trap();
            left = __ballot_sync(0xffffffffu, todo);
            if (wait && __popc(left) <= NLEFT) {
                asm volatile("bar.arrive 1, 512;" ::: "memory");
                wait = false;
            }
        } while (left);
        asm volatile("bar.sync 2, 512;" ::: "memory");
        TSX(2, 511);
    } else {
        asm volatile("bar.arrive 2, 512;" ::: "memory");
        asm volatile("bar.sync 1, 512;" ::: "memory");
    }
    load_edges(1);
#pragma unroll 1
    for (int r = tid >> 2; r < G; r += THREADS / 4) {
        uint4* const x = p.g->xbuf + (r * G + b) * 8 + (tid & 3);
        stg128_if(x, make_uint4(0, 0, 0, 0), true);
        stg128_if(x + 4, make_uint4(0, 0, 0, 0), ((r ^ epoch) & 15) == 0);
    }
    load_edges(2);
    if (tid == THREADS - 1) asm volatile("fence.acq_rel.gpu;" ::: "memory");
    mbar_wait(bar_tab, 0);
    TS0(3);
    if (warp == 15) warm(0, WA);

    bool over = false;
#pragma unroll 1
    for (int i = 0, g = e0 + tid; i < 3; i++, g += THREADS) {
        const int s[4] = {es[0].x, es[0].y, es[0].z, es[0].w}, d[4] = {ed[0].x, ed[0].y, ed[0].z, ed[0].w};
        uint32_t ca[4], cb[4], own[4], sl[4];
        bool c[4];
#pragma unroll
        for (int j = 0; j < 4; j++) { ca[j] = lds32(sb + 4 * s[j]); cb[j] = lds32(sb + 4 * d[j]); }
#pragma unroll
        for (int j = 0; j < 4; j++) {
            c[j] = near_test(ca[j], cb[j], tag << 24) && g < e1;
            own[j] = __umulhi((uint32_t)d[j], magic);
            sl[j] = atomicAdd(reinterpret_cast<uint32_t*>(smem + SCNT_OFF) + (c[j] ? own[j] : MAXG + lane), 4u);
        }
#pragma unroll
        for (int j = 0; j < 4; j++)
            sts32_if(sb + STAGE_OFF + own[j] * PITCH + sl[j], own[j] * (uint32_t)(-64 * NPC) + (((uint32_t)s[j] << 15) + (((uint32_t)d[j] << 6) + tag)),
                     c[j] && sl[j] < 124);
#pragma unroll
        for (int j = 0; j < 4; j++) over |= c[j] && sl[j] >= 124;
        es[0] = es[1]; es[1] = es[2];
        ed[0] = ed[1]; ed[1] = ed[2];
    }
    {
        const int redo = __syncthreads_or(over);
        if (__builtin_expect(redo || odd_edges, 0)) cold_filter(smem, p, e0, e1, tag, redo);
    }
    TS0(4);
#pragma unroll 1
    for (int r = tid >> 2; r < G; r += THREADS / 4) {
        const int c = r * (PITCH / 16) + (tid & 3);
        uint4* const x = p.g->xbuf + (r * G + b) * 8 + (tid & 3);
        const bool more = reinterpret_cast<uint32_t*>(smem + SCNT_OFF)[r] > 64;
        uint4 v = stage4[c];
        if (more && (tid & 3) == 3) v.w |= 0x80000000u;
        stg128_if(x + 4, stage4[c + 4], more);
        stg128_if(x, v, true);
    }
    ncnt[tid] = 0;
    reinterpret_cast<uint32_t*>(smem + E0_OFF)[tid] = ~0u;
    if (tid < 480) reinterpret_cast<uint32_t*>(smem + SLOT_OFF)[tid] = tid < 32 ? tid * 0x100010 + 0x80000 : tid < 320 ? ~0u : 0u;
    if (tid == 511) reinterpret_cast<uint2*>(smem + NPOS_OFF)[511] = make_uint2(sb + SLOT_OFF + 1278, 0);
    __syncthreads();
    reinterpret_cast<uint4*>(smem + RR_OFF)[tid] = make_uint4(0, 0, 0, 0);
    if (tid < ROUNDS * 80 - THREADS) reinterpret_cast<uint4*>(smem + RR_OFF)[tid + THREADS] = make_uint4(0, 0, 0, 0);
    if (tid < ROUNDS * 32) reinterpret_cast<uint2*>(smem + SRC_OFF)[tid] = make_uint2(~0u, ~0u);
    pause(PDELAY);
    TS0(5);

    uint32_t rxy[4], gz[4], src[4], rk[4], dn[4];
    const uint32_t sink = sb + NCNT_OFF + 4 * (480 + lane);
    if (warp < 15) {
        uint32_t ew[3][4], bad[2];
        const int u = tid - 3 * G;
        const uint4* const xin = p.g->xbuf + b * G * 8;
        const uint4* cp = xin + (u < 0 ? tid + tid / 3 * 5 : u * 8 + 3);
        bad[0] = u < G;
        bad[1] = u >= 0 && u + 480 - 3 * G < G;
#pragma unroll
        for (int i = 0; i < 3; i++) ew[i][0] = ew[i][1] = ew[i][2] = ew[i][3] = (PAY_INVALID << 6) | tag;
        int it = 0;
#pragma unroll 1
        do {
#pragma unroll
            for (int i = 0; i < 2; i++)
                asm volatile("{\n.reg .pred p;\nsetp.ne.u32 p, %5, 0;\n@p ld.relaxed.gpu.global.v4.u32 {%0,%1,%2,%3}, [%4];\n}\n"
                             : "+r"(ew[i][0]), "+r"(ew[i][1]), "+r"(ew[i][2]), "+r"(ew[i][3]) : "l"(cp + i * (480 - 3 * G) * 8), "r"(bad[i]) : "memory");
#pragma unroll
            for (int i = 0; i < 2; i++) bad[i] = ((ew[i][0] ^ tag) | (ew[i][1] ^ tag) | (ew[i][2] ^ tag) | (ew[i][3] ^ tag)) & 63u;
            if (++it > (1 << 22)) __trap();
        } while (__any_sync(0xffffffffu, bad[0] | bad[1]));
        if (warp >= (3 * G) >> 5) {
            constexpr int EMPTY = (int)(PAY_MARK << 6);
            const bool e0 = ew[0][0] >= (PAY_MARK << 6);
            if (__builtin_expect(__any_sync(0xffffffffu, min((int)ew[0][3], (int)ew[1][3]) < EMPTY || (!e0 && ew[1][0] < (PAY_MARK << 6))), 0)) {
                uint64_t f = (uint64_t)__ballot_sync(0xffffffffu, (int)ew[1][3] < EMPTY) << 32 | __ballot_sync(0xffffffffu, (int)ew[0][3] < EMPTY);
                if ((int)ew[0][3] < EMPTY) ew[0][3] &= 0x7FFFFFFFu;
                if ((int)ew[1][3] < EMPTY) ew[1][3] &= 0x7FFFFFFFu;
#pragma unroll 1
                for (int k = 7 - (lane >> 2); k && f; k--) f &= f - 1;
                if (f) {
                    const int l = __ffsll(f) - 1;
                    do {
                        asm volatile("ld.relaxed.gpu.global.v4.u32 {%0,%1,%2,%3}, [%4];" : "=r"(ew[2][0]), "=r"(ew[2][1]), "=r"(ew[2][2]), "=r"(ew[2][3])
                                     : "l"(xin + (u - lane + l + (l >> 5) * (448 - 3 * G)) * 8 + 4 + (lane & 3)) : "memory");
                        if (++it > (1 << 22)) __trap();
                    } while (((ew[2][0] ^ tag) | (ew[2][1] ^ tag) | (ew[2][2] ^ tag) | (ew[2][3] ^ tag)) & 63u);
                    if ((ew[2][3] >> 6) == PAY_MARK || lane == 0) misc[0] = 1;
                }
                __syncwarp();
#pragma unroll 1
                for (int i = 0; i < 2; i++) {
                    if (ew[0][0] >= (PAY_MARK << 6)) {
#pragma unroll
                        for (int j = 0; j < 4; j++) { ew[0][j] = ew[1][j]; ew[1][j] = ~0u; }
                    }
                    uint32_t from = __ballot_sync(0xffffffffu, ew[1][0] < (PAY_MARK << 6)), to = __ballot_sync(0xffffffffu, ew[0][0] >= (PAY_MARK << 6));
#pragma unroll 1
                    for (; from; from &= from - 1, to &= to - 1) {
                        if (!to) misc[0] = 1;
#pragma unroll
                        for (int j = 0; j < 4; j++) {
                            const uint32_t x = __shfl_sync(0xffffffffu, ew[1][j], __ffs(from) - 1);
                            if (lane == __ffs(to) - 1) ew[0][j] = x;
                        }
                    }
#pragma unroll
                    for (int j = 0; j < 4; j++) ew[1][j] = ew[2][j];
                }
            } else if (e0) {
#pragma unroll
                for (int j = 0; j < 4; j++) ew[0][j] = ew[1][j];
            }
        }
        {
            uint2 ps[4], pd[4];
#pragma unroll
            for (int j = 0; j < 4; j++) {
                dn[j] = (ew[0][j] >> 3) & 4088u;
                src[j] = ew[0][j] >> 15;
                ps[j] = __ldcg(p.g->pos8 + (dn[j] == 4088u ? nbase : src[j]));
            }
#pragma unroll
            for (int j = 0; j < 4; j++) pd[j] = *reinterpret_cast<const uint2*>(smem + OPOS_OFF + dn[j]);
            asm volatile("bar.arrive 1, 512;" ::: "memory");
            float q[4];
#pragma unroll
            for (int j = 0; j < 4; j++) {
                rxy[j] = hsub2(ps[j].x, pd[j].x);
                gz[j] = hsub2(ps[j].y, pd[j].y);
                q[j] = square(rxy[j], gz[j]);
                const bool in = q[j] < QMAX && dn[j] != 4088u;
                rk[j] = atoms_add(in ? sb + NCNT_OFF + (dn[j] >> 1) : sink, 512u);
                if (!in) dn[j] = 4088u;
            }
            uint32_t row[4], n = 0;
            bool single[4];
#pragma unroll
            for (int j = 0; j < 4; j++) {
                q[j] = distance(q[j]);
                row[j] = 0x409D - (__float_as_uint(q[j]) >> 16);
                single[j] = row[j] >= LUTS && dn[j] != 4088u;
                n += single[j];
            }
            n = atoms_add(n ? sb + MISC_OFF + 4 : sink, n) + LUTS;
#pragma unroll
            for (int j = 0; j < 4; j++) {
                float id;
                asm("rcp.approx.ftz.f32 %0, %1;" : "=f"(id) : "f"(q[j]));
                sts32_if(sb + LUT_OFF + min(n, LUTN - 1) * 32, __float_as_uint(q[j]), single[j]);
                if (single[j]) row[j] = n++;
                rxy[j] = pack2(bf_lo(rxy[j]) * id, bf_hi(rxy[j]) * id);
                gz[j] = pack2(0.f, bf_lo(gz[j]) * id) + row[j] * 32;
                sts16_if(sb + E0_OFF + (dn[j] >> 1) + (rk[j] >> 8), src[j], rk[j] < 1024 && dn[j] != 4088u);
            }
        }
    } else {
        const uint4 fq = __ldg(reinterpret_cast<const uint4*>(p.freqs) + (lane & 1));
        rxy[0] = fq.x; rxy[1] = fq.y; rxy[2] = fq.z; rxy[3] = fq.w;
        asm volatile("bar.sync 1, 512;" ::: "memory");
        warm(WA, WC);
    }
    __syncthreads();
    TS0(6);

    const uint32_t lt = (1u << lane) - 1;
    uint32_t place = ~0u, mid = 0, last = 0, steps = 0, c = 0;
    if (warp < 15) {
        if (tid < nn) c = ncnt[tid] >> 9;
        const uint32_t e0w = lds32(sb + E0_OFF + 4 * tid);
        steps = min((c + 1) >> 1, 15u);
        const uint32_t bin = sel(tid >= nn, 9, (uint32_t)(0x11223354678ull >> (4 * min(c, 11u))) & 15), sh = (bin & 1) * 16;
        const bool odd = c > 3 && (c & 1);
        const uint32_t peers = __match_any_sync(0xffffffffu, bin), om = __ballot_sync(0xffffffffu, odd);
        uint32_t x = atoms_add(lane == 0 ? sb + MISC_OFF + 4 * 37 : sink, __popc(om));
        uint32_t r = atoms_add((peers & lt) == 0 ? sb + MISC_OFF + 4 * 32 + 2 * (bin & 14) : sink, __popc(peers) << sh);
        x = __shfl_sync(0xffffffffu, x, 0) + __popc(om & lt);
        r = ((__shfl_sync(0xffffffffu, r, __ffs(peers) - 1) >> sh) & 0xFFFFu) + __popc(peers & lt);
        sts16_if(sb + sel(bin == 8, ZL_OFF, sel(bin == 7, YL_OFF, TL_OFF)) + 2 * r, tid, (0x190 >> bin) & 1);
        const uint64_t ones = 0x0001010101010101ull >> (56 - 8 * min(bin, 7u));
        asm volatile("bar.sync 2, 480;" ::: "memory");
        uint32_t h[4];
        lds128(sb + MISC_OFF + 4 * 32, h);
        const int nodd = misc[37], n1 = h[3] >> 16, n3 = h[2] & 0xFFFF, left = max(min(nodd + n3 - n1, n3), 0), half = left >> 1;
        const bool twin = bin == 4 && (int)r < 2 * half;
        x = sel(bin == 4, nodd + r - left, sel(odd, x, 1023));
        const bool pair = twin ? !(r & 1) : (int)x >= (bin == 4 ? nodd : 0) && (int)x < n1;
        const uint32_t y = lds16(sel(twin, sb + TL_OFF + 2 + 2 * r, sb + YL_OFF + 2 * (x & 511)));
        const uint32_t base = __dp2a_lo(h[0], (uint32_t)ones, __dp2a_hi(h[1], (uint32_t)ones, 0u)) +
                              __dp2a_lo(h[2], (uint32_t)(ones >> 32), __dp2a_hi(h[3], (uint32_t)(ones >> 32), 0u));
        r -= sel(bin == 7, nodd + n3, 0);
        const bool unit = (bin < 8 && (int)r >= 0 && (pair || !twin));
        place = sel(unit, base + sel(twin, r >> 1, r - sel(bin < 4, 0, half)), ~0u);
        place = sel(place < 64, (place >> 1) + (place & 1) * 32, place);
        sts16_if(sb + SRC_OFF + 2 * place, e0w, place < 64);
        sts16_if(sb + SRC_OFF + 128 + 2 * place, e0w >> 16, place < 64);
        sts32_if(sb + MISC_OFF + 16, base - half + max(n1 - nodd - n3, 0), bin >= 7);
        steps += twin;
        last = sel(twin, y, tid) | sel(steps > 1, ST_CLOSE, ST_CLOSE | ST_START);
        mid = sel(pair, y | sel(twin, ST_MID, ST_MID | ST_CLOSE) | (tid << 16), last);
        c = sel(pair, c, 2 * steps - 1);
        const uint32_t sa = sb + SLOT_OFF + sel(steps <= ROUNDS, 2 * place, 1278);
        sts64_if(sb + NPOS_OFF + 8 * tid, sa, 0, unit);
        sts64_if(sb + NPOS_OFF + 8 * y, sa, c << 9, pair);
        asm volatile("{\n.reg .pred p;\nsetp.ne.u32 p, %2, 0;\n@p st.shared.u8 [%0], %1;\n}\n" ::"r"(sb + SIZE_OFF + place), "r"(steps), "r"((uint32_t)unit) : "memory");
    } else {
        if (elect()) {
            if (b == 0) p.g->sync[0] = epoch + 1;
            asm volatile("fence.proxy.async.global;" ::: "memory");
            mbar_expect_tx(bar_tab, WIMG + LUTS * 32);
            bulk_g2s(sb, p.g->wimg, WIMG, bar_tab);
            bulk_g2s(sb + LUT_OFF, p.g->wimg + WIMG / 16, LUTS * 32, bar_tab);
        }
        warm(WA + WC, WE);
#pragma unroll 1
        for (uint32_t i = lane; i - lane < 2 * min(misc[1], LUTN - LUTS); i += 32) {
            const uint32_t d = lds32(sb + LUT_OFF + (LUTS + (i >> 1)) * 32);
            __syncwarp();
            reinterpret_cast<uint4*>(smem + LUT_OFF)[2 * LUTS + i] = basis8(__uint_as_float(d), make_uint4(rxy[0], rxy[1], rxy[2], rxy[3]));
        }
        TSX(12, 511);
    }
    __syncthreads();
    TS0(7);
    uint32_t st[4];
    if (warp == 15) {
        uint32_t until0 = lds16(sb + SIZE_OFF + 2 * lane), until1 = until0 >> 8, next = 64, s0, s1;
        const uint32_t nsched = misc[4];
        until0 &= 255;
        uint32_t t = __reduce_min_sync(0xffffffffu, min(until0, until1));
        bool go = true;
#pragma unroll 1
        while (go) {
            go = t < ROUNDS && next < nsched;
            const bool n0 = until0 == t, n1 = until1 == t;
            const uint32_t i = next + __popc(__ballot_sync(0xffffffffu, n0) & lt) + __popc(__ballot_sync(0xffffffffu, n1) & lt), j = i + n0;
            next += __reduce_add_sync(0xffffffffu, n0 + n1);
            asm volatile("{\n.reg .pred p, q;\nsetp.ne.u32 p, %4, 0;\nsetp.ne.u32 q, %5, 0;\nmov.u32 %0, 0;\nmov.u32 %1, 0;\n@p ld.shared.u8 %0, [%2];\n@q ld.shared.u8 %1, [%3];\n}\n"
                         : "=&r"(s0), "=&r"(s1) : "r"(sb + SIZE_OFF + i), "r"(sb + SIZE_OFF + j), "r"((uint32_t)n0), "r"((uint32_t)n1) : "memory");
            until0 += s0;
            until1 += s1;
            sts16_if(sb + SLOT_OFF + 2 * i, 1024 * t + 16 * lane, n0 && until0 <= ROUNDS);
            sts16_if(sb + SLOT_OFF + 2 * j, 1024 * t + 16 * lane + 8, n1 && until1 <= ROUNDS);
            t++;
        }
        until0 = __reduce_max_sync(lane < 16 ? 0xFFFFu : 0xFFFF0000u, max(until0, until1));
        if ((lane & 15) == 0) misc[2 + (lane >> 4)] = until0;
        __syncthreads();
        lds128(sb + MISC_OFF, st);
    } else {
        if (warp < 8) {
            const int s = lane >> 3, c = lane & 7;
            const uint32_t dst = sb + RING_OFF + warp * 16384 + s * 128, y = sb + SRC_OFF + (warp * 8 + s) * 2;
            const uint32_t sdst = dst + ((c ^ s) << 4), vdst = dst + ((c ^ ((s & 1) << 2)) << 4);
            const uint32_t s0 = lds16(y), s1 = lds16(y + 8), s2 = lds16(y + 128), s3 = lds16(y + 136);
            const char* svl = reinterpret_cast<const char*>(p.sv) + c * 16;
            gather_s(sdst, svl, s0);
            gather_s((sdst ^ 64) + 512, svl, s1);
            gather_s(sdst + 8192, svl, s2);
            gather_s((sdst ^ 64) + 8704, svl, s3);
            cp_async_arrive(bar_full);
            TS0(10);
            pause(warp & 4 ? P1W : P0);
            gather_v(vdst, svl, s0);
            pause(P0);
            gather_v(vdst + 512, svl, s1);
            pause(P0);
            gather_v(vdst + 8192, svl, s2);
            pause(P0);
            gather_v(vdst + 8704, svl, s3);
            asm volatile("cp.async.mbarrier.arrive.shared::cta.b64 [%0];" ::"r"(bar_side) : "memory");
        }
#pragma unroll
        for (int j = 0; j < 4; j++) {
            const uint2 np = *reinterpret_cast<const uint2*>(smem + NPOS_OFF + dn[j]);
            dn[j] = np.x;
            rk[j] += np.y;
        }
        __syncthreads();
        TS0(8);
        lds128(sb + MISC_OFF, st);
        uint32_t e[4];
#pragma unroll
        for (int j = 0; j < 4; j++) e[j] = lds16(dn[j]);
        const uint32_t x = lds16(sb + SLOT_OFF + 2 * min(place, 639u));
#pragma unroll
        for (int j = 0; j < 4; j++) {
            sts16_if(sb + SRC_OFF + ((rk[j] + e[j]) >> 2), src[j], e[j] != 0xFFFFu);
            sts64_if(sb + RR_OFF + rk[j] + e[j], rxy[j], gz[j], e[j] != 0xFFFFu);
        }
        const uint32_t nd = sb + ND_OFF + ((x >> 2) & 0xFF00) + ((x >> 1) & 0xFC);
        sts32_if(nd, tid | ST_START, x != 0xFFFFu);
        sts32_if(nd + steps * 256 - 256, last, x != 0xFFFFu && steps <= ROUNDS);
        sts32_if(nd + c * 128 - 128, mid, x != 0xFFFFu && steps <= ROUNDS);
    }
    __syncthreads();
    if (__builtin_expect(max(st[2], st[3]) > ROUNDS || st[1] > LUTN - LUTS || st[0], 0)) {
        asm volatile("cp.async.wait_all;" ::: "memory");
        mbar_wait(bar_tab, 1);
        mbar_wait(bar_tab + 8, 0);
        cold_nodes(smem, p, nn, tag);
        return;
    }
    TS0(9);
    const int T = __shfl_sync(0xffffffffu, warp & 4 ? st[3] : st[2], 0);

    if (warp < 8) {
        asm volatile("setmaxnreg.inc.sync.aligned.u32 %0;" ::"n"(REG_C));
        const int lane = fresh_lane();
        const int g = lane >> 2, q = lane & 3;
        const uint64_t d0 = (uint64_t)__shfl_sync(0xffffffffu, pin((uint32_t)(p.desc0 >> 32)), 0) << 32 | __shfl_sync(0xffffffffu, pin((uint32_t)p.desc0), 0);
        const uint32_t swz = g * 128 + ((q ^ ((g & 1) << 2)) << 4);
        const uint32_t srow = pin(sb + SIDE_OFF + warp * 4096 + swz);
        uint32_t vrow = pin(sb + RING_OFF + warp * 16384 + swz + 4096);
        uint32_t ent = pin(sb + RR_OFF + (warp * 8 + g) * 8), fent = pin(sb + ND_OFF + (warp * 8 + g) * 4);
        uint32_t lent = pin(sb + RR_OFF + (warp * 8 + (lane & 7)) * 8 + 4 + (lane & 8) * 64);
        const uint32_t lutq = pin(sb + LUT_OFF + (lane >> 4) * 16);
        uint64_t outq;
        {
            const uint64_t a = reinterpret_cast<uint64_t>(p.out) + (size_t)nbase * 512 + q * 16;
            const uint32_t lo = pin((uint32_t)a), hi = pin((uint32_t)(a >> 32));
            asm volatile("mov.b64 %0, {%1, %2};" : "=l"(outq) : "r"(lo), "r"(hi));
        }
        uint32_t acc[32], rf[4], h[16], rr[4], fl = 0;
#pragma unroll
        for (int i = 0; i < 32; i++) asm volatile("" : "=r"(acc[i]));
#pragma unroll
        for (int i = 0; i < 16; i++) asm volatile("" : "=r"(h[i]));
#pragma unroll
        for (int i = 0; i < 4; i++) asm volatile("" : "=r"(rf[i]), "=r"(rr[i]));
        int t = -1;
        TSX(18, 0);
        mbar_wait(bar_tab, 1);
        TSX(14, 0);
        const int Tm = __shfl_sync(0xffffffffu, min(st[2], st[3]), 0);
        if (warp >= 4 && Tm > 0) asm volatile("bar.arrive 3, 256;" ::: "memory");
        bool more = T < 0x7FFFFFFF;
#pragma unroll 1
        while (more) {
            float y[32], p1[32], w1[32], p2[32], w2[32], p3[32], w3[32];
            uint32_t m1[16], m2[16], v[3][16], ts[8];
            auto products = [](uint32_t* m, const float* P, const float* W) {
#pragma unroll
                for (int j = 0; j < 8; j++) {
                    m[j] = pack2(P[4 * j] * W[4 * j], P[4 * j + 1] * W[4 * j + 1]);
                    m[8 + j] = pack2(P[4 * j + 2] * W[4 * j + 2], P[4 * j + 3] * W[4 * j + 3]);
                }
            };
            auto vterm = [&](int k, int o) {
#pragma unroll
                for (int j = 0; j < 8; j++) acc[8 * k + 8 + j] = hfma2(m1[o + j], v[k][o + j], acc[8 * k + 8 + j]);
            };
            auto rterm = [&](int k, int o) {
#pragma unroll
                for (int j = 0; j < 8; j++)
                    acc[8 * k + 8 + j] = k == 0 ? hfma2_lo(m2[o + j], rr[o / 4], acc[8 * k + 8 + j]) : hfma2_hi(m2[o + j], rr[o / 4 + k / 2], acc[8 * k + 8 + j]);
            };
            TR(0, 0, t);
            uint64_t om, op;
#pragma unroll
            for (int j = 0; j < 8; j++) asm volatile("" : "=r"(ts[j]), "=r"(m1[8 + j]), "=r"(m2[8 + j]), "=r"(v[0][8 + j]), "=r"(v[1][8 + j]), "=r"(v[2][8 + j]));
            asm volatile("" : "=l"(om));
            if (t >= 0) {
            TC(0);
            if (t < Tm) asm volatile("bar.sync %0, 256;" ::"r"(3 + (warp >> 2)) : "memory");
            wg_fence();
            wgmma_rs2<W2_OFF + 8192, 8192, 0>(p1, p2, h, d0);
            wgmma_rs2<W2_OFF + 10240, 8192, 1>(p1, p2, h + 4, d0);
            wgmma_rs2<W2_OFF + 12288, 8192, 1>(p1, p2, h + 8, d0);
            wgmma_rs2<W2_OFF + 14336, 8192, 1>(p1, p2, h + 12, d0);
            wgmma_rs2<WR_OFF + 2048, 2048, 0>(w1, w2, rf, d0);
            wg_commit();
            TC(1);
            mbar_wait(bar_side, t & 1);
            TC(2);
#pragma unroll
            for (int k = 0; k < 4; k++) lds2_if(srow + 1024 * k, (srow ^ 64) + 1024 * k, acc + 8 * k, fl & ST_START);
            wg_wait<0>();
            fence_regs(p1); fence_regs(w1);
            TC(3);
            products(m1, p1, w1);
#pragma unroll
            for (int k = 0; k < 3; k++) { lds128(vrow + 1024 + 1024 * k, v[k]); lds128((vrow ^ 64) + 1024 + 1024 * k, v[k] + 4); }
            fence_regs(p2); fence_regs(w2);
            products(m2, p2, w2);
            asm("mad.wide.u32 %0, %1, 512, %2;" : "=l"(om) : "r"(fl >> 16), "l"(outq));
#pragma unroll
            for (int k = 0; k < 3; k++) { lds128(vrow + 9216 + 1024 * k, v[k] + 8); lds128((vrow ^ 64) + 9216 + 1024 * k, v[k] + 12); }
#pragma unroll
            for (int j = 0; j < 8; j++) asm volatile("" : "=r"(ts[j]));
            lds2_if(srow, srow ^ 64, ts, fl & ST_MID);
#pragma unroll
            for (int k = 0; k < 3; k++) { vterm(k, 0); rterm(k, 0); stg2_if(om + 128 + 128 * k, acc + 8 + 8 * k, fl & ST_MID); }
            TC(4);
            if (t + (warp >> 2) < Tm) asm volatile("bar.arrive %0, 256;" ::"r"(4 - (warp >> 2)) : "memory");
            }
            t++;
            wg_fence();
            wgmma_group<0>(p3, w3, h, rf, d0);
            wg_commit();
            if (T > 1000000) asm volatile("nanosleep.u32 0;");
#pragma unroll
            for (int k = 1; k < 4; k++) lds2_if(srow + 1024 * k, (srow ^ 64) + 1024 * k, acc + 8 * k, fl & ST_MID);
            uint32_t lo;
            asm volatile("ld.shared.u16 %0, [%1];" : "=r"(lo) : "r"(lent) : "memory");
            __syncwarp();
            if (lane == 0 && t > 0) mbar_arrive(bar_empty);
            if (t > 0) TC(5);
            if (t >= T) {
                asm("mad.wide.u32 %0, %1, 512, %2;" : "=l"(op) : "r"(fl & 511), "l"(outq));
#pragma unroll
                for (int k = 0; k < 3; k++) { vterm(k, 8); rterm(k, 8); stg2_if(op + 128 + 128 * k, acc + 8 + 8 * k, fl & ST_CLOSE); }
                wg_wait<0>();
                fence_regs(p3); fence_regs(w3);
                products(m1, p3, w3);
#pragma unroll
                for (int j = 0; j < 8; j++) acc[j] = hadd2(acc[j], m1[j]);
                stg2_if(om, acc, fl & ST_MID);
#pragma unroll
                for (int j = 0; j < 8; j++) acc[j] = hadd2(fl & ST_MID ? ts[j] : acc[j], m1[8 + j]);
                stg2_if(op, acc, fl & ST_CLOSE);
                asm volatile("cp.async.wait_all;" ::: "memory");
                break;
            }
            mbar_wait(bar_full + 8 * (t & 1), (t >> 1) & 1);
            if (t > 0) TC(6);
            wg_fence();
            wgmma_ss_k64(y, d0 + ((RING_OFF >> 4) + (warp >> 2) * 4096 + (t & 1) * 256 + ((uint64_t)(512 - 64) << 32)), d0);
            wg_commit();
            if (T > 1000000) asm volatile("nanosleep.u32 0;");
            asm("mad.wide.u32 %0, %1, 512, %2;" : "=l"(op) : "r"(fl & 511), "l"(outq));
            vrow ^= 4096;
#pragma unroll
            for (int k = 0; k < 3; k++) vterm(k, 8);
#define BBS if (T > 1000000) asm volatile("nanosleep.u32 0;")
            auto silu = [&](int i0, int i1) {
#pragma unroll
                for (int i = i0; i < i1; i++)
                    h[i] = pack2(fmaf(y[2 * i], tanh_fast(y[2 * i]), y[2 * i]), fmaf(y[2 * i + 1], tanh_fast(y[2 * i + 1]), y[2 * i + 1]));
            };
#pragma unroll
            for (int k = 0; k < 3; k++) rterm(k, 8);
            const uint32_t fo = fl;
            asm volatile("ld.shared.v2.u32 {%0,%1}, [%4];\nld.shared.v2.u32 {%2,%3}, [%4 + 512];" : "=r"(rr[0]), "=r"(rr[1]), "=r"(rr[2]), "=r"(rr[3]) : "r"(ent) : "memory");
            asm volatile("ld.shared.u32 %0, [%1];" : "=r"(fl) : "r"(fent) : "memory");
            stg2_if(op + 128, acc + 8, fo & ST_CLOSE);
            BBS;
            if (t > 0) TC(7);
            wg_wait<0>();
            fence_regs(p3); fence_regs(w3); fence_regs(y);
            if (t > 0) TC(8);
            ldsm4(lutq + lo, rf);
            products(m1, p3, w3);
            silu(0, 6);
            stg2_if(op + 256, acc + 16, fo & ST_CLOSE);
            BBS;
#pragma unroll
            for (int j = 0; j < 8; j++) acc[j] = hadd2(acc[j], m1[j]);
            stg2_if(om, acc, fo & ST_MID);
#pragma unroll
            for (int j = 0; j < 8; j++) acc[j] = hadd2(fo & ST_MID ? ts[j] : acc[j], m1[8 + j]);
            silu(6, 11);
            stg2_if(op + 384, acc + 24, fo & ST_CLOSE);
            BBS;
            silu(11, 16);
            stg2_if(op, acc, fo & ST_CLOSE);
            ent += 1024; fent += 256; lent += 1024;
        }
        TSX(15, 0);
        TSX(16, 128);
    } else {
        asm volatile("setmaxnreg.dec.sync.aligned.u32 %0;" ::"n"(256 - REG_C));
        const int lane = fresh_lane();
        const int w = warp - 8, s = lane >> 3, c = lane & 7, nzero = misc[36] & 0xFFFF;
        uint32_t sdst = sb + RING_OFF + w * 16384 + s * 128 + ((c ^ s) << 4);
        const uint32_t sw = s * 128 + ((c ^ ((s & 1) << 2)) << 4);
        uint32_t vdst = sb + RING_OFF + w * 16384 + sw;
        const uint32_t odst = sb + SIDE_OFF + w * 4096 + sw;
        uint32_t ent = sb + ND_OFF + (w * 8 + s) * 4;
        const char* svl = reinterpret_cast<const char*>(p.sv) + c * 16;
        const char* own = svl + (size_t)nbase * 512;
        pause((warp & 4 ? LAG1 : 0) + LAG * max(min(16 - (int)(misc[2] + misc[3]), 2), 0));
#pragma unroll 1
        for (int t = 1; t <= T; t++) {
            const uint32_t e = sb + SRC_OFF + t * 256 + (w * 8 + s) * 2;
            const uint32_t s0 = lds16(e), s1 = lds16(e + 8), s2 = lds16(e + 128), s3 = lds16(e + 136);
            const uint32_t f0 = lds32(ent), f1 = lds32(ent + 16);
            ent += 256;
            sdst ^= 4096; vdst ^= 4096;
            TR(5, 256, t);
            mbar_wait(bar_empty, t & 1);
            TR(6, 256, t);
            gather_row_if(odst, own + (f0 & 511) * 512, f0 & (ST_START | ST_MID));
            gather_row_if(odst + 512, own + (f1 & 511) * 512, f1 & (ST_START | ST_MID));
            cp_async_arrive(bar_side);
            if (t == T) break;
            gather_s(sdst, svl, s0);
            gather_s((sdst ^ 64) + 512, svl, s1);
            gather_s(sdst + 8192, svl, s2);
            gather_s((sdst ^ 64) + 8704, svl, s3);
            cp_async_arrive(bar_full + 8 * (t & 1));
            gather_v(vdst, svl, s0);
            gather_v(vdst + 512, svl, s1);
            gather_v(vdst + 8192, svl, s2);
            gather_v(vdst + 8704, svl, s3);
            TR(7, 256, t);
        }
        TSX(17, 256);
        TSX(20, 384);
        const uint32_t rb = sb + RING_OFF + w * 16384 + (max(T, 1) & 1) * 4096 + s * 512 + c * 16;
#pragma unroll 1
        for (int z = (w & 3) + ((w >> 2) == (misc[2] > misc[3]) ? 0 : 48); z < nzero; z += 96) {
            const int n = (nzero - z + 3) >> 2;
            uint32_t zn[3];
#pragma unroll
            for (int i = 0; i < 3; i++) zn[i] = lds16(sb + ZL_OFF + 2 * min(z + 16 * i + 4 * s, 511));
#pragma unroll
            for (int i = 0; i < 3; i++)
                asm volatile("{\n.reg .pred p;\nsetp.lt.s32 p, %2, %3;\n@p cp.async.cg.shared.global [%0], [%1], 16;\n@p cp.async.cg.shared.global [%0 + 128], [%1 + 128], 16;\n"
                             "@p cp.async.cg.shared.global [%0 + 256], [%1 + 256], 16;\n@p cp.async.cg.shared.global [%0 + 384], [%1 + 384], 16;\n}\n"
                             ::"r"(rb + (i & 1) * 2048 + (i >> 1) * 8192), "l"(own + zn[i] * 512), "r"(4 * i + s), "r"(n) : "memory");
            TSX(21, 256);
            asm volatile("cp.async.wait_all;" ::: "memory");
            TSX(22, 256);
#pragma unroll
            for (int i = 0; i < 3; i++) {
                if (4 * i < n) {
                    char* dst = reinterpret_cast<char*>(p.out) + (size_t)(nbase + zn[i]) * 512 + c * 16;
#pragma unroll
                    for (int k = 0; k < 4; k += 2) {
                        uint32_t x[8];
                        lds128(rb + (i & 1) * 2048 + (i >> 1) * 8192 + k * 128, x);
                        lds128(rb + (i & 1) * 2048 + (i >> 1) * 8192 + k * 128 + 128, x + 4);
                        if (4 * i + s < n) {
                            __stcs(reinterpret_cast<uint4*>(dst + k * 128), make_uint4(x[0], x[1], x[2], x[3]));
                            __stcs(reinterpret_cast<uint4*>(dst + k * 128 + 128), make_uint4(x[4], x[5], x[6], x[7]));
                        }
                    }
                }
            }
        }
        mbar_wait(bar_tab + 8, 0);
        TSX(11, 256);
        TSX(19, 384);
    }
}

}

extern "C" void kernel_launch(void* const* d_in, const int* in_sizes, int n_in, void* d_out, int out_size) {
    static int s_G = 0;
    static void* s_scratch = nullptr;
    static void* s_encode = nullptr;
    const int N = in_sizes[0] / 256, E = in_sizes[2];
    if (s_G == 0) {
        cudaFuncSetAttribute(painn_kernel<0, 0, 0>, cudaFuncAttributeMaxDynamicSharedMemorySize, SMEM_BYTES);
        cudaFuncSetAttribute(painn_kernel<50000, 800000, 132>, cudaFuncAttributeMaxDynamicSharedMemorySize, SMEM_BYTES);
        int dev = 0, sms = 0, occ = 0;
        cudaGetDevice(&dev);
        cudaDeviceGetAttribute(&sms, cudaDevAttrMultiProcessorCount, dev);
        cudaOccupancyMaxActiveBlocksPerMultiprocessor(&occ, painn_kernel<0, 0, 0>, THREADS, SMEM_BYTES);
        cudaGetSymbolAddress(&s_scratch, g_scratch);
        cudaDriverEntryPointQueryResult qr;
        cudaGetDriverEntryPoint("cuTensorMapEncodeTiled", &s_encode, cudaEnableDefault, &qr);
        s_G = occ >= 1 ? (sms < MAXG ? sms : MAXG) : 0;
    }
    if (s_G == 0 || N > TABLE_MAXN || N > s_G * (MAXNPC - 1) || (s_G - 1) * ((N + s_G - 1) / s_G) >= N || E > MAXE || E < 4 * MAXG * MAXG) return;
    Params p;
    CUtensorMap tm;
    {
        typedef CUresult (*Encode)(CUtensorMap*, CUtensorMapDataType, cuuint32_t, void*, const cuuint64_t*, const cuuint64_t*, const cuuint32_t*,
                                   const cuuint32_t*, CUtensorMapInterleave, CUtensorMapSwizzle, CUtensorMapL2promotion, CUtensorMapFloatOOBfill);
        const cuuint64_t dims[2] = {64, (cuuint64_t)N * 4}, strides[1] = {128};
        const cuuint32_t box[2] = {8, 32}, es[2] = {1, 1};
        ((Encode)s_encode)(&tm, CU_TENSOR_MAP_DATA_TYPE_BFLOAT16, 2, d_in[0], dims, strides, box, es, CU_TENSOR_MAP_INTERLEAVE_NONE,
                           CU_TENSOR_MAP_SWIZZLE_NONE, CU_TENSOR_MAP_L2_PROMOTION_L2_128B, CU_TENSOR_MAP_FLOAT_OOB_FILL_NONE);
    }
    p.g = (Scratch*)s_scratch;
    p.sv = (const __nv_bfloat16*)d_in[0];
    p.pos = (const __nv_bfloat16*)d_in[1];
    p.src = (const int*)d_in[2];
    p.dst = (const int*)d_in[3];
    p.freqs = (const __nv_bfloat16*)d_in[4];
    p.w1 = (const __nv_bfloat16*)d_in[5];
    p.w2 = (const __nv_bfloat16*)d_in[6];
    p.wr = (const __nv_bfloat16*)d_in[7];
    p.out = (__nv_bfloat16*)d_out;
    p.desc0 = (uint64_t)(SB >> 4) | ((uint64_t)1 << 16) | ((uint64_t)64 << 32) | ((uint64_t)1 << 62);
    p.N = N; p.E = E; p.G = s_G;
    p.NPC = (N + s_G - 1) / s_G;
    p.magic = (uint32_t)(((1ull << 32) + p.NPC - 1) / p.NPC);
    p.gpc = ((E >> 2) + s_G - 1) / s_G;
    p.odd_edges = (E & 3) != 0 || p.gpc > 3 * THREADS;
    if (N == 50000 && E == 800000 && s_G == 132) painn_kernel<50000, 800000, 132><<<s_G, THREADS, SMEM_BYTES, cudaStreamPerThread>>>(p, tm);
    else painn_kernel<0, 0, 0><<<s_G, THREADS, SMEM_BYTES, cudaStreamPerThread>>>(p, tm);
}
```

```cpp
#include <cuda_runtime.h>
#include <cuda_bf16.h>
#include <cuda.h>
#include <stdint.h>

namespace {

constexpr int REG_C = 224;
constexpr int PDELAY = 200;
constexpr int WA = 7, WC = 3, WE = 3;
constexpr int P0 = 100, P1W = 200;
constexpr int LAG = 1200, LAG1 = 1300;
constexpr int NP = 8, NLEFT = 4;
constexpr int THREADS = 512;
constexpr int MAXG = 136;
constexpr int XH = MAXG * MAXG * 4;
constexpr int ROUNDS = 11;
constexpr int LUTS = 286, LUTN = 318;
constexpr int MAXNPC = 480;
constexpr int MAXE = 1 << 20;

constexpr int W2_OFF = 8192;
constexpr int WR_OFF = 32768;
constexpr int WIMG = 38912;
constexpr int ZL_OFF = WIMG;
constexpr int RING_OFF = 39936;
constexpr int SIDE_OFF = RING_OFF + 16 * 8192;
constexpr int RR_OFF = SIDE_OFF + 32768;
constexpr int ND_OFF = RR_OFF + ROUNDS * 1024;
constexpr int SRC_OFF = ND_OFF + ROUNDS * 256;
constexpr int LUT_OFF = SRC_OFF + ROUNDS * 256;
constexpr int SINK_OFF = LUT_OFF + 320 * 32;
constexpr int BAR_OFF = SINK_OFF + 512;
constexpr int MISC_OFF = BAR_OFF + 8 * 46;
constexpr int SMEM_BYTES = MISC_OFF + 192 + MAXG;
constexpr int PITCH = 144;
constexpr int TABLE_MAXN = 50176;
constexpr int STAGE_OFF = TABLE_MAXN * 4;
constexpr int SCNT_OFF = STAGE_OFF + MAXG * PITCH;
constexpr int OVL_OFF = MISC_OFF + 192;
constexpr int OPOS_OFF = LUT_OFF + 1024;
constexpr int NCNT_OFF = SIDE_OFF;
constexpr int NPOS_OFF = NCNT_OFF + 2048;
constexpr int YL_OFF = NPOS_OFF + 4096;
constexpr int TL_OFF = YL_OFF + 1024;
constexpr int E0_OFF = TL_OFF + 1024;
constexpr int SLOT_OFF = E0_OFF + 2048;
constexpr int SIZE_OFF = SLOT_OFF + 1280;
static_assert(SCNT_OFF + 4 * (MAXG + 32) <= OPOS_OFF && OPOS_OFF + 4096 <= LUT_OFF + LUTS * 32, "smem map");
static_assert(2 * (480 - 3 * MAXG) >= MAXG, "chunk map");
static_assert(SMEM_BYTES <= 232448 && MISC_OFF % 16 == 0 && BAR_OFF % 8 == 0 && (RING_OFF + 1024) % 8192 == 0 && SINK_OFF % 128 == 0, "smem map");

constexpr uint32_t PAY_INVALID = 0x3FFFFFFu;
constexpr uint32_t PAY_MARK = 0x3FFFDFFu;
constexpr uint32_t ST_START = 512, ST_CLOSE = 1024, ST_MID = 2048;
constexpr float QINVP = 9.0f / 510.0f;
constexpr uint32_t QTHRESH = 2126;

struct Scratch {
    unsigned sync[32];
    uint4 table[TABLE_MAXN / 4];
    uint4 wimg[WIMG / 16 + LUTS * 2 + 4];
    uint2 pos8[TABLE_MAXN];
    uint4 xbuf[2 * XH];
    int ovfcnt[MAXG];
    int2 ovf[MAXE + 8 * MAXG + 8];
};
__device__ __align__(128) Scratch g_scratch;

struct Params {
    const __nv_bfloat16* pos;
    Scratch* g;
    const int* src;
    const int* dst;
    int N, NPC, E, gpc;
    const __nv_bfloat16* w2;
    const __nv_bfloat16* wr;
    const __nv_bfloat16* w1;
    const __nv_bfloat16* freqs;
    const __nv_bfloat16* sv;
    __nv_bfloat16* out;
    uint64_t desc0;
    int G;
    uint32_t magic;
    int odd_edges;
};
constexpr uint32_t SB = 1024;

#define TSX(i, thr)
#define TR(k, thr, t)
#define TC(k)
#define TS0(i) TSX(i, 0)

__device__ __forceinline__ uint32_t smem_u32(const void* p) { return (uint32_t)__cvta_generic_to_shared(p); }
__device__ __forceinline__ void mbar_init(uint32_t bar, uint32_t cnt) {
    asm volatile("mbarrier.init.shared::cta.b64 [%0], %1;" ::"r"(bar), "r"(cnt) : "memory");
}
__device__ __forceinline__ void mbar_arrive(uint32_t bar) {
    asm volatile("mbarrier.arrive.shared::cta.b64 _, [%0];" ::"r"(bar) : "memory");
}
__device__ __forceinline__ void mbar_expect_tx(uint32_t bar, uint32_t bytes) {
    asm volatile("mbarrier.arrive.expect_tx.shared::cta.b64 _, [%0], %1;" ::"r"(bar), "r"(bytes) : "memory");
}
__device__ __forceinline__ void mbar_wait(uint32_t bar, uint32_t parity) {
    asm volatile("{\n.reg .pred p;\n.reg .u32 c;\nmbarrier.try_wait.parity.shared::cta.b64 p, [%0], %1;\n@p bra DONE;\nmov.u32 c, 0;\n"
                 "AGAIN:\nmbarrier.try_wait.parity.shared::cta.b64 p, [%0], %1, 2000;\n@p bra DONE;\nadd.u32 c, c, 1;\n"
                 "setp.lt.u32 p, c, 0x100000;\n@p bra AGAIN;\ntrap;\nDONE:\n}\n" ::"r"(bar), "r"(parity) : "memory");
}
__device__ __forceinline__ void pause(uint32_t cycles) {
    uint32_t t0, t;
    asm volatile("mov.u32 %0, %%clock;" : "=r"(t0));
    do {
        __nanosleep(20);
        asm volatile("mov.u32 %0, %%clock;" : "=r"(t));
    } while (t - t0 < cycles);
}
__device__ __forceinline__ bool elect() {
    uint32_t r;
    asm volatile("{\n.reg .pred p;\nelect.sync _|p, 0xffffffff;\nselp.u32 %0, 1, 0, p;\n}\n" : "=r"(r));
    return r;
}
__device__ __forceinline__ uint32_t pin(uint32_t x) {
    uint32_t r;
    asm volatile("shfl.sync.bfly.b32 %0, %1, 0, 31, -1;" : "=r"(r) : "r"(x));
    return r;
}
__device__ __forceinline__ void bulk_g2s(uint32_t dst, const void* src, uint32_t bytes, uint32_t bar) {
    asm volatile("cp.async.bulk.shared::cluster.global.mbarrier::complete_tx::bytes [%0], [%1], %2, [%3];"
                 ::"r"(dst), "l"(src), "r"(bytes), "r"(bar) : "memory");
}
__device__ __forceinline__ void ldsm4(uint32_t addr, uint32_t* r) {
    asm volatile("ldmatrix.sync.aligned.m8n8.x4.shared.b16 {%0,%1,%2,%3}, [%4];"
                 : "=r"(r[0]), "=r"(r[1]), "=r"(r[2]), "=r"(r[3]) : "r"(addr) : "memory");
}
__device__ __forceinline__ uint32_t pack2(float lo, float hi) {
    uint32_t r;
    asm("cvt.rn.bf16x2.f32 %0, %1, %2;" : "=r"(r) : "f"(hi), "f"(lo));
    return r;
}
__device__ __forceinline__ float bf_lo(uint32_t w) { return __uint_as_float(w << 16); }
__device__ __forceinline__ float bf_hi(uint32_t w) { return __uint_as_float(w & 0xFFFF0000u); }
__device__ __forceinline__ float rbf16(float x) { return __uint_as_float(pack2(0.f, x)); }
__device__ __forceinline__ uint32_t hmul2(uint32_t a, uint32_t b) {
    uint32_t r;
    asm("mul.rn.bf16x2 %0, %1, %2;" : "=r"(r) : "r"(a), "r"(b));
    return r;
}
__device__ __forceinline__ uint32_t hfma2(uint32_t a, uint32_t b, uint32_t c) {
    uint32_t r;
    asm("fma.rn.bf16x2 %0, %1, %2, %3;" : "=r"(r) : "r"(a), "r"(b), "r"(c));
    return r;
}
__device__ __forceinline__ uint32_t hfma2_lo(uint32_t a, uint32_t b, uint32_t c) {
    uint32_t r;
    asm("{\n.reg .b16 l, h;\n.reg .b32 t;\nmov.b32 {l, h}, %2;\nmov.b32 t, {l, l};\nfma.rn.bf16x2 %0, %1, t, %3;\n}\n" : "=r"(r) : "r"(a), "r"(b), "r"(c));
    return r;
}
__device__ __forceinline__ uint32_t hfma2_hi(uint32_t a, uint32_t b, uint32_t c) {
    uint32_t r;
    asm("{\n.reg .b16 l, h;\n.reg .b32 t;\nmov.b32 {l, h}, %2;\nmov.b32 t, {h, h};\nfma.rn.bf16x2 %0, %1, t, %3;\n}\n" : "=r"(r) : "r"(a), "r"(b), "r"(c));
    return r;
}
__device__ __forceinline__ uint32_t hadd2(uint32_t a, uint32_t b) {
    uint32_t r;
    asm("add.rn.bf16x2 %0, %1, %2;" : "=r"(r) : "r"(a), "r"(b));
    return r;
}
__device__ __forceinline__ uint32_t hsub2(uint32_t a, uint32_t b) {
    uint32_t r;
    asm("sub.rn.bf16x2 %0, %1, %2;" : "=r"(r) : "r"(a), "r"(b));
    return r;
}
__device__ __forceinline__ void cp_async_arrive(uint32_t bar) {
    asm volatile("cp.async.mbarrier.arrive.noinc.shared::cta.b64 [%0];" ::"r"(bar) : "memory");
}
__device__ __forceinline__ float tanh_fast(float x) {
    float r;
    asm("tanh.approx.f32 %0, %1;" : "=f"(r) : "f"(x));
    return r;
}
__device__ __forceinline__ void wg_fence() { asm volatile("wgmma.fence.sync.aligned;" ::: "memory"); }
__device__ __forceinline__ void wg_commit() { asm volatile("wgmma.commit_group.sync.aligned;" ::: "memory"); }
template <int N>
__device__ __forceinline__ void wg_wait() { asm volatile("wgmma.wait_group.sync.aligned %0;" ::"n"(N) : "memory"); }

#define WG_REGS "{%0,%1,%2,%3,%4,%5,%6,%7,%8,%9,%10,%11,%12,%13,%14,%15,%16,%17,%18,%19,%20,%21,%22,%23,%24,%25,%26,%27,%28,%29,%30,%31}"
#define WG_OPS(c) c(d[0]), c(d[1]), c(d[2]), c(d[3]), c(d[4]), c(d[5]), c(d[6]), c(d[7]), c(d[8]), c(d[9]), c(d[10]), \
    c(d[11]), c(d[12]), c(d[13]), c(d[14]), c(d[15]), c(d[16]), c(d[17]), c(d[18]), c(d[19]), c(d[20]), c(d[21]),     \
    c(d[22]), c(d[23]), c(d[24]), c(d[25]), c(d[26]), c(d[27]), c(d[28]), c(d[29]), c(d[30]), c(d[31])
#define WG_OPSE(c) c(e[0]), c(e[1]), c(e[2]), c(e[3]), c(e[4]), c(e[5]), c(e[6]), c(e[7]), c(e[8]), c(e[9]), c(e[10]), c(e[11]), c(e[12]), c(e[13]), c(e[14]), c(e[15]), c(e[16]), c(e[17]), c(e[18]), c(e[19]), c(e[20]), c(e[21]), c(e[22]), c(e[23]), c(e[24]), c(e[25]), c(e[26]), c(e[27]), c(e[28]), c(e[29]), c(e[30]), c(e[31])
template <int OFF, int ACC, int IDX>
__device__ __forceinline__ void wgmma_rs(float* d, const uint32_t* a, uint64_t d0) {
    if (!ACC) {
#pragma unroll
        for (int i = 0; i < 32; i++) d[i] = 0.f;
    }
    if (IDX < 4)
        asm volatile("wgmma.mma_async.sync.aligned.m64n64k16.f32.bf16.bf16 " WG_REGS ", {%32,%33,%34,%35}, %36, %37, 1, 1, 1;"
                     : WG_OPS("+f") : "r"(a[0]), "r"(a[1]), "r"(a[2]), "r"(a[3]), "l"(d0 + (OFF >> 4)), "n"(ACC));
    else
        asm volatile("{\n.reg .b64 dd;\nmov.b64 dd, {%36, 0x40000040};\nwgmma.mma_async.sync.aligned.m64n64k16.f32.bf16.bf16 " WG_REGS
                     ", {%32,%33,%34,%35}, dd, %37, 1, 1, 1;\n}\n"
                     : WG_OPS("+f") : "r"(a[0]), "r"(a[1]), "r"(a[2]), "r"(a[3]), "n"(((SB + OFF) >> 4) | (1u << 16)), "n"(ACC));
}
template <int OFF, int LBO, int ACC>
__device__ __forceinline__ void wgmma_rs2(float* d, float* e, const uint32_t* a, uint64_t d0) {
    if (!ACC) {
#pragma unroll
        for (int i = 0; i < 32; i++) d[i] = e[i] = 0.f;
    }
    asm volatile("wgmma.mma_async.sync.aligned.m64n128k16.f32.bf16.bf16 {%0,%1,%2,%3,%4,%5,%6,%7,%8,%9,%10,%11,%12,%13,%14,%15,%16,%17,%18,%19,%20,%21,%22,%23,%24,%25,%26,%27,%28,%29,%30,%31,%32,%33,%34,%35,%36,%37,%38,%39,%40,%41,%42,%43,%44,%45,%46,%47,%48,%49,%50,%51,%52,%53,%54,%55,%56,%57,%58,%59,%60,%61,%62,%63}, {%64,%65,%66,%67}, %68, %69, 1, 1, 1;"
                 : WG_OPS("+f"), WG_OPSE("+f") : "r"(a[0]), "r"(a[1]), "r"(a[2]), "r"(a[3]), "l"(d0 + (OFF >> 4) + ((LBO / 16 - 1) << 16)), "n"(ACC));
}
template <int G>
__device__ __forceinline__ void wgmma_group(float* P, float* W, const uint32_t* h, const uint32_t* rf, uint64_t d0) {
    wgmma_rs<W2_OFF + 8192 * G, 0, 5 * G>(P, h, d0);
    wgmma_rs<W2_OFF + 8192 * G + 2048, 1, 5 * G + 1>(P, h + 4, d0);
    wgmma_rs<W2_OFF + 8192 * G + 4096, 1, 5 * G + 2>(P, h + 8, d0);
    wgmma_rs<W2_OFF + 8192 * G + 6144, 1, 5 * G + 3>(P, h + 12, d0);
    wgmma_rs<WR_OFF + 2048 * G, 0, 5 * G + 4>(W, rf, d0);
}
__device__ __forceinline__ void wgmma_ss_k64(float* d, uint64_t da, uint64_t db) {
#pragma unroll
    for (int i = 0; i < 32; i++) d[i] = 0.f;
    asm volatile("wgmma.mma_async.sync.aligned.m64n64k16.f32.bf16.bf16 " WG_REGS ", %32, %33, 0, 1, 1, 0, 1;" : WG_OPS("+f") : "l"(da), "l"(db));
#pragma unroll
    for (int k = 1; k < 4; k++)
        asm volatile("wgmma.mma_async.sync.aligned.m64n64k16.f32.bf16.bf16 " WG_REGS ", %32, %33, 1, 1, 1, 0, 1;"
                     : WG_OPS("+f") : "l"(da + 2 * k), "l"(db + 128 * k));
}
__device__ __forceinline__ void fence_regs(float* d) { asm volatile("" : WG_OPS("+f")::"memory"); }
__device__ __forceinline__ uint32_t qaxis(float x) {
    const float u = fmaf(x, QINVP, 0.25f);
    const float f = u - ((u + 12582912.f) - 12582912.f);
    return __float_as_uint(fmaf(fabsf(f), 510.f, 12582912.f));
}
__device__ __forceinline__ uint32_t qcode(float x, float y, float z, uint32_t tx) {
    return __byte_perm(__byte_perm(qaxis(x), qaxis(y), 0x3340), qaxis(z), 0x3410) ^ tx;
}
__device__ __forceinline__ bool near_test(uint32_t ca, uint32_t cb, uint32_t tag24) {
    const uint32_t D = __vabsdiffu4(ca, cb);
    return __dp4a(D, D, 0u) <= QTHRESH || ((ca ^ tag24) | (cb ^ tag24)) >= 0x1000000u;
}
constexpr float QMAX = 23.9375f;
__device__ __forceinline__ float square(uint32_t rxy, uint32_t rz) {
    const uint32_t qxy = hmul2(rxy, rxy), qz = hmul2(rz, rz);
    return bf_lo(qxy) + bf_hi(qxy) + bf_lo(qz);
}

__device__ __forceinline__ uint32_t lds32(uint32_t addr) {
    uint32_t r;
    asm volatile("ld.shared.u32 %0, [%1];" : "=r"(r) : "r"(addr) : "memory");
    return r;
}
__device__ __forceinline__ void sts32_if(uint32_t addr, uint32_t v, bool c) {
    asm volatile("{\n.reg .pred p;\nsetp.ne.u32 p, %2, 0;\n@p st.shared.u32 [%0], %1;\n}\n" ::"r"(addr), "r"(v), "r"((uint32_t)c) : "memory");
}
__device__ __forceinline__ uint32_t sel(bool c, uint32_t a, uint32_t b) {
    uint32_t r;
    asm("{\n.reg .pred p;\nsetp.ne.u32 p, %3, 0;\nselp.b32 %0, %1, %2, p;\n}\n" : "=r"(r) : "r"(a), "r"(b), "r"((uint32_t)c));
    return r;
}
__device__ __forceinline__ uint32_t lds16(uint32_t addr) {
    uint32_t r;
    asm volatile("ld.shared.u16 %0, [%1];" : "=r"(r) : "r"(addr) : "memory");
    return r;
}
__device__ __forceinline__ void sts16_if(uint32_t addr, uint32_t v, bool c) {
    asm volatile("{\n.reg .pred p;\nsetp.ne.u32 p, %2, 0;\n@p st.shared.u16 [%0], %1;\n}\n" ::"r"(addr), "h"((unsigned short)v), "r"((uint32_t)c) : "memory");
}
__device__ __forceinline__ void sts64_if(uint32_t addr, uint32_t x, uint32_t y, bool c) {
    asm volatile("{\n.reg .pred p;\nsetp.ne.u32 p, %3, 0;\n@p st.shared.v2.u32 [%0], {%1, %2};\n}\n" ::"r"(addr), "r"(x), "r"(y), "r"((uint32_t)c) : "memory");
}
__device__ __forceinline__ uint32_t atoms_add(uint32_t addr, uint32_t v) {
    uint32_t r;
    asm volatile("atom.shared.add.u32 %0, [%1], %2;" : "=r"(r) : "r"(addr), "r"(v) : "memory");
    return r;
}
__device__ __forceinline__ void stg128_if(void* ptr, uint4 v, bool c) {
    asm volatile("{\n.reg .pred p;\nsetp.ne.u32 p, %5, 0;\n@p st.relaxed.gpu.global.v4.u32 [%0], {%1,%2,%3,%4};\n}\n"
                 ::"l"(ptr), "r"(v.x), "r"(v.y), "r"(v.z), "r"(v.w), "r"((uint32_t)c) : "memory");
}
__device__ __forceinline__ void lds128(uint32_t addr, uint32_t* r) {
    asm volatile("ld.shared.v4.u32 {%0,%1,%2,%3}, [%4];" : "=r"(r[0]), "=r"(r[1]), "=r"(r[2]), "=r"(r[3]) : "r"(addr) : "memory");
}
__device__ __forceinline__ void stg2_if(uint64_t ptr, const uint32_t* r, uint32_t c) {
    asm volatile("{\n.reg .pred p;\nsetp.ne.u32 p, %9, 0;\n@p st.global.cs.v4.u32 [%8], {%0,%1,%2,%3};\n"
                 "@p st.global.cs.v4.u32 [%8 + 64], {%4,%5,%6,%7};\n}\n"
                 ::"r"(r[0]), "r"(r[1]), "r"(r[2]), "r"(r[3]), "r"(r[4]), "r"(r[5]), "r"(r[6]), "r"(r[7]), "l"(ptr), "r"(c) : "memory");
}
__device__ __forceinline__ void gather_s(uint32_t dst, const char* base, uint32_t src) {
    asm volatile("{\n.reg .pred p;\nsetp.eq.u32 p, %2, 0xFFFF;\ncp.async.cg.shared.global [%0], [%1], 16, p;\n}\n"
                 ::"r"(dst), "l"(base + (size_t)src * 512), "r"(src) : "memory");
}
__device__ __forceinline__ void gather_v(uint32_t dst, const char* base, uint32_t src) {
    asm volatile("{\n.reg .pred p;\nsetp.eq.u32 p, %2, 0xFFFF;\n"
                 "cp.async.cg.shared.global [%0 + 1024], [%1 + 128], 16, p;\ncp.async.cg.shared.global [%0 + 2048], [%1 + 256], 16, p;\n"
                 "cp.async.cg.shared.global [%0 + 3072], [%1 + 384], 16, p;\n}\n" ::"r"(dst), "l"(base + (size_t)src * 512), "r"(src) : "memory");
}
__device__ __forceinline__ void gather_row_if(uint32_t dst, const char* src, uint32_t c) {
    asm volatile("{\n.reg .pred p;\nsetp.ne.u32 p, %2, 0;\n@p cp.async.cg.shared.global [%0], [%1], 16;\n"
                 "@p cp.async.cg.shared.global [%0 + 1024], [%1 + 128], 16;\n@p cp.async.cg.shared.global [%0 + 2048], [%1 + 256], 16;\n"
                 "@p cp.async.cg.shared.global [%0 + 3072], [%1 + 384], 16;\n}\n" ::"r"(dst), "l"(src), "r"(c) : "memory");
}
__device__ __forceinline__ void lds2_if(uint32_t a0, uint32_t a1, uint32_t* r, uint32_t c) {
    asm volatile("{\n.reg .pred p;\nsetp.ne.u32 p, %10, 0;\n@p ld.shared.v4.u32 {%0,%1,%2,%3}, [%8];\n@p ld.shared.v4.u32 {%4,%5,%6,%7}, [%9];\n}\n"
                 : "+r"(r[0]), "+r"(r[1]), "+r"(r[2]), "+r"(r[3]), "+r"(r[4]), "+r"(r[5]), "+r"(r[6]), "+r"(r[7])
                 : "r"(a0), "r"(a1), "r"(c) : "memory");
}
__device__ __forceinline__ int fresh_lane() {
    int l;
    asm volatile("mov.u32 %0, %%laneid;" : "=r"(l));
    return l;
}

__device__ __forceinline__ void cold_edges(unsigned char* smem, const Params& p, int lo, int hi, uint32_t tag) {
#pragma unroll 1
    for (int e = lo + threadIdx.x; e < hi; e += THREADS) {
        const int s = p.src[e], d = p.dst[e];
        if (near_test(reinterpret_cast<const uint32_t*>(smem)[s], reinterpret_cast<const uint32_t*>(smem)[d], tag << 24)) {
            const uint32_t own = __umulhi((uint32_t)d, p.magic);
            const uint32_t slot4 = atomicAdd(reinterpret_cast<uint32_t*>(smem + SCNT_OFF) + own, 4u);
            uint32_t* line = reinterpret_cast<uint32_t*>(smem + STAGE_OFF) + own * (PITCH / 4);
            if (slot4 < 124) {
                line[slot4 >> 2] = ((uint32_t)s << 15) + ((uint32_t)(d - own * p.NPC) << 6) + tag;
            } else {
                uint32_t o = atomicAdd(reinterpret_cast<uint32_t*>(smem + MISC_OFF) + 16, 1u);
                p.g->ovf[(size_t)blockIdx.x * (4 * p.gpc + 4) + o] = make_int2(s, d);
                line[31] = (PAY_MARK << 6) | tag;
            }
        }
    }
}
__device__ __forceinline__ void cold_filter(unsigned char* smem, const Params& p, int e0, int e1, uint32_t tag, int redo) {
    if (redo) {
        if (threadIdx.x < MAXG) reinterpret_cast<uint32_t*>(smem + SCNT_OFF)[threadIdx.x] = 0;
        __syncthreads();
    }
    cold_edges(smem, p, redo ? 4 * e0 : 4 * (e0 + 3 * THREADS), 4 * e1, tag);
    if (blockIdx.x == 0) cold_edges(smem, p, p.E & ~3, p.E, tag);
    __syncthreads();
    if (threadIdx.x == 0) p.g->ovfcnt[blockIdx.x] = reinterpret_cast<uint32_t*>(smem + MISC_OFF)[16];
    __threadfence();
    __syncthreads();
}
__device__ __forceinline__ float distance(float q) {
    float d;
    asm("sqrt.approx.ftz.f32 %0, %1;" : "=f"(d) : "f"(rbf16(rbf16(q) + 1e-8f)));
    return rbf16(d);
}
__device__ __forceinline__ float fcut(float d) {
    return d < 5.0f ? 0.5f * rbf16(rbf16(__cosf(rbf16(rbf16(3.14159265358979f * d) * 0.2f))) + 1.0f) : 0.f;
}
__device__ __forceinline__ uint4 basis8(float d, uint4 f) {
    const float sc = __fdividef(fcut(d), d);
    const uint32_t dd = __byte_perm(__float_as_uint(d), 0, 0x3232);
    uint32_t x[4] = {hmul2(f.x, dd), hmul2(f.y, dd), hmul2(f.z, dd), hmul2(f.w, dd)};
#pragma unroll
    for (int i = 0; i < 4; i++) x[i] = pack2(__sinf(bf_lo(x[i])) * sc, __sinf(bf_hi(x[i])) * sc);
    return make_uint4(x[0], x[1], x[2], x[3]);
}
__device__ __forceinline__ void cold_nodes(unsigned char* smem, const Params& p, int nn, uint32_t tag) {
    float* acc = reinterpret_cast<float*>(smem + RING_OFF);
    const int nbase = blockIdx.x * p.NPC, lane = threadIdx.x & 31;
    const uint32_t* sv = reinterpret_cast<const uint32_t*>(p.sv);
    const volatile uint32_t* xin = reinterpret_cast<const uint32_t*>(p.g->xbuf) + blockIdx.x * p.G * 16;
    auto word = [](int i) { return (i >> 5) * 16 + (i & 15) + (i & 16 ? XH * 4 : 0); };
#pragma unroll 1
    for (int i = threadIdx.x; i < p.G * 32; i += THREADS) {
        if ((int)xin[word((i & ~31) + 15)] < (int)(PAY_MARK << 6)) {
            uint32_t w;
            int it = 0;
            do {
                w = xin[word(i)];
                if (++it > (1 << 22)) __trap();
            } while ((w ^ tag) & 63u);
            if ((w >> 6) == PAY_MARK) smem[OVL_OFF + atomicAdd(reinterpret_cast<uint32_t*>(smem + MISC_OFF) + 17, 1u)] = (unsigned char)(i >> 5);
        }
    }
    __threadfence();
    __syncthreads();
    const int nmark = reinterpret_cast<uint32_t*>(smem + MISC_OFF)[17];
#pragma unroll 1
    for (int c0 = 0; c0 < nn; c0 += 128) {
        __syncthreads();
#pragma unroll 1
        for (int i = threadIdx.x; i < 128 * 256; i += THREADS) acc[i] = 0.f;
        __syncthreads();
#pragma unroll 1
        for (int m = -1; m < nmark; m++) {
            const int pr = m < 0 ? 0 : smem[OVL_OFF + m];
            const int cnt = m < 0 ? p.G * 32 : __ldcg(&p.g->ovfcnt[pr]);
#pragma unroll 1
            for (int i = threadIdx.x; i - lane < cnt; i += THREADS) {
                int2 e = make_int2(0, -1);
                if (i < cnt) {
                    if (m < 0) {
                        const uint32_t w = xin[word(i)];
                        if (((w ^ tag) & 63u) == 0) e = make_int2((w >> 15) & 0xFFFFu, (w >> 6) & 511u);
                    } else {
                        e = __ldcg(p.g->ovf + (size_t)pr * (4 * p.gpc + 4) + i);
                        e.y -= nbase;
                    }
                }
                uint32_t rxy = 0, rz = 0;
                bool in = e.y >= c0 && e.y < min(c0 + 128, nn);
                if (in) {
                    const uint2 ps = __ldcg(p.g->pos8 + e.x), pd = __ldcg(p.g->pos8 + nbase + e.y);
                    rxy = hsub2(ps.x, pd.x);
                    rz = hsub2(ps.y, pd.y);
                    in = square(rxy, rz) < QMAX;
                }
#pragma unroll 1
                for (uint32_t todo = __ballot_sync(0xffffffffu, in); todo; todo &= todo - 1) {
                    const int l = __ffs(todo) - 1;
                    const uint32_t* row = sv + (size_t)__shfl_sync(0xffffffffu, e.x, l) * 128 + lane;
                    float* o = acc + (__shfl_sync(0xffffffffu, e.y, l) - c0) * 256 + 2 * lane;
                    const uint32_t xy = __shfl_sync(0xffffffffu, rxy, l), z = __shfl_sync(0xffffffffu, rz, l);
                    const float d = distance(square(xy, z)), fc = fcut(d);
                    uint32_t x = __ldg(row);
                    float y0 = 0.f, y1 = 0.f, m2[6];
#pragma unroll 4
                    for (int k = 0; k < 64; k++) {
                        const uint32_t u = __shfl_sync(0xffffffffu, x, k >> 1), w = __ldg(reinterpret_cast<const uint32_t*>(p.w1) + k * 32 + lane);
                        const float a = k & 1 ? bf_hi(u) : bf_lo(u);
                        y0 = fmaf(a, bf_lo(w), y0);
                        y1 = fmaf(a, bf_hi(w), y1);
                    }
                    y0 = rbf16(y0); y1 = rbf16(y1);
                    x = pack2(y0 / (1.f + __expf(-y0)), y1 / (1.f + __expf(-y1)));
                    const float rb = rbf16(rbf16(__sinf(rbf16(d * __bfloat162float(p.freqs[lane & 15])))) / d);
#pragma unroll
                    for (int g = 0; g < 3; g++) {
                        float p0 = 0.f, p1 = 0.f, w0 = 0.f, w1 = 0.f;
#pragma unroll 4
                        for (int k = 0; k < 64; k++) {
                            const uint32_t u = __shfl_sync(0xffffffffu, x, k >> 1), w = __ldg(reinterpret_cast<const uint32_t*>(p.w2) + k * 96 + g * 32 + lane);
                            const float a = k & 1 ? bf_hi(u) : bf_lo(u);
                            p0 = fmaf(a, bf_lo(w), p0);
                            p1 = fmaf(a, bf_hi(w), p1);
                        }
#pragma unroll 4
                        for (int k = 0; k < 16; k++) {
                            const uint32_t w = __ldg(reinterpret_cast<const uint32_t*>(p.wr) + k * 96 + g * 32 + lane);
                            const float a = __shfl_sync(0xffffffffu, rb, k);
                            w0 = fmaf(a, bf_lo(w), w0);
                            w1 = fmaf(a, bf_hi(w), w1);
                        }
                        m2[2 * g] = rbf16(rbf16(p0) * rbf16(rbf16(w0) * fc));
                        m2[2 * g + 1] = rbf16(rbf16(p1) * rbf16(rbf16(w1) * fc));
                    }
                    atomicAdd(o, m2[0]);
                    atomicAdd(o + 1, m2[1]);
#pragma unroll
                    for (int k = 1; k < 4; k++) {
                        const uint32_t v = __ldg(row + 32 * k);
                        const float rh = rbf16((k == 1 ? bf_lo(xy) : k == 2 ? bf_hi(xy) : bf_lo(z)) / d);
                        atomicAdd(o + 64 * k, fmaf(m2[2], bf_lo(v), m2[4] * rh));
                        atomicAdd(o + 64 * k + 1, fmaf(m2[3], bf_hi(v), m2[5] * rh));
                    }
                }
            }
        }
        __syncthreads();
#pragma unroll 1
        for (int i = threadIdx.x; i < min(128, nn - c0) * 128; i += THREADS) {
            const uint32_t v = __ldg(sv + (size_t)(nbase + c0) * 128 + i);
            reinterpret_cast<uint32_t*>(p.out)[(size_t)(nbase + c0) * 128 + i] = pack2(bf_lo(v) + rbf16(acc[2 * i]), bf_hi(v) + rbf16(acc[2 * i + 1]));
        }
    }
}

template <int CN, int CE, int CG>
__global__ void __launch_bounds__(THREADS, 1) painn_kernel(const __grid_constant__ Params p, const __grid_constant__ CUtensorMap tm) {
    extern __shared__ __align__(1024) unsigned char smem_dyn[];
    unsigned char* const smem = static_cast<unsigned char*>(__cvta_shared_to_generic(SB));
    constexpr uint32_t sb = SB;
    const int tid = threadIdx.x, lane = tid & 31;
    const int warp = __shfl_sync(0xffffffffu, tid >> 5, 0);
    constexpr int CNPC = CG ? (CN + CG - 1) / CG : 1, CGPC = CG ? (CE / 4 + CG - 1) / CG : 1;
    const int b = blockIdx.x, G = CG ? CG : p.G, NPC = CG ? CNPC : p.NPC, N = CG ? CN : p.N, gpc = CG ? CGPC : p.gpc;
    const uint32_t magic = CG ? (uint32_t)(((1ull << 32) + CNPC - 1) / CNPC) : p.magic;
    const bool odd_edges = CG ? (CE & 3) != 0 || CGPC > 3 * THREADS : p.odd_edges;
    const int nbase = b * NPC, nn = min(NPC, N - nbase);
    const int e0 = b * gpc, e1 = min((CG ? CE : p.E) >> 2, e0 + gpc);

    uint4* stage4 = reinterpret_cast<uint4*>(smem + STAGE_OFF);
    uint32_t* ncnt = reinterpret_cast<uint32_t*>(smem + NCNT_OFF);
    uint32_t* misc = reinterpret_cast<uint32_t*>(smem + MISC_OFF);
    const uint32_t bar_full = sb + BAR_OFF + (warp & 7) * 40, bar_empty = bar_full + 16, bar_side = bar_full + 32, bar_tab = sb + BAR_OFF + 336;

    auto warm = [&](int first, int n) {
#pragma unroll 1
        for (int i = first; i < first + n; i++) {
            if (elect())
                asm volatile("cp.async.bulk.tensor.2d.shared::cluster.global.mbarrier::complete_tx::bytes [%0], [%1, {0, %3}], [%2];"
                             ::"r"(sb + SINK_OFF), "l"(&tm), "r"(bar_tab + 8), "r"(nbase * 4 + i * 32) : "memory");
        }
    };
    TS0(0);
    int4 es[3], ed[3];
    auto load_edges = [&](int i) {
        const int g = min(e0 + tid + i * THREADS, e1 - 1);
        asm volatile("ld.global.cs.v4.u32 {%0,%1,%2,%3}, [%8];\nld.global.cs.v4.u32 {%4,%5,%6,%7}, [%9];"
                     : "=r"(es[i].x), "=r"(es[i].y), "=r"(es[i].z), "=r"(es[i].w), "=r"(ed[i].x), "=r"(ed[i].y), "=r"(ed[i].z), "=r"(ed[i].w)
                     : "l"(reinterpret_cast<const int4*>(p.src) + g), "l"(reinterpret_cast<const int4*>(p.dst) + g) : "memory");
    };
    unsigned epoch;
    const uint32_t tbytes = ((N + 3) >> 2) * 16;
    {
        uint32_t pxy, pz;
        asm volatile("ld.global.nc.u32 %0, [%3];\nld.global.nc.u32 %1, [%3 + 4];\nld.global.ca.u32 %2, [%4];"
                     : "=r"(pxy), "=r"(pz), "=r"(epoch)
                     : "l"(reinterpret_cast<const uint32_t*>(p.pos) + ((nbase + min(tid, nn - 1)) * 3 >> 1)), "l"(p.g->sync) : "memory");
        const uint32_t sh = ((nbase + tid) & 1) << 4;
        pxy = __funnelshift_r(pxy, pz, sh);
        pz >>= sh;
        if (tid < nn) {
            reinterpret_cast<uint32_t*>(p.g->table)[nbase + tid] = qcode(bf_lo(pxy), bf_hi(pxy), bf_lo(pz), ((epoch & 31u) ^ 0x6Bu) << 24);
            p.g->pos8[nbase + tid] = make_uint2(pxy, pz);
        }
        reinterpret_cast<uint2*>(smem + OPOS_OFF)[tid] = make_uint2(pxy, pz);
        if (pxy == 0xFFFFFFFFu && pz == 0xFFFFFFFFu && epoch == 0xFFFFFFFFu) asm volatile("nanosleep.u32 0;");
        load_edges(0);
    }
    __syncthreads();
    const uint32_t tag = (epoch & 31u) | 32u;
    if (warp == 15) {
        if (elect()) {
            asm volatile("red.relaxed.gpu.global.add.u32 [%0], 1;" ::"l"(p.g->sync + 8 + b * NP / G) : "memory");
            asm volatile("prefetch.tensormap [%0];" ::"l"(&tm) : "memory");
            mbar_init(bar_tab, 1);
            mbar_init(bar_tab + 8, 1);
            mbar_expect_tx(bar_tab, tbytes);
            mbar_expect_tx(bar_tab + 8, (WA + WC + WE) * 512);
        }
        TSX(1, 511);
    }
    if (warp == 14) {
#pragma unroll 1
        for (int c = b * 32 + lane; c < WIMG / 16 + LUTS * 2; c += G * 32) {
            const int row = c >> 3, j = (c ^ row) & 7;
            uint4 v;
            if (c < 512) {
                const uint32_t half = 0x3F003F00u;
                v = __ldg(reinterpret_cast<const uint4*>(p.w1) + row * 8 + j);
                v = make_uint4(hmul2(v.x, half), hmul2(v.y, half), hmul2(v.z, half), hmul2(v.w, half));
            } else if (c >= WIMG / 16) {
                v = basis8(__uint_as_float((0x409D - ((c - WIMG / 16) >> 1)) << 16), __ldg(reinterpret_cast<const uint4*>(p.freqs) + (c & 1)));
            } else {
                const uint32_t* q = (c < 2048 ? reinterpret_cast<const uint32_t*>(p.w2) + (row & 63) * 96 + ((row >> 6) - 1) * 32
                                              : reinterpret_cast<const uint32_t*>(p.wr) + (row & 15) * 96 + ((row >> 4) - 16) * 32) + (j & 4) * 4 + (j & 3);
                v = make_uint4(__ldg(q), __ldg(q + 4), __ldg(q + 8), __ldg(q + 12));
            }
            p.g->wimg[c] = v;
        }
    }
    if (warp < 8 && elect()) {
        mbar_init(bar_full, 32); mbar_init(bar_full + 8, 32);
        mbar_init(bar_empty, 1);
        mbar_init(bar_side, 32);
    }
    if (tid < MAXG) reinterpret_cast<uint32_t*>(smem + SCNT_OFF)[tid] = 0;
    if (tid < 48) misc[tid] = 0;
    {
        const uint32_t inv = (PAY_INVALID << 6) | tag;
        stage4[tid] = stage4[tid + THREADS] = make_uint4(inv, inv, inv, inv);
        if (tid < MAXG * (PITCH / 16) - 2 * THREADS) stage4[tid + 2 * THREADS] = make_uint4(inv, inv, inv, inv);
    }
    if (warp == 15) {
        __syncwarp();
        const int k = lane & (NP - 1), b0 = (k * G + NP - 1) / NP, b1 = ((k + 1) * G + NP - 1) / NP;
        const uint32_t o0 = (b0 * NPC * 4) & ~127u, o1 = k == NP - 1 ? tbytes : (b1 * NPC * 4) & ~127u;
        bool todo = lane < NP, wait = true;
        uint32_t left;
        int it = smem_u32(smem_dyn) == SB ? 0 : 1 << 22;
        do {
            unsigned c;
            asm volatile("ld.relaxed.gpu.global.u32 %0, [%1];" : "=r"(c) : "l"(p.g->sync + 8 + k) : "memory");
            if (todo && c == (epoch + 1) * (b1 - b0)) {
                bulk_g2s(sb + o0, reinterpret_cast<const char*>(p.g->table) + o0, o1 - o0, bar_tab);
                todo = false;
            }
            if (++it > (1 << 22)) __trap();
            left = __ballot_sync(0xffffffffu, todo);
            if (wait && __popc(left) <= NLEFT) {
                asm volatile("bar.arrive 1, 512;" ::: "memory");
                wait = false;
            }
        } while (left);
        asm volatile("bar.sync 2, 512;" ::: "memory");
        TSX(2, 511);
    } else {
        asm volatile("bar.arrive 2, 512;" ::: "memory");
        asm volatile("bar.sync 1, 512;" ::: "memory");
    }
    load_edges(1);
#pragma unroll 1
    for (int r = tid >> 2; r < G; r += THREADS / 4) {
        uint4* const x = p.g->xbuf + (r * G + b) * 4 + (tid & 3);
        stg128_if(x, make_uint4(0, 0, 0, 0), true);
        stg128_if(x + XH, make_uint4(0, 0, 0, 0), ((r ^ epoch) & 15) == 0);
    }
    load_edges(2);
    if (tid == THREADS - 1) asm volatile("fence.acq_rel.gpu;" ::: "memory");
    mbar_wait(bar_tab, 0);
    TS0(3);
    if (warp == 15) warm(0, WA);

    bool over = false;
#pragma unroll 1
    for (int i = 0, g = e0 + tid; i < 3; i++, g += THREADS) {
        const int s[4] = {es[0].x, es[0].y, es[0].z, es[0].w}, d[4] = {ed[0].x, ed[0].y, ed[0].z, ed[0].w};
        uint32_t ca[4], cb[4], own[4], sl[4];
        bool c[4];
#pragma unroll
        for (int j = 0; j < 4; j++) { ca[j] = lds32(sb + 4 * s[j]); cb[j] = lds32(sb + 4 * d[j]); }
#pragma unroll
        for (int j = 0; j < 4; j++) {
            c[j] = near_test(ca[j], cb[j], tag << 24) && g < e1;
            own[j] = __umulhi((uint32_t)d[j], magic);
            sl[j] = atomicAdd(reinterpret_cast<uint32_t*>(smem + SCNT_OFF) + (c[j] ? own[j] : MAXG + lane), 4u);
        }
#pragma unroll
        for (int j = 0; j < 4; j++)
            sts32_if(sb + STAGE_OFF + own[j] * PITCH + sl[j], own[j] * (uint32_t)(-64 * NPC) + (((uint32_t)s[j] << 15) + (((uint32_t)d[j] << 6) + tag)),
                     c[j] && sl[j] < 124);
#pragma unroll
        for (int j = 0; j < 4; j++) over |= c[j] && sl[j] >= 124;
        es[0] = es[1]; es[1] = es[2];
        ed[0] = ed[1]; ed[1] = ed[2];
    }
    {
        const int redo = __syncthreads_or(over);
        if (__builtin_expect(redo || odd_edges, 0)) cold_filter(smem, p, e0, e1, tag, redo);
    }
    TS0(4);
#pragma unroll 1
    for (int r = tid >> 2; r < G; r += THREADS / 4) {
        const int c = r * (PITCH / 16) + (tid & 3);
        uint4* const x = p.g->xbuf + (r * G + b) * 4 + (tid & 3);
        const bool more = reinterpret_cast<uint32_t*>(smem + SCNT_OFF)[r] > 64;
        uint4 v = stage4[c];
        if (more && (tid & 3) == 3) v.w |= 0x80000000u;
        stg128_if(x + XH, stage4[c + 4], more);
        stg128_if(x, v, true);
    }
    ncnt[tid] = 0;
    reinterpret_cast<uint32_t*>(smem + E0_OFF)[tid] = ~0u;
    if (tid < 480) reinterpret_cast<uint32_t*>(smem + SLOT_OFF)[tid] = tid < 32 ? tid * 0x100010 + 0x80000 : tid < 320 ? ~0u : 0u;
    if (tid == 511) reinterpret_cast<uint2*>(smem + NPOS_OFF)[511] = make_uint2(sb + SLOT_OFF + 1278, 0);
    __syncthreads();
    reinterpret_cast<uint4*>(smem + RR_OFF)[tid] = make_uint4(0, 0, 0, 0);
    if (tid < ROUNDS * 80 - THREADS) reinterpret_cast<uint4*>(smem + RR_OFF)[tid + THREADS] = make_uint4(0, 0, 0, 0);
    if (tid < ROUNDS * 32) reinterpret_cast<uint2*>(smem + SRC_OFF)[tid] = make_uint2(~0u, ~0u);
    pause(PDELAY);
    TS0(5);

    uint32_t rxy[4], gz[4], src[4], rk[4], dn[4];
    const uint32_t sink = sb + NCNT_OFF + 4 * (480 + lane);
    if (warp < 15) {
        uint32_t ew[3][4], bad[2];
        const int u = tid - 3 * G;
        const uint4* const xin = p.g->xbuf + b * G * 4;
        const uint4* cp = xin + (u < 0 ? tid + tid / 3 : u * 4 + 3);
        bad[0] = u < G;
        bad[1] = u >= 0 && u + 480 - 3 * G < G;
#pragma unroll
        for (int i = 0; i < 3; i++) ew[i][0] = ew[i][1] = ew[i][2] = ew[i][3] = (PAY_INVALID << 6) | tag;
        int it = 0;
#pragma unroll 1
        do {
#pragma unroll
            for (int i = 0; i < 2; i++)
                asm volatile("{\n.reg .pred p;\nsetp.ne.u32 p, %5, 0;\n@p ld.relaxed.gpu.global.v4.u32 {%0,%1,%2,%3}, [%4];\n}\n"
                             : "+r"(ew[i][0]), "+r"(ew[i][1]), "+r"(ew[i][2]), "+r"(ew[i][3]) : "l"(cp + i * (480 - 3 * G) * 4), "r"(bad[i]) : "memory");
#pragma unroll
            for (int i = 0; i < 2; i++) bad[i] = ((ew[i][0] ^ tag) | (ew[i][1] ^ tag) | (ew[i][2] ^ tag) | (ew[i][3] ^ tag)) & 63u;
            if (++it > (1 << 22)) __trap();
        } while (__any_sync(0xffffffffu, bad[0] | bad[1]));
        if (warp >= (3 * G) >> 5) {
            constexpr int EMPTY = (int)(PAY_MARK << 6);
            const bool e0 = ew[0][0] >= (PAY_MARK << 6);
            if (__builtin_expect(__any_sync(0xffffffffu, min((int)ew[0][3], (int)ew[1][3]) < EMPTY || (!e0 && ew[1][0] < (PAY_MARK << 6))), 0)) {
                uint64_t f = (uint64_t)__ballot_sync(0xffffffffu, (int)ew[1][3] < EMPTY) << 32 | __ballot_sync(0xffffffffu, (int)ew[0][3] < EMPTY);
                if ((int)ew[0][3] < EMPTY) ew[0][3] &= 0x7FFFFFFFu;
                if ((int)ew[1][3] < EMPTY) ew[1][3] &= 0x7FFFFFFFu;
#pragma unroll 1
                for (int k = 7 - (lane >> 2); k && f; k--) f &= f - 1;
                if (f) {
                    const int l = __ffsll(f) - 1;
                    do {
                        asm volatile("ld.relaxed.gpu.global.v4.u32 {%0,%1,%2,%3}, [%4];" : "=r"(ew[2][0]), "=r"(ew[2][1]), "=r"(ew[2][2]), "=r"(ew[2][3])
                                     : "l"(xin + (u - lane + l + (l >> 5) * (448 - 3 * G)) * 4 + XH + (lane & 3)) : "memory");
                        if (++it > (1 << 22)) __trap();
                    } while (((ew[2][0] ^ tag) | (ew[2][1] ^ tag) | (ew[2][2] ^ tag) | (ew[2][3] ^ tag)) & 63u);
                    if ((ew[2][3] >> 6) == PAY_MARK || lane == 0) misc[0] = 1;
                }
                __syncwarp();
#pragma unroll 1
                for (int i = 0; i < 2; i++) {
                    if (ew[0][0] >= (PAY_MARK << 6)) {
#pragma unroll
                        for (int j = 0; j < 4; j++) { ew[0][j] = ew[1][j]; ew[1][j] = ~0u; }
                    }
                    uint32_t from = __ballot_sync(0xffffffffu, ew[1][0] < (PAY_MARK << 6)), to = __ballot_sync(0xffffffffu, ew[0][0] >= (PAY_MARK << 6));
#pragma unroll 1
                    for (; from; from &= from - 1, to &= to - 1) {
                        if (!to) misc[0] = 1;
#pragma unroll
                        for (int j = 0; j < 4; j++) {
                            const uint32_t x = __shfl_sync(0xffffffffu, ew[1][j], __ffs(from) - 1);
                            if (lane == __ffs(to) - 1) ew[0][j] = x;
                        }
                    }
#pragma unroll
                    for (int j = 0; j < 4; j++) ew[1][j] = ew[2][j];
                }
            } else if (e0) {
#pragma unroll
                for (int j = 0; j < 4; j++) ew[0][j] = ew[1][j];
            }
        }
        {
            uint2 ps[4], pd[4];
#pragma unroll
            for (int j = 0; j < 4; j++) {
                dn[j] = (ew[0][j] >> 3) & 4088u;
                src[j] = ew[0][j] >> 15;
                ps[j] = __ldcg(p.g->pos8 + (dn[j] == 4088u ? nbase : src[j]));
            }
#pragma unroll
            for (int j = 0; j < 4; j++) pd[j] = *reinterpret_cast<const uint2*>(smem + OPOS_OFF + dn[j]);
            asm volatile("bar.arrive 1, 512;" ::: "memory");
            float q[4];
#pragma unroll
            for (int j = 0; j < 4; j++) {
                rxy[j] = hsub2(ps[j].x, pd[j].x);
                gz[j] = hsub2(ps[j].y, pd[j].y);
                q[j] = square(rxy[j], gz[j]);
                const bool in = q[j] < QMAX && dn[j] != 4088u;
                rk[j] = atoms_add(in ? sb + NCNT_OFF + (dn[j] >> 1) : sink, 512u);
                if (!in) dn[j] = 4088u;
            }
            uint32_t row[4], n = 0;
            bool single[4];
#pragma unroll
            for (int j = 0; j < 4; j++) {
                q[j] = distance(q[j]);
                row[j] = 0x409D - (__float_as_uint(q[j]) >> 16);
                single[j] = row[j] >= LUTS && dn[j] != 4088u;
                n += single[j];
            }
            n = atoms_add(n ? sb + MISC_OFF + 4 : sink, n) + LUTS;
#pragma unroll
            for (int j = 0; j < 4; j++) {
                float id;
                asm("rcp.approx.ftz.f32 %0, %1;" : "=f"(id) : "f"(q[j]));
                sts32_if(sb + LUT_OFF + min(n, LUTN - 1) * 32, __float_as_uint(q[j]), single[j]);
                if (single[j]) row[j] = n++;
                rxy[j] = pack2(bf_lo(rxy[j]) * id, bf_hi(rxy[j]) * id);
                gz[j] = pack2(0.f, bf_lo(gz[j]) * id) + row[j] * 32;
                sts16_if(sb + E0_OFF + (dn[j] >> 1) + (rk[j] >> 8), src[j], rk[j] < 1024 && dn[j] != 4088u);
            }
        }
    } else {
        const uint4 fq = __ldg(reinterpret_cast<const uint4*>(p.freqs) + (lane & 1));
        rxy[0] = fq.x; rxy[1] = fq.y; rxy[2] = fq.z; rxy[3] = fq.w;
        asm volatile("bar.sync 1, 512;" ::: "memory");
        warm(WA, WC);
    }
    __syncthreads();
    TS0(6);

    const uint32_t lt = (1u << lane) - 1;
    uint32_t place = ~0u, mid = 0, last = 0, steps = 0, c = 0;
    if (warp < 15) {
        if (tid < nn) c = ncnt[tid] >> 9;
        const uint32_t e0w = lds32(sb + E0_OFF + 4 * tid);
        steps = min((c + 1) >> 1, 15u);
        const uint32_t bin = sel(tid >= nn, 9, (uint32_t)(0x11223354678ull >> (4 * min(c, 11u))) & 15), sh = (bin & 1) * 16;
        const bool odd = c > 3 && (c & 1);
        const uint32_t peers = __match_any_sync(0xffffffffu, bin), om = __ballot_sync(0xffffffffu, odd);
        uint32_t x = atoms_add(lane == 0 ? sb + MISC_OFF + 4 * 37 : sink, __popc(om));
        uint32_t r = atoms_add((peers & lt) == 0 ? sb + MISC_OFF + 4 * 32 + 2 * (bin & 14) : sink, __popc(peers) << sh);
        x = __shfl_sync(0xffffffffu, x, 0) + __popc(om & lt);
        r = ((__shfl_sync(0xffffffffu, r, __ffs(peers) - 1) >> sh) & 0xFFFFu) + __popc(peers & lt);
        sts16_if(sb + sel(bin == 8, ZL_OFF, sel(bin == 7, YL_OFF, TL_OFF)) + 2 * r, tid, (0x190 >> bin) & 1);
        const uint64_t ones = 0x0001010101010101ull >> (56 - 8 * min(bin, 7u));
        asm volatile("bar.sync 2, 480;" ::: "memory");
        uint32_t h[4];
        lds128(sb + MISC_OFF + 4 * 32, h);
        const int nodd = misc[37], n1 = h[3] >> 16, n3 = h[2] & 0xFFFF, left = max(min(nodd + n3 - n1, n3), 0), half = left >> 1;
        const bool twin = bin == 4 && (int)r < 2 * half;
        x = sel(bin == 4, nodd + r - left, sel(odd, x, 1023));
        const bool pair = twin ? !(r & 1) : (int)x >= (bin == 4 ? nodd : 0) && (int)x < n1;
        const uint32_t y = lds16(sel(twin, sb + TL_OFF + 2 + 2 * r, sb + YL_OFF + 2 * (x & 511)));
        const uint32_t base = __dp2a_lo(h[0], (uint32_t)ones, __dp2a_hi(h[1], (uint32_t)ones, 0u)) +
                              __dp2a_lo(h[2], (uint32_t)(ones >> 32), __dp2a_hi(h[3], (uint32_t)(ones >> 32), 0u));
        r -= sel(bin == 7, nodd + n3, 0);
        const bool unit = (bin < 8 && (int)r >= 0 && (pair || !twin));
        place = sel(unit, base + sel(twin, r >> 1, r - sel(bin < 4, 0, half)), ~0u);
        place = sel(place < 64, (place >> 1) + (place & 1) * 32, place);
        sts16_if(sb + SRC_OFF + 2 * place, e0w, place < 64);
        sts16_if(sb + SRC_OFF + 128 + 2 * place, e0w >> 16, place < 64);
        sts32_if(sb + MISC_OFF + 16, base - half + max(n1 - nodd - n3, 0), bin >= 7);
        steps += twin;
        last = sel(twin, y, tid) | sel(steps > 1, ST_CLOSE, ST_CLOSE | ST_START);
        mid = sel(pair, y | sel(twin, ST_MID, ST_MID | ST_CLOSE) | (tid << 16), last);
        c = sel(pair, c, 2 * steps - 1);
        const uint32_t sa = sb + SLOT_OFF + sel(steps <= ROUNDS, 2 * place, 1278);
        sts64_if(sb + NPOS_OFF + 8 * tid, sa, 0, unit);
        sts64_if(sb + NPOS_OFF + 8 * y, sa, c << 9, pair);
        asm volatile("{\n.reg .pred p;\nsetp.ne.u32 p, %2, 0;\n@p st.shared.u8 [%0], %1;\n}\n" ::"r"(sb + SIZE_OFF + place), "r"(steps), "r"((uint32_t)unit) : "memory");
    } else {
        if (elect()) {
            if (b == 0) p.g->sync[0] = epoch + 1;
            asm volatile("fence.proxy.async.global;" ::: "memory");
            mbar_expect_tx(bar_tab, WIMG + LUTS * 32);
            bulk_g2s(sb, p.g->wimg, WIMG, bar_tab);
            bulk_g2s(sb + LUT_OFF, p.g->wimg + WIMG / 16, LUTS * 32, bar_tab);
        }
        warm(WA + WC, WE);
#pragma unroll 1
        for (uint32_t i = lane; i - lane < 2 * min(misc[1], LUTN - LUTS); i += 32) {
            const uint32_t d = lds32(sb + LUT_OFF + (LUTS + (i >> 1)) * 32);
            __syncwarp();
            reinterpret_cast<uint4*>(smem + LUT_OFF)[2 * LUTS + i] = basis8(__uint_as_float(d), make_uint4(rxy[0], rxy[1], rxy[2], rxy[3]));
        }
        TSX(12, 511);
    }
    __syncthreads();
    TS0(7);
    uint32_t st[4];
    if (warp == 15) {
        uint32_t until0 = lds16(sb + SIZE_OFF + 2 * lane), until1 = until0 >> 8, next = 64, s0, s1;
        const uint32_t nsched = misc[4];
        until0 &= 255;
        uint32_t t = __reduce_min_sync(0xffffffffu, min(until0, until1));
        bool go = true;
#pragma unroll 1
        while (go) {
            go = t < ROUNDS && next < nsched;
            const bool n0 = until0 == t, n1 = until1 == t;
            const uint32_t i = next + __popc(__ballot_sync(0xffffffffu, n0) & lt) + __popc(__ballot_sync(0xffffffffu, n1) & lt), j = i + n0;
            next += __reduce_add_sync(0xffffffffu, n0 + n1);
            asm volatile("{\n.reg .pred p, q;\nsetp.ne.u32 p, %4, 0;\nsetp.ne.u32 q, %5, 0;\nmov.u32 %0, 0;\nmov.u32 %1, 0;\n@p ld.shared.u8 %0, [%2];\n@q ld.shared.u8 %1, [%3];\n}\n"
                         : "=&r"(s0), "=&r"(s1) : "r"(sb + SIZE_OFF + i), "r"(sb + SIZE_OFF + j), "r"((uint32_t)n0), "r"((uint32_t)n1) : "memory");
            until0 += s0;
            until1 += s1;
            sts16_if(sb + SLOT_OFF + 2 * i, 1024 * t + 16 * lane, n0 && until0 <= ROUNDS);
            sts16_if(sb + SLOT_OFF + 2 * j, 1024 * t + 16 * lane + 8, n1 && until1 <= ROUNDS);
            t++;
        }
        until0 = __reduce_max_sync(lane < 16 ? 0xFFFFu : 0xFFFF0000u, max(until0, until1));
        if ((lane & 15) == 0) misc[2 + (lane >> 4)] = until0;
        __syncthreads();
        lds128(sb + MISC_OFF, st);
    } else {
        if (warp < 8) {
            const int s = lane >> 3, c = lane & 7;
            const uint32_t dst = sb + RING_OFF + warp * 16384 + s * 128, y = sb + SRC_OFF + (warp * 8 + s) * 2;
            const uint32_t sdst = dst + ((c ^ s) << 4), vdst = dst + ((c ^ ((s & 1) << 2)) << 4);
            const uint32_t s0 = lds16(y), s1 = lds16(y + 8), s2 = lds16(y + 128), s3 = lds16(y + 136);
            const char* svl = reinterpret_cast<const char*>(p.sv) + c * 16;
            gather_s(sdst, svl, s0);
            gather_s((sdst ^ 64) + 512, svl, s1);
            gather_s(sdst + 8192, svl, s2);
            gather_s((sdst ^ 64) + 8704, svl, s3);
            cp_async_arrive(bar_full);
            TS0(10);
            pause(warp & 4 ? P1W : P0);
            gather_v(vdst, svl, s0);
            pause(P0);
            gather_v(vdst + 512, svl, s1);
            pause(P0);
            gather_v(vdst + 8192, svl, s2);
            pause(P0);
            gather_v(vdst + 8704, svl, s3);
            asm volatile("cp.async.mbarrier.arrive.shared::cta.b64 [%0];" ::"r"(bar_side) : "memory");
        }
#pragma unroll
        for (int j = 0; j < 4; j++) {
            const uint2 np = *reinterpret_cast<const uint2*>(smem + NPOS_OFF + dn[j]);
            dn[j] = np.x;
            rk[j] += np.y;
        }
        __syncthreads();
        TS0(8);
        lds128(sb + MISC_OFF, st);
        uint32_t e[4];
#pragma unroll
        for (int j = 0; j < 4; j++) e[j] = lds16(dn[j]);
        const uint32_t x = lds16(sb + SLOT_OFF + 2 * min(place, 639u));
#pragma unroll
        for (int j = 0; j < 4; j++) {
            sts16_if(sb + SRC_OFF + ((rk[j] + e[j]) >> 2), src[j], e[j] != 0xFFFFu);
            sts64_if(sb + RR_OFF + rk[j] + e[j], rxy[j], gz[j], e[j] != 0xFFFFu);
        }
        const uint32_t nd = sb + ND_OFF + ((x >> 2) & 0xFF00) + ((x >> 1) & 0xFC);
        sts32_if(nd, tid | ST_START, x != 0xFFFFu);
        sts32_if(nd + steps * 256 - 256, last, x != 0xFFFFu && steps <= ROUNDS);
        sts32_if(nd + c * 128 - 128, mid, x != 0xFFFFu && steps <= ROUNDS);
    }
    __syncthreads();
    if (__builtin_expect(max(st[2], st[3]) > ROUNDS || st[1] > LUTN - LUTS || st[0], 0)) {
        asm volatile("cp.async.wait_all;" ::: "memory");
        mbar_wait(bar_tab, 1);
        mbar_wait(bar_tab + 8, 0);
        cold_nodes(smem, p, nn, tag);
        return;
    }
    TS0(9);
    const int T = __shfl_sync(0xffffffffu, warp & 4 ? st[3] : st[2], 0);

    if (warp < 8) {
        asm volatile("setmaxnreg.inc.sync.aligned.u32 %0;" ::"n"(REG_C));
        const int lane = fresh_lane();
        const int g = lane >> 2, q = lane & 3;
        const uint64_t d0 = (uint64_t)__shfl_sync(0xffffffffu, pin((uint32_t)(p.desc0 >> 32)), 0) << 32 | __shfl_sync(0xffffffffu, pin((uint32_t)p.desc0), 0);
        const uint32_t swz = g * 128 + ((q ^ ((g & 1) << 2)) << 4);
        const uint32_t srow = pin(sb + SIDE_OFF + warp * 4096 + swz);
        uint32_t vrow = pin(sb + RING_OFF + warp * 16384 + swz + 4096);
        uint32_t ent = pin(sb + RR_OFF + (warp * 8 + g) * 8), fent = pin(sb + ND_OFF + (warp * 8 + g) * 4);
        uint32_t lent = pin(sb + RR_OFF + (warp * 8 + (lane & 7)) * 8 + 4 + (lane & 8) * 64);
        const uint32_t lutq = pin(sb + LUT_OFF + (lane >> 4) * 16);
        uint64_t outq;
        {
            const uint64_t a = reinterpret_cast<uint64_t>(p.out) + (size_t)nbase * 512 + q * 16;
            const uint32_t lo = pin((uint32_t)a), hi = pin((uint32_t)(a >> 32));
            asm volatile("mov.b64 %0, {%1, %2};" : "=l"(outq) : "r"(lo), "r"(hi));
        }
        uint32_t acc[32], rf[4], h[16], rr[4], fl = 0;
#pragma unroll
        for (int i = 0; i < 32; i++) asm volatile("" : "=r"(acc[i]));
#pragma unroll
        for (int i = 0; i < 16; i++) asm volatile("" : "=r"(h[i]));
#pragma unroll
        for (int i = 0; i < 4; i++) asm volatile("" : "=r"(rf[i]), "=r"(rr[i]));
        int t = -1;
        TSX(18, 0);
        mbar_wait(bar_tab, 1);
        TSX(14, 0);
        const int Tm = __shfl_sync(0xffffffffu, min(st[2], st[3]), 0);
        if (warp >= 4 && Tm > 0) asm volatile("bar.arrive 3, 256;" ::: "memory");
        bool more = T < 0x7FFFFFFF;
#pragma unroll 1
        while (more) {
            float y[32], p1[32], w1[32], p2[32], w2[32], p3[32], w3[32];
            uint32_t m1[16], m2[16], v[3][16], ts[8];
            auto products = [](uint32_t* m, const float* P, const float* W) {
#pragma unroll
                for (int j = 0; j < 8; j++) {
                    m[j] = pack2(P[4 * j] * W[4 * j], P[4 * j + 1] * W[4 * j + 1]);
                    m[8 + j] = pack2(P[4 * j + 2] * W[4 * j + 2], P[4 * j + 3] * W[4 * j + 3]);
                }
            };
            auto vterm = [&](int k, int o) {
#pragma unroll
                for (int j = 0; j < 8; j++) acc[8 * k + 8 + j] = hfma2(m1[o + j], v[k][o + j], acc[8 * k + 8 + j]);
            };
            auto rterm = [&](int k, int o) {
#pragma unroll
                for (int j = 0; j < 8; j++)
                    acc[8 * k + 8 + j] = k == 0 ? hfma2_lo(m2[o + j], rr[o / 4], acc[8 * k + 8 + j]) : hfma2_hi(m2[o + j], rr[o / 4 + k / 2], acc[8 * k + 8 + j]);
            };
            TR(0, 0, t);
            uint64_t om, op;
#pragma unroll
            for (int j = 0; j < 8; j++) asm volatile("" : "=r"(ts[j]), "=r"(m1[8 + j]), "=r"(m2[8 + j]), "=r"(v[0][8 + j]), "=r"(v[1][8 + j]), "=r"(v[2][8 + j]));
            asm volatile("" : "=l"(om));
            if (t >= 0) {
            TC(0);
            if (t < Tm) asm volatile("bar.sync %0, 256;" ::"r"(3 + (warp >> 2)) : "memory");
            wg_fence();
            wgmma_rs2<W2_OFF + 8192, 8192, 0>(p1, p2, h, d0);
            wgmma_rs2<W2_OFF + 10240, 8192, 1>(p1, p2, h + 4, d0);
            wgmma_rs2<W2_OFF + 12288, 8192, 1>(p1, p2, h + 8, d0);
            wgmma_rs2<W2_OFF + 14336, 8192, 1>(p1, p2, h + 12, d0);
            wgmma_rs2<WR_OFF + 2048, 2048, 0>(w1, w2, rf, d0);
            wg_commit();
            TC(1);
            mbar_wait(bar_side, t & 1);
            TC(2);
#pragma unroll
            for (int k = 0; k < 4; k++) lds2_if(srow + 1024 * k, (srow ^ 64) + 1024 * k, acc + 8 * k, fl & ST_START);
            wg_wait<0>();
            fence_regs(p1); fence_regs(w1);
            TC(3);
            products(m1, p1, w1);
#pragma unroll
            for (int k = 0; k < 3; k++) { lds128(vrow + 1024 + 1024 * k, v[k]); lds128((vrow ^ 64) + 1024 + 1024 * k, v[k] + 4); }
            fence_regs(p2); fence_regs(w2);
            products(m2, p2, w2);
            asm("mad.wide.u32 %0, %1, 512, %2;" : "=l"(om) : "r"(fl >> 16), "l"(outq));
#pragma unroll
            for (int k = 0; k < 3; k++) { lds128(vrow + 9216 + 1024 * k, v[k] + 8); lds128((vrow ^ 64) + 9216 + 1024 * k, v[k] + 12); }
#pragma unroll
            for (int j = 0; j < 8; j++) asm volatile("" : "=r"(ts[j]));
            lds2_if(srow, srow ^ 64, ts, fl & ST_MID);
#pragma unroll
            for (int k = 0; k < 3; k++) { vterm(k, 0); rterm(k, 0); stg2_if(om + 128 + 128 * k, acc + 8 + 8 * k, fl & ST_MID); }
            TC(4);
            if (t + (warp >> 2) < Tm) asm volatile("bar.arrive %0, 256;" ::"r"(4 - (warp >> 2)) : "memory");
            }
            t++;
            wg_fence();
            wgmma_group<0>(p3, w3, h, rf, d0);
            wg_commit();
            if (T > 1000000) asm volatile("nanosleep.u32 0;");
#pragma unroll
            for (int k = 1; k < 4; k++) lds2_if(srow + 1024 * k, (srow ^ 64) + 1024 * k, acc + 8 * k, fl & ST_MID);
            uint32_t lo;
            asm volatile("ld.shared.u16 %0, [%1];" : "=r"(lo) : "r"(lent) : "memory");
            __syncwarp();
            if (lane == 0 && t > 0) mbar_arrive(bar_empty);
            if (t > 0) TC(5);
            if (t >= T) {
                asm("mad.wide.u32 %0, %1, 512, %2;" : "=l"(op) : "r"(fl & 511), "l"(outq));
#pragma unroll
                for (int k = 0; k < 3; k++) { vterm(k, 8); rterm(k, 8); stg2_if(op + 128 + 128 * k, acc + 8 + 8 * k, fl & ST_CLOSE); }
                wg_wait<0>();
                fence_regs(p3); fence_regs(w3);
                products(m1, p3, w3);
#pragma unroll
                for (int j = 0; j < 8; j++) acc[j] = hadd2(acc[j], m1[j]);
                stg2_if(om, acc, fl & ST_MID);
#pragma unroll
                for (int j = 0; j < 8; j++) acc[j] = hadd2(fl & ST_MID ? ts[j] : acc[j], m1[8 + j]);
                stg2_if(op, acc, fl & ST_CLOSE);
                asm volatile("cp.async.wait_all;" ::: "memory");
                break;
            }
            mbar_wait(bar_full + 8 * (t & 1), (t >> 1) & 1);
            if (t > 0) TC(6);
            wg_fence();
            wgmma_ss_k64(y, d0 + ((RING_OFF >> 4) + (warp >> 2) * 4096 + (t & 1) * 256 + ((uint64_t)(512 - 64) << 32)), d0);
            wg_commit();
            if (T > 1000000) asm volatile("nanosleep.u32 0;");
            asm("mad.wide.u32 %0, %1, 512, %2;" : "=l"(op) : "r"(fl & 511), "l"(outq));
            vrow ^= 4096;
#pragma unroll
            for (int k = 0; k < 3; k++) vterm(k, 8);
#define BBS if (T > 1000000) asm volatile("nanosleep.u32 0;")
            auto silu = [&](int i0, int i1) {
#pragma unroll
                for (int i = i0; i < i1; i++)
                    h[i] = pack2(fmaf(y[2 * i], tanh_fast(y[2 * i]), y[2 * i]), fmaf(y[2 * i + 1], tanh_fast(y[2 * i + 1]), y[2 * i + 1]));
            };
#pragma unroll
            for (int k = 0; k < 3; k++) rterm(k, 8);
            const uint32_t fo = fl;
            asm volatile("ld.shared.v2.u32 {%0,%1}, [%4];\nld.shared.v2.u32 {%2,%3}, [%4 + 512];" : "=r"(rr[0]), "=r"(rr[1]), "=r"(rr[2]), "=r"(rr[3]) : "r"(ent) : "memory");
            asm volatile("ld.shared.u32 %0, [%1];" : "=r"(fl) : "r"(fent) : "memory");
            stg2_if(op + 128, acc + 8, fo & ST_CLOSE);
            BBS;
            if (t > 0) TC(7);
            wg_wait<0>();
            fence_regs(p3); fence_regs(w3); fence_regs(y);
            if (t > 0) TC(8);
            ldsm4(lutq + lo, rf);
            products(m1, p3, w3);
            silu(0, 6);
            stg2_if(op + 256, acc + 16, fo & ST_CLOSE);
            BBS;
#pragma unroll
            for (int j = 0; j < 8; j++) acc[j] = hadd2(acc[j], m1[j]);
            stg2_if(om, acc, fo & ST_MID);
#pragma unroll
            for (int j = 0; j < 8; j++) acc[j] = hadd2(fo & ST_MID ? ts[j] : acc[j], m1[8 + j]);
            silu(6, 11);
            stg2_if(op + 384, acc + 24, fo & ST_CLOSE);
            BBS;
            silu(11, 16);
            stg2_if(op, acc, fo & ST_CLOSE);
            ent += 1024; fent += 256; lent += 1024;
        }
        TSX(15, 0);
        TSX(16, 128);
    } else {
        asm volatile("setmaxnreg.dec.sync.aligned.u32 %0;" ::"n"(256 - REG_C));
        const int lane = fresh_lane();
        const int w = warp - 8, s = lane >> 3, c = lane & 7, nzero = misc[36] & 0xFFFF;
        uint32_t sdst = sb + RING_OFF + w * 16384 + s * 128 + ((c ^ s) << 4);
        const uint32_t sw = s * 128 + ((c ^ ((s & 1) << 2)) << 4);
        uint32_t vdst = sb + RING_OFF + w * 16384 + sw;
        const uint32_t odst = sb + SIDE_OFF + w * 4096 + sw;
        uint32_t ent = sb + ND_OFF + (w * 8 + s) * 4;
        const char* svl = reinterpret_cast<const char*>(p.sv) + c * 16;
        const char* own = svl + (size_t)nbase * 512;
        pause((warp & 4 ? LAG1 : 0) + LAG * max(min(16 - (int)(misc[2] + misc[3]), 2), 0));
#pragma unroll 1
        for (int t = 1; t <= T; t++) {
            const uint32_t e = sb + SRC_OFF + t * 256 + (w * 8 + s) * 2;
            const uint32_t s0 = lds16(e), s1 = lds16(e + 8), s2 = lds16(e + 128), s3 = lds16(e + 136);
            const uint32_t f0 = lds32(ent), f1 = lds32(ent + 16);
            ent += 256;
            sdst ^= 4096; vdst ^= 4096;
            TR(5, 256, t);
            mbar_wait(bar_empty, t & 1);
            TR(6, 256, t);
            gather_row_if(odst, own + (f0 & 511) * 512, f0 & (ST_START | ST_MID));
            gather_row_if(odst + 512, own + (f1 & 511) * 512, f1 & (ST_START | ST_MID));
            cp_async_arrive(bar_side);
            if (t == T) break;
            gather_s(sdst, svl, s0);
            gather_s((sdst ^ 64) + 512, svl, s1);
            gather_s(sdst + 8192, svl, s2);
            gather_s((sdst ^ 64) + 8704, svl, s3);
            cp_async_arrive(bar_full + 8 * (t & 1));
            gather_v(vdst, svl, s0);
            gather_v(vdst + 512, svl, s1);
            gather_v(vdst + 8192, svl, s2);
            gather_v(vdst + 8704, svl, s3);
            TR(7, 256, t);
        }
        TSX(17, 256);
        TSX(20, 384);
        const uint32_t rb = sb + RING_OFF + w * 16384 + (max(T, 1) & 1) * 4096 + s * 512 + c * 16;
#pragma unroll 1
        for (int z = (w & 3) + ((w >> 2) == (misc[2] > misc[3]) ? 0 : 48); z < nzero; z += 96) {
            const int n = (nzero - z + 3) >> 2;
            uint32_t zn[3];
#pragma unroll
            for (int i = 0; i < 3; i++) zn[i] = lds16(sb + ZL_OFF + 2 * min(z + 16 * i + 4 * s, 511));
#pragma unroll
            for (int i = 0; i < 3; i++)
                asm volatile("{\n.reg .pred p;\nsetp.lt.s32 p, %2, %3;\n@p cp.async.cg.shared.global [%0], [%1], 16;\n@p cp.async.cg.shared.global [%0 + 128], [%1 + 128], 16;\n"
                             "@p cp.async.cg.shared.global [%0 + 256], [%1 + 256], 16;\n@p cp.async.cg.shared.global [%0 + 384], [%1 + 384], 16;\n}\n"
                             ::"r"(rb + (i & 1) * 2048 + (i >> 1) * 8192), "l"(own + zn[i] * 512), "r"(4 * i + s), "r"(n) : "memory");
            TSX(21, 256);
            asm volatile("cp.async.wait_all;" ::: "memory");
            TSX(22, 256);
#pragma unroll
            for (int i = 0; i < 3; i++) {
                if (4 * i < n) {
                    char* dst = reinterpret_cast<char*>(p.out) + (size_t)(nbase + zn[i]) * 512 + c * 16;
#pragma unroll
                    for (int k = 0; k < 4; k += 2) {
                        uint32_t x[8];
                        lds128(rb + (i & 1) * 2048 + (i >> 1) * 8192 + k * 128, x);
                        lds128(rb + (i & 1) * 2048 + (i >> 1) * 8192 + k * 128 + 128, x + 4);
                        if (4 * i + s < n) {
                            __stcs(reinterpret_cast<uint4*>(dst + k * 128), make_uint4(x[0], x[1], x[2], x[3]));
                            __stcs(reinterpret_cast<uint4*>(dst + k * 128 + 128), make_uint4(x[4], x[5], x[6], x[7]));
                        }
                    }
                }
            }
        }
        mbar_wait(bar_tab + 8, 0);
        TSX(11, 256);
        TSX(19, 384);
    }
}

}

extern "C" void kernel_launch(void* const* d_in, const int* in_sizes, int n_in, void* d_out, int out_size) {
    static int s_G = 0;
    static void* s_scratch = nullptr;
    static void* s_encode = nullptr;
    const int N = in_sizes[0] / 256, E = in_sizes[2];
    if (s_G == 0) {
        cudaFuncSetAttribute(painn_kernel<0, 0, 0>, cudaFuncAttributeMaxDynamicSharedMemorySize, SMEM_BYTES);
        cudaFuncSetAttribute(painn_kernel<50000, 800000, 132>, cudaFuncAttributeMaxDynamicSharedMemorySize, SMEM_BYTES);
        int dev = 0, sms = 0, occ = 0;
        cudaGetDevice(&dev);
        cudaDeviceGetAttribute(&sms, cudaDevAttrMultiProcessorCount, dev);
        cudaOccupancyMaxActiveBlocksPerMultiprocessor(&occ, painn_kernel<0, 0, 0>, THREADS, SMEM_BYTES);
        cudaGetSymbolAddress(&s_scratch, g_scratch);
        cudaDriverEntryPointQueryResult qr;
        cudaGetDriverEntryPoint("cuTensorMapEncodeTiled", &s_encode, cudaEnableDefault, &qr);
        s_G = occ >= 1 ? (sms < MAXG ? sms : MAXG) : 0;
    }
    if (s_G == 0 || N > TABLE_MAXN || N > s_G * (MAXNPC - 1) || (s_G - 1) * ((N + s_G - 1) / s_G) >= N || E > MAXE || E < 4 * MAXG * MAXG) return;
    Params p;
    CUtensorMap tm;
    {
        typedef CUresult (*Encode)(CUtensorMap*, CUtensorMapDataType, cuuint32_t, void*, const cuuint64_t*, const cuuint64_t*, const cuuint32_t*,
                                   const cuuint32_t*, CUtensorMapInterleave, CUtensorMapSwizzle, CUtensorMapL2promotion, CUtensorMapFloatOOBfill);
        const cuuint64_t dims[2] = {64, (cuuint64_t)N * 4}, strides[1] = {128};
        const cuuint32_t box[2] = {8, 32}, es[2] = {1, 1};
        ((Encode)s_encode)(&tm, CU_TENSOR_MAP_DATA_TYPE_BFLOAT16, 2, d_in[0], dims, strides, box, es, CU_TENSOR_MAP_INTERLEAVE_NONE,
                           CU_TENSOR_MAP_SWIZZLE_NONE, CU_TENSOR_MAP_L2_PROMOTION_L2_128B, CU_TENSOR_MAP_FLOAT_OOB_FILL_NONE);
    }
    p.g = (Scratch*)s_scratch;
    p.sv = (const __nv_bfloat16*)d_in[0];
    p.pos = (const __nv_bfloat16*)d_in[1];
    p.src = (const int*)d_in[2];
    p.dst = (const int*)d_in[3];
    p.freqs = (const __nv_bfloat16*)d_in[4];
    p.w1 = (const __nv_bfloat16*)d_in[5];
    p.w2 = (const __nv_bfloat16*)d_in[6];
    p.wr = (const __nv_bfloat16*)d_in[7];
    p.out = (__nv_bfloat16*)d_out;
    p.desc0 = (uint64_t)(SB >> 4) | ((uint64_t)1 << 16) | ((uint64_t)64 << 32) | ((uint64_t)1 << 62);
    p.N = N; p.E = E; p.G = s_G;
    p.NPC = (N + s_G - 1) / s_G;
    p.magic = (uint32_t)(((1ull << 32) + p.NPC - 1) / p.NPC);
    p.gpc = ((E >> 2) + s_G - 1) / s_G;
    p.odd_edges = (E & 3) != 0 || p.gpc > 3 * THREADS;
    if (N == 50000 && E == 800000 && s_G == 132) painn_kernel<50000, 800000, 132><<<s_G, THREADS, SMEM_BYTES, cudaStreamPerThread>>>(p, tm);
    else painn_kernel<0, 0, 0><<<s_G, THREADS, SMEM_BYTES, cudaStreamPerThread>>>(p, tm);
}
```
